```python
import torch

def _softmax(x, axis=-1):
    return torch.softmax(x, dim=axis)

def _gelu(x):
    return torch.nn.functional.gelu(x, approximate='tanh')

def _silu(x):
    return torch.nn.functional.silu(x)

def _sigmoid(x):
    return torch.sigmoid(x)

def _layernorm(x, axis=-1, eps=1e-05):
    m = x.mean(dim=axis, keepdim=True)
    v = x.var(dim=axis, keepdim=True, unbiased=False)
    return (x - m) / torch.sqrt(v + eps)

def _scatter_add(tgt, idx, src, axis=0):
    return tgt.clone().index_add_(axis, idx, src)

def _segment_sum(src, seg, n):
    out = torch.zeros((n,) + src.shape[1:], dtype=src.dtype)
    return out.index_add_(0, seg, src)

def _pad(x, pw):
    flat = tuple((v for pair in reversed(pw) for v in pair))
    return torch.nn.functional.pad(x, flat)
kernel_name = 'gated_mix__memory_aug_recurrent_mem_tr__sliding_local_dilated__prompt'

def setup_inputs():

    _w = lambda a: (lambda t: t.to(torch.bfloat16) if t.is_floating_point() else t)(torch.as_tensor(a))

    def _A_setup():
        B, S, Dm = (1, 2048, 640)
        H, Dh = (32, 192)
        M, seg = (8, 32)
        seg = min(seg, S)
        S = S // seg * seg
        return {'x': _w((lambda *s: torch.randn(*s, dtype=torch.bfloat16) * 0.05)(B, S, Dm)), 'mem0': _w((lambda *s: torch.randn(*s, dtype=torch.bfloat16) * 1.6)(B, M, Dm)), 'Wq': _w((lambda *s: torch.randn(*s, dtype=torch.bfloat16) * 0.8)(Dm, H, Dh) * Dm ** (-0.5)), 'Wk': _w((lambda *s: torch.randn(*s, dtype=torch.bfloat16) * 0.8)(Dm, H, Dh) * Dm ** (-0.5)), 'Wv': _w((lambda *s: torch.randn(*s, dtype=torch.bfloat16) * 1.6)(Dm, H, Dh) * Dm ** (-0.5)), 'Wo': _w((lambda *s: torch.randn(*s, dtype=torch.bfloat16) * 1.6)(H, Dh, Dm) * (H * Dh) ** (-0.5)), 'seg_len': seg}
    _A_in = _A_setup()

    def _B_setup():
        B, S, D = (1, 2048, 640)
        return {'x': _w((lambda *s: torch.randn(*s, dtype=torch.bfloat16) * 0.05)(B, S, D)), 'wqkv': _w((lambda *s: torch.randn(*s, dtype=torch.bfloat16) * 0.8)(D, 3 * D)), 'wo': _w((lambda *s: torch.randn(*s, dtype=torch.bfloat16) * 0.05)(D, D))}
    _B_in = _B_setup()
    return {'A_x': _A_in['x'], 'A_mem0': _A_in['mem0'], 'A_Wq': _A_in['Wq'], 'A_Wk': _A_in['Wk'], 'A_Wv': _A_in['Wv'], 'A_Wo': _A_in['Wo'], 'A_seg_len': _A_in['seg_len'], 'B_x': _B_in['x'], 'B_wqkv': _B_in['wqkv'], 'B_wo': _B_in['wo'], 'gate_w': _w((lambda *s: torch.randn(*s, dtype=torch.bfloat16) * 0.05)(640) * 16.0)}

def reference(A_x, A_mem0, A_Wq, A_Wk, A_Wv, A_Wo, A_seg_len, B_x, B_wqkv, B_wo, gate_w):

    def _A_ref(x, mem0, Wq, Wk, Wv, Wo, seg_len):
        B, S, Dm = x.shape
        H, Dh = (Wq.shape[1], Wq.shape[2])
        M = mem0.shape[1]
        scale = Dh ** (-0.5)
        n_seg = S // seg_len
        L = M + seg_len
        idx = torch.arange(L)
        mask = (idx[:, None] < M) | (idx[:, None] >= idx[None, :])
        mem = mem0
        outs = []
        for s in range(n_seg):
            xs = x[:, s * seg_len:(s + 1) * seg_len, :].clone()
            h = torch.concatenate([mem, xs], axis=1)
            q = torch.einsum('btd,dhe->bhte', h, Wq)
            k = torch.einsum('btd,dhe->bhte', h, Wk)
            v = torch.einsum('btd,dhe->bhte', h, Wv)
            scores = torch.einsum('bhqe,bhke->bhqk', q, k) * scale
            scores = torch.where(mask[None, None], scores, -1000000000.0)
            p = _softmax(scores, axis=-1)
            o = torch.einsum('bhqk,bhke->bhqe', p, v)
            o = torch.einsum('bhte,hed->btd', o, Wo)
            mem = o[:, :M, :].clone()
            outs.append(o[:, M:, :])
        return torch.concatenate(outs, axis=1)

    def _B_ref(x, wqkv, wo):
        B, S, D = x.shape
        H = 32
        Dh = D // H
        W, dil = (8, 2)
        qkv = (lambda x, *d: x.permute(*d))((x @ wqkv).reshape(B, S, 3, H, Dh), 2, 0, 3, 1, 4)
        q, k, v = (qkv[0], qkv[1], qkv[2])
        scale = Dh ** (-0.5)
        pos = torch.arange(S)
        off = torch.arange(W) * dil
        idx = pos[:, None] - off[None, :]
        mask = idx >= 0
        idx_c = torch.where(mask, idx, 0).reshape(-1)
        kg = k[:, :, idx_c, :].reshape(B, H, S, W, Dh)
        vg = v[:, :, idx_c, :].reshape(B, H, S, W, Dh)
        logits = torch.einsum('bhsd,bhswd->bhsw', q, kg) * scale
        logits = torch.where(mask[None, None, :, :], logits, -1000000000.0)
        attn = _softmax(logits, axis=-1)
        o = torch.einsum('bhsw,bhswd->bhsd', attn, vg)
        return (lambda x, *d: x.permute(*d))(o, 0, 2, 1, 3).reshape(B, S, D) @ wo
    x = A_x
    g = _sigmoid((x * gate_w).sum(-1, keepdims=True))
    a = _A_ref(x, A_mem0, A_Wq, A_Wk, A_Wv, A_Wo, A_seg_len)
    b = _B_ref(x, B_wqkv, B_wo)
    return g * a + (1 - g) * b
```

```cpp
#include <cuda_runtime.h>
#include <cuda_bf16.h>
#include <cuda.h>
#include <stdint.h>
#include <type_traits>

typedef __nv_bfloat16 bf16;

namespace {

constexpr int S_TOK = 2048, DM = 640, NH = 32, DH = 192, HD = NH * DH, SEG = 32, NSEG = 64, MT = 8, LK = 40;
constexpr int SPIN_MAX = 1 << 20;

constexpr int NCAND = 8;
constexpr int NFCAND = 16;
constexpr int COMM_CHUNKS = 80 * NCAND + NFCAND;
__device__ __align__(4096) unsigned char g_comm[COMM_CHUNKS * 4096];
__device__ uint32_t g_tab[96];
__device__ uint32_t g_epoch;
__device__ uint32_t g_err;
__device__ uint32_t g_segcnt[NSEG];
__device__ __align__(1024) bf16 g_K[NSEG * LK * HD];
__device__ __align__(1024) bf16 g_V[NSEG * LK * HD];

__device__ __forceinline__ uint32_t smem_u32(const void* p) { return (uint32_t)__cvta_generic_to_shared(p); }
__device__ __forceinline__ uint32_t clk32() { uint32_t t; asm volatile("mov.u32 %0, %%clock;" : "=r"(t)::"memory"); return t; }
__device__ __forceinline__ uint32_t mapa(uint32_t a, uint32_t r) { uint32_t o; asm("mapa.shared::cluster.u32 %0, %1, %2;" : "=r"(o) : "r"(a), "r"(r)); return o; }
__device__ __forceinline__ void mbar_init(uint32_t b, uint32_t c) { asm volatile("mbarrier.init.shared::cta.b64 [%0], %1;" ::"r"(b), "r"(c) : "memory"); }
__device__ __forceinline__ void mbar_expect(uint32_t b, uint32_t bytes) { asm volatile("mbarrier.arrive.expect_tx.shared::cta.b64 _, [%0], %1;" ::"r"(b), "r"(bytes) : "memory"); }
__device__ __forceinline__ void mbar_arrive(uint32_t b) { asm volatile("mbarrier.arrive.shared::cta.b64 _, [%0];" ::"r"(b) : "memory"); }
__device__ __forceinline__ bool mbar_try(uint32_t b, uint32_t par) {
  uint32_t p;
  asm volatile("{.reg .pred p; mbarrier.try_wait.parity.shared::cta.b64 p, [%1], %2; selp.u32 %0,1,0,p;}" : "=r"(p) : "r"(b), "r"(par) : "memory");
  return p;
}
__device__ __forceinline__ bool mbar_try_cl(uint32_t b, uint32_t par) {
  uint32_t p;
  asm volatile("{.reg .pred p; mbarrier.try_wait.parity.acquire.cluster.shared::cta.b64 p, [%1], %2; selp.u32 %0,1,0,p;}" : "=r"(p) : "r"(b), "r"(par) : "memory");
  return p;
}
__device__ __forceinline__ void mbar_wait(uint32_t b, uint32_t par) {
  int n = 0;
#pragma unroll 1
  while (!mbar_try(b, par)) { if (++n > SPIN_MAX) { g_err = 1; break; } }
}
__device__ __forceinline__ void mbar_wait_cl(uint32_t b, uint32_t par) {
  int n = 0;
#pragma unroll 1
  while (!mbar_try_cl(b, par)) { if (++n > SPIN_MAX) { g_err = 2; break; } }
}
__device__ __forceinline__ void cluster_sync() { asm volatile("barrier.cluster.arrive.release.aligned; barrier.cluster.wait.acquire.aligned;" ::: "memory"); }
__device__ __forceinline__ void bar_sync(int id, int n) { asm volatile("bar.sync %0, %1;" ::"r"(id), "r"(n) : "memory"); }
__device__ __forceinline__ void bar_arrive(int id, int n) { asm volatile("bar.arrive %0, %1;" ::"r"(id), "r"(n) : "memory"); }
__device__ __forceinline__ void fence_async_smem() { asm volatile("fence.proxy.async.shared::cta;" ::: "memory"); }
__device__ __forceinline__ void ldsm4(uint32_t* r, uint32_t a) {
  asm volatile("ldmatrix.sync.aligned.m8n8.x4.shared.b16 {%0,%1,%2,%3}, [%4];" : "=r"(r[0]), "=r"(r[1]), "=r"(r[2]), "=r"(r[3]) : "r"(a) : "memory");
}
__device__ __forceinline__ void ldsm4t(uint32_t* r, uint32_t a) {
  asm volatile("ldmatrix.sync.aligned.m8n8.x4.trans.shared.b16 {%0,%1,%2,%3}, [%4];" : "=r"(r[0]), "=r"(r[1]), "=r"(r[2]), "=r"(r[3]) : "r"(a) : "memory");
}
__device__ __forceinline__ void ldsm2t(uint32_t* r, uint32_t a) {
  asm volatile("ldmatrix.sync.aligned.m8n8.x2.trans.shared.b16 {%0,%1}, [%2];" : "=r"(r[0]), "=r"(r[1]) : "r"(a) : "memory");
}
__device__ __forceinline__ void stsm4t(uint32_t a, uint32_t r0, uint32_t r1, uint32_t r2, uint32_t r3) {
  asm volatile("stmatrix.sync.aligned.m8n8.x4.trans.shared.b16 [%0], {%1,%2,%3,%4};" ::"r"(a), "r"(r0), "r"(r1), "r"(r2), "r"(r3) : "memory");
}
__device__ __forceinline__ void stsm2t(uint32_t a, uint32_t r0, uint32_t r1) {
  asm volatile("stmatrix.sync.aligned.m8n8.x2.trans.shared.b16 [%0], {%1,%2};" ::"r"(a), "r"(r0), "r"(r1) : "memory");
}
__device__ __forceinline__ uint32_t movmat(uint32_t a) { uint32_t d; asm volatile("movmatrix.sync.aligned.m8n8.trans.b16 %0, %1;" : "=r"(d) : "r"(a)); return d; }
__device__ __forceinline__ void mma16816(float* d, const uint32_t* a, uint32_t b0, uint32_t b1) {
  asm volatile("mma.sync.aligned.m16n8k16.row.col.f32.bf16.bf16.f32 {%0,%1,%2,%3}, {%4,%5,%6,%7}, {%8,%9}, {%0,%1,%2,%3};"
               : "+f"(d[0]), "+f"(d[1]), "+f"(d[2]), "+f"(d[3]) : "r"(a[0]), "r"(a[1]), "r"(a[2]), "r"(a[3]), "r"(b0), "r"(b1));
}
__device__ __forceinline__ void mma1688(float* d, uint32_t a0, uint32_t a1, uint32_t b0) {
  asm volatile("mma.sync.aligned.m16n8k8.row.col.f32.bf16.bf16.f32 {%0,%1,%2,%3}, {%4,%5}, {%6}, {%0,%1,%2,%3};"
               : "+f"(d[0]), "+f"(d[1]), "+f"(d[2]), "+f"(d[3]) : "r"(a0), "r"(a1), "r"(b0));
}
__device__ __forceinline__ uint32_t pack2(float lo, float hi) { uint32_t r; asm("cvt.rn.bf16x2.f32 %0, %1, %2;" : "=r"(r) : "f"(hi), "f"(lo)); return r; }
__device__ __forceinline__ float bf_lo(uint32_t w) { return __uint_as_float(w << 16); }
__device__ __forceinline__ float bf_hi(uint32_t w) { return __uint_as_float(w & 0xffff0000u); }
__device__ __forceinline__ float ex2(float x) { float y; asm("ex2.approx.ftz.f32 %0, %1;" : "=f"(y) : "f"(x)); return y; }
__device__ __forceinline__ void sts128(uint32_t a, uint32_t x, uint32_t y, uint32_t z, uint32_t w) { asm volatile("st.shared.v4.b32 [%0], {%1,%2,%3,%4};" ::"r"(a), "r"(x), "r"(y), "r"(z), "r"(w) : "memory"); }
__device__ __forceinline__ void sts128f(uint32_t a, float x, float y, float z, float w) { asm volatile("st.shared.v4.f32 [%0], {%1,%2,%3,%4};" ::"r"(a), "f"(x), "f"(y), "f"(z), "f"(w) : "memory"); }
__device__ __forceinline__ void sts64f(uint32_t a, float x, float y) { asm volatile("st.shared.v2.f32 [%0], {%1,%2};" ::"r"(a), "f"(x), "f"(y) : "memory"); }
__device__ __forceinline__ void sts32(uint32_t a, uint32_t x) { asm volatile("st.shared.b32 [%0], %1;" ::"r"(a), "r"(x) : "memory"); }
__device__ __forceinline__ uint32_t lds32(uint32_t a) { uint32_t v; asm volatile("ld.shared.b32 %0, [%1];" : "=r"(v) : "r"(a) : "memory"); return v; }
__device__ __forceinline__ float4 lds128f(uint32_t a) { float4 v; asm volatile("ld.shared.v4.f32 {%0,%1,%2,%3}, [%4];" : "=f"(v.x), "=f"(v.y), "=f"(v.z), "=f"(v.w) : "r"(a) : "memory"); return v; }
__device__ __forceinline__ uint4 lds128(uint32_t a) { uint4 v; asm volatile("ld.shared.v4.b32 {%0,%1,%2,%3}, [%4];" : "=r"(v.x), "=r"(v.y), "=r"(v.z), "=r"(v.w) : "r"(a) : "memory"); return v; }
__device__ __forceinline__ float2 lds64f(uint32_t a) { float2 v; asm volatile("ld.shared.v2.f32 {%0,%1}, [%2];" : "=f"(v.x), "=f"(v.y) : "r"(a) : "memory"); return v; }
__device__ __forceinline__ void st_async2(uint32_t a, uint32_t x, uint32_t y, uint32_t bar) {
  asm volatile("st.async.weak.shared::cluster.mbarrier::complete_tx::bytes.v2.b32 [%0], {%1,%2}, [%3];" ::"r"(a), "r"(x), "r"(y), "r"(bar) : "memory");
}
__device__ __forceinline__ void st_async4(uint32_t a, uint32_t x, uint32_t y, uint32_t z, uint32_t w, uint32_t bar) {
  asm volatile("st.async.weak.shared::cluster.mbarrier::complete_tx::bytes.v4.b32 [%0], {%1,%2,%3,%4}, [%5];" ::"r"(a), "r"(x), "r"(y), "r"(z), "r"(w), "r"(bar) : "memory");
}
__device__ __forceinline__ void sts64(uint32_t a, uint32_t x, uint32_t y) { asm volatile("st.shared.v2.b32 [%0], {%1,%2};" ::"r"(a), "r"(x), "r"(y) : "memory"); }
__device__ __forceinline__ bool bar_red_or(int id, int n, bool q) {
  uint32_t r;
  asm volatile("{.reg .pred p, q; setp.ne.u32 q, %3, 0; barrier.cta.red.or.aligned.pred p, %1, %2, q; selp.u32 %0,1,0,p;}" : "=r"(r) : "r"(id), "r"(n), "r"((uint32_t)q) : "memory");
  return r;
}
__device__ __forceinline__ float rcp(float x) { float y; asm("rcp.approx.ftz.f32 %0, %1;" : "=f"(y) : "f"(x)); return y; }
__device__ __forceinline__ uint32_t hadd2(uint32_t a, uint32_t b) { uint32_t r; asm("add.rn.bf16x2 %0, %1, %2;" : "=r"(r) : "r"(a), "r"(b)); return r; }
__device__ __forceinline__ uint32_t pin(uint32_t v) { asm volatile("" : "+r"(v)); return v; }
__device__ __forceinline__ uint32_t opaque(uint32_t v) { return __shfl_sync(~0u, v, threadIdx.x & 31); }
__device__ __forceinline__ uint4 ldg_rlx128(const void* p) {
  uint4 v; asm volatile("ld.relaxed.gpu.global.v4.b32 {%0,%1,%2,%3}, [%4];" : "=r"(v.x), "=r"(v.y), "=r"(v.z), "=r"(v.w) : "l"(p) : "memory"); return v;
}
__device__ __forceinline__ uint32_t ldg_rlx32(const void* p) {
  uint32_t v; asm volatile("ld.relaxed.gpu.global.b32 %0, [%1];" : "=r"(v) : "l"(p) : "memory"); return v;
}
__device__ __forceinline__ void spin_until(uint32_t t0, uint32_t d) {
#pragma unroll 1
  while (clk32() - t0 < d) {}
}
__device__ __forceinline__ void stg_rlx64(void* p, uint32_t a, uint32_t b) {
  asm volatile("{.reg .b64 t; mov.b64 t, {%1,%2}; st.relaxed.gpu.global.b64 [%0], t;}" ::"l"(p), "r"(a), "r"(b) : "memory");
}
__device__ __forceinline__ uint32_t ldg_acq32(const void* p) { uint32_t v; asm volatile("ld.acquire.gpu.global.b32 %0, [%1];" : "=r"(v) : "l"(p) : "memory"); return v; }
__device__ __forceinline__ void stg_rel32(void* p, uint32_t v) { asm volatile("st.release.gpu.global.b32 [%0], %1;" ::"l"(p), "r"(v) : "memory"); }
__device__ __forceinline__ void cp_async16(uint32_t dst, const void* src) { asm volatile("cp.async.cg.shared.global [%0], [%1], 16;" ::"r"(dst), "l"(src) : "memory"); }
__device__ __forceinline__ void cp_async_wait_all() { asm volatile("cp.async.wait_all;" ::: "memory"); }
__device__ __forceinline__ void prefetch_l2(const void* p) { asm volatile("prefetch.global.L2 [%0];" ::"l"(p)); }
__device__ __forceinline__ void tma_load3(uint32_t dst, const CUtensorMap* tm, int c0, int c1, int c2, uint32_t bar) {
  asm volatile("cp.async.bulk.tensor.3d.shared::cluster.global.mbarrier::complete_tx::bytes [%0], [%1, {%3,%4,%5}], [%2];"
               ::"r"(dst), "l"(tm), "r"(bar), "r"(c0), "r"(c1), "r"(c2) : "memory");
}
__device__ __forceinline__ void tma_load2(uint32_t dst, const CUtensorMap* tm, int c0, int c1, uint32_t bar) {
  asm volatile("cp.async.bulk.tensor.2d.shared::cluster.global.mbarrier::complete_tx::bytes [%0], [%1, {%3,%4}], [%2];"
               ::"r"(dst), "l"(tm), "r"(bar), "r"(c0), "r"(c1) : "memory");
}
__device__ __forceinline__ void tma_store2(const CUtensorMap* tm, uint32_t src, int c0, int c1) {
  asm volatile("cp.async.bulk.tensor.2d.global.shared::cta.bulk_group [%0, {%2,%3}], [%1];" ::"l"(tm), "r"(src), "r"(c0), "r"(c1) : "memory");
}
__device__ __forceinline__ void bulk_commit() { asm volatile("cp.async.bulk.commit_group;" ::: "memory"); }
__device__ __forceinline__ void bulk_wait0() { asm volatile("cp.async.bulk.wait_group 0;" ::: "memory"); }
__device__ __forceinline__ void bulk_wait_read0() { asm volatile("cp.async.bulk.wait_group.read 0;" ::: "memory"); }
__device__ __forceinline__ void wg_fence() { asm volatile("wgmma.fence.sync.aligned;" ::: "memory"); }
__device__ __forceinline__ void wg_commit() { asm volatile("wgmma.commit_group.sync.aligned;" ::: "memory"); }
__device__ __forceinline__ void wg_wait0() { asm volatile("wgmma.wait_group.sync.aligned 0;" ::: "memory"); }
__device__ __forceinline__ uint64_t desc_sw128(uint32_t addr) {
  return (uint64_t)((addr & 0x3FFFF) >> 4) | ((uint64_t)1 << 16) | ((uint64_t)64 << 32) | ((uint64_t)1 << 62);
}
template <int ACC>
__device__ __forceinline__ void wgmma_rs32(float* d, const uint32_t* a, uint64_t db) {
  asm volatile("{.reg .pred p; setp.ne.b32 p, %21, 0;\n"
               "wgmma.mma_async.sync.aligned.m64n32k16.f32.bf16.bf16 {%0,%1,%2,%3,%4,%5,%6,%7,%8,%9,%10,%11,%12,%13,%14,%15}, {%16,%17,%18,%19}, %20, p, 1, 1, 0;}"
               : "+f"(d[0]), "+f"(d[1]), "+f"(d[2]), "+f"(d[3]), "+f"(d[4]), "+f"(d[5]), "+f"(d[6]), "+f"(d[7]), "+f"(d[8]), "+f"(d[9]),
                 "+f"(d[10]), "+f"(d[11]), "+f"(d[12]), "+f"(d[13]), "+f"(d[14]), "+f"(d[15])
               : "r"(a[0]), "r"(a[1]), "r"(a[2]), "r"(a[3]), "l"(db), "n"(ACC));
}

constexpr int NPQ = 2;
#define NQ0 10
#define NQ1 12
#define NO_EARLY 6
#define WN1 14
#define PD0 1450
#define PD1 280
#define PW0 700
#define NQ_WIN 4
constexpr int NQM = NQ0 > NQ1 ? NQ0 : NQ1;
constexpr int R_WQ = 0;
constexpr int R_WO = R_WQ + 8 * (20 - NPQ) * 512;
constexpr int R_XT = R_WO + 14 * 12 * 512;
constexpr int R_QB = R_XT + 40960;
constexpr int R_KB = R_QB + 1024;
constexpr int R_QA = R_KB + 1024;
constexpr int R_KT = R_QA + 1024;
constexpr int R_VT = R_KT + 5120;
constexpr int R_MEM = R_VT + 5120;
constexpr int R_SX = R_MEM + 10240;
constexpr int R_O2 = R_SX + 3840;
constexpr int R_RB = R_O2 + 1024;
constexpr int R_TAB = R_RB + 2048;
constexpr int R_BAR = R_TAB + 384;
constexpr int R_MISC = R_BAR + 64;
constexpr int R_SMEM = R_MISC + 128;
static_assert(R_XT % 1024 == 0 && R_KT % 1024 == 0 && R_VT % 1024 == 0, "align");
constexpr int R_SMEM_ALLOC = R_SMEM;
static_assert(R_SMEM_ALLOC <= 232448, "smem");

#define TR(i) do {} while (0)

__device__ __forceinline__ int probe_lat(unsigned char* p) {
  int best = 1 << 30;
  uint32_t v = 0;
#pragma unroll 1
  for (int r = 0; r < 4; r++) {
    uint32_t t0 = clk32();
    asm volatile("atom.relaxed.gpu.global.exch.b32 %0, [%1], %2;" : "=r"(v) : "l"(p + (v & 0)), "r"(0u) : "memory");
    uint32_t t1 = clk32() + (v & 0);
    if (v == 0x12345678u) t1++;
    best = min(best, (int)(t1 - t0));
  }
  return best;
}

__global__ void __cluster_dims__(3, 1, 1) __launch_bounds__(256, 1)
rec_kernel(const __grid_constant__ CUtensorMap tmX, const __grid_constant__ CUtensorMap tmK, const __grid_constant__ CUtensorMap tmV,
           const bf16* __restrict__ Wq, const bf16* __restrict__ Wk, const bf16* __restrict__ Wv, const bf16* __restrict__ Wo,
           const bf16* __restrict__ mem0) {
  extern __shared__ __align__(1024) unsigned char smem[];
  const uint32_t sb = smem_u32(smem);
  const int tid = threadIdx.x, lane = tid & 31, wid = __shfl_sync(~0u, tid >> 5, 0), g = wid >> 2, w = wid & 3;
  const int cta = blockIdx.x, head = cta / 3, rank = cta % 3;
  const int D0 = head * DH + rank * 64;
  const int tile0 = rank == 0 ? 0 : (rank == 1 ? 14 : 27), ntile = rank == 0 ? 14 : 13;
  const uint32_t XBAR = sb + R_BAR, SBAR = XBAR + 8, OBAR = XBAR + 16;
  const uint32_t epoch = (*(volatile uint32_t*)&g_epoch + 1) & 0xFFFFF;

  if (tid == 0) {
    mbar_init(XBAR, 1); mbar_init(SBAR, 1); mbar_init(OBAR, 1);
    asm volatile("fence.mbarrier_init.release.cluster;" ::: "memory");
  }
  {
    const int c = tid & 7, kr = tid >> 3;
#pragma unroll 4
    for (int i = 0; i < 20; i++) {
      const int k = kr + 32 * i, gg = k / 320, f = (k % 320) >> 4;
      const uint32_t o = ((gg * 4 + (c >> 1)) * 20 + f) * 512 + ((c & 1) + 2 * ((k >> 3) & 1)) * 128 + (k & 7) * 16;
      const size_t go = (size_t)k * HD + D0 + c * 8;
      cp_async16(sb + o, Wk + go);
      cp_async16(sb + 81920 + o, Wv + go);
      if (f < NPQ) cp_async16(sb + 163840 + ((gg * 4 + (c >> 1)) * NPQ + f) * 512 + ((c & 1) + 2 * ((k >> 3) & 1)) * 128 + (k & 7) * 16, Wq + go);
    }
    for (int k = tid; k < 640; k += 256) prefetch_l2(Wq + (size_t)k * HD + D0);
    for (int i = tid; i < 192 * 4; i += 256) prefetch_l2(Wo + (size_t)(head * DH + (i >> 2)) * DM + tile0 * 16 + min((i & 3) * 64, ntile * 16 - 8));
  }
  if (cta < 80 || cta == 80) {
    const int nc = cta < 80 ? 1 : 2;
    for (int j = 0; j < nc; j++) {
      const int ch = cta < 80 ? cta * NCAND + wid : 80 * NCAND + wid * 2 + j;
      if (lane == 0) {
        unsigned char* p = g_comm + (size_t)ch * 4096;
        *(volatile uint32_t*)p = 0;
        sts32(sb + R_MISC + (wid * nc + j) * 4, (uint32_t)probe_lat(p));
      }
    }
    __syncthreads();
    if (cta < 80) {
      int best = 1 << 30, bc = 0;
      for (int j = 0; j < NCAND; j++) { int l = (int)lds32(sb + R_MISC + j * 4); if (l < best) { best = l; bc = j; } }
      const int ch = cta * NCAND + bc;
      *(uint4*)(g_comm + (size_t)ch * 4096 + tid * 16) = make_uint4(0, 0, 0, 0);
      __threadfence();
      __syncthreads();
      if (tid == 0) stg_rel32(&g_tab[cta], (epoch << 12) | ch);
    } else {
      int mn = 1 << 30, mx = 0;
      for (int j = 0; j < NFCAND; j++) { int l = (int)lds32(sb + R_MISC + j * 4); mn = min(mn, l); mx = max(mx, l); }
      const int thr = (mn + mx) >> 1;
      uint32_t near = 0;
      for (int j = 0; j < NFCAND; j++) if ((int)lds32(sb + R_MISC + j * 4) <= thr) near |= 1u << j;
      uint32_t far = ~near & ((1u << NFCAND) - 1);
      while (__popc(near) < 3) { const uint32_t t = 1u << (31 - __clz(far)); far ^= t; near |= t; }
      while (__popc(far) < 3) { const uint32_t t = 1u << (31 - __clz(near)); near ^= t; far |= t; }
      int mine = 0;
#pragma unroll 1
      for (int q = 0; q < 6; q++) {
        const int c = __fns(q < 3 ? near : far, 0, q % 3 + 1);
        *(uint4*)(g_comm + (size_t)(80 * NCAND + c) * 4096 + tid * 16) = make_uint4(0, 0, 0, 0);
        if (q == tid) mine = c;
      }
      __threadfence();
      __syncthreads();
      if (tid < 6) stg_rel32(&g_tab[80 + tid], (epoch << 12) | (80 * NCAND + mine));
    }
  }
  cp_async_wait_all();
  __syncthreads();
  uint32_t wk[20][4], wv[20][4], wqp[NPQ][4];
#pragma unroll
  for (int f = 0; f < 20; f++) { ldsm4t(wk[f], sb + (wid * 20 + f) * 512 + lane * 16); ldsm4t(wv[f], sb + 81920 + (wid * 20 + f) * 512 + lane * 16); }
#pragma unroll
  for (int f = 0; f < NPQ; f++) ldsm4t(wqp[f], sb + 163840 + (wid * NPQ + f) * 512 + lane * 16);
  fence_async_smem();
  __syncthreads();
  if (tid == 0) { mbar_expect(XBAR, 40960); tma_load3(sb + R_XT, &tmX, 0, 0, 0, XBAR); }
  {
    const int c = tid & 7, kr = tid >> 3;
#pragma unroll 4
    for (int i = 0; i < 20; i++) {
      const int k = kr + 32 * i, gg = k / 320, f = (k % 320) >> 4;
      if (f >= NPQ)
        cp_async16(sb + R_WQ + ((gg * 4 + (c >> 1)) * (20 - NPQ) + (f - NPQ)) * 512 + ((c & 1) + 2 * ((k >> 3) & 1)) * 128 + (k & 7) * 16,
                   Wq + (size_t)k * HD + D0 + c * 8);
    }
    const int nch = ntile * 2;
#pragma unroll 1
    for (int p = tid; p < 192 * nch; p += 256) {
      const int j = p / nch, cc = p % nch;
      cp_async16(sb + R_WO + ((cc >> 1) * 12 + ((j >> 4) + 12 - 4 * rank) % 12) * 512 + ((cc & 1) + 2 * ((j >> 3) & 1)) * 128 + (j & 7) * 16,
                 Wo + (size_t)(head * DH + j) * DM + tile0 * 16 + cc * 8);
    }
  }
  if (tid < 86) {
    uint32_t e; int n = 0;
    while (((e = ldg_acq32(&g_tab[tid])) >> 12) != epoch) { if (++n > SPIN_MAX) { g_err = 3; break; } }
    sts32(sb + R_TAB + tid * 4, (e & 0xFFF) * 4096u);
  }
  __syncthreads();
  if (wid < 2 && lane == 0) sts32(sb + R_MISC + wid * 4, (uint32_t)probe_lat(g_comm + lds32(sb + R_TAB + (80 + wid * 3 + 2) * 4) + 2048 + (cta & 15) * 128));
  cp_async_wait_all();
  __syncthreads();
  if (tid < 3) {
    const int cp = lds32(sb + R_MISC) <= lds32(sb + R_MISC + 4) ? 0 : 1;
    sts32(sb + R_TAB + (86 + tid) * 4, lds32(sb + R_TAB + (80 + cp * 3 + tid) * 4));
    if (tid < 2) {
      const int hh = cta / 40, ix = cta % 40;
      sts32(sb + R_TAB + (90 + tid) * 4, ix < 32 ? lds32(sb + R_TAB + (80 + tid * 3 + hh) * 4) + ix * 128
                                                 : lds32(sb + R_TAB + (80 + tid * 3 + 2) * 4) + hh * 1024 + (ix - 32) * 128);
    }
  }
  cluster_sync();

  const uint32_t rF_ = opaque(sb + lane * 16);
  const uint32_t rM_ = opaque(sb + R_MEM + g * 5120 + (lane >> 3) * 128 + (((lane & 7) ^ (((lane >> 3) & 1) << 2)) << 4));
  const uint32_t rP_ = opaque(sb + (lane >> 4) * 1024 + (lane & 7) * 128 + (((2 * w + ((lane >> 3) & 1)) ^ (lane & 7)) << 4));
  const uint32_t rA_ = opaque(sb + R_MEM + g * 5120 + (((tid & 127) >> 4) * 2 + ((tid >> 2) & 1)) * 128 +
                             (((((tid >> 3) & 1) * 4 + (tid & 3)) ^ (((tid >> 2) & 1) << 2)) << 4));
  const uint32_t rD1_ = opaque(sb + ((lane & 8) ? R_QB : R_QA) + (lane & 7) * 128 + (((lane >> 4) ^ (lane & 7)) << 4));
  const uint32_t rD2_ = opaque(sb + R_KT + (w == 0 ? -2048 : 2048 * w - 1024) + (lane & 7) * 128 + (((lane >> 3) ^ (lane & 7)) << 4));
  const bool isred = cta < 80;
  const int tA = g == 1 ? 2 * w : (rank == 0 ? (w < 2 ? 8 + 2 * w : 10 + w) : (w == 0 ? 8 : 9 + w));
  const bool two = g == 1 || w == 0 || (w == 1 && rank == 0);
  const uint32_t r1 = rank == 2 ? 0 : rank + 1, r2 = rank == 0 ? 2 : rank - 1;
  const uint32_t oA_ = opaque(lds32(sb + R_TAB + (tile0 + tA) * 8 + (lane >> 4) * 4) + head * 128 + (lane & 15) * 8);
  const uint32_t oB_ = opaque(lds32(sb + R_TAB + (tile0 + tA) * 8 + 8 + (lane >> 4) * 4) + head * 128 + (lane & 15) * 8);
  uint32_t wqt[NQM][4];
  int s = -1;

#define ISSUE(G, i) do { const int j_ = (i) >> 1; \
      const uint64_t d_ = ((uint64_t)0x40000040 << 32) | (dlo + (((G) * 20480 + (j_ >> 2) * 4096 + (j_ & 3) * 32) >> 4)); \
      if ((i) & 1) { if (j_ == 0) wgmma_rs32<0>(dv, wv[j_], d_); else wgmma_rs32<1>(dv, wv[j_], d_); } \
      else { if (j_ == 0) wgmma_rs32<0>(dk, wk[j_], d_); else wgmma_rs32<1>(dk, wk[j_], d_); } } while (0)

  auto window = [&](auto G_, auto FIRST_) {
    constexpr int G = decltype(G_)::value;
    constexpr bool FIRST = decltype(FIRST_)::value;
    constexpr int NQ = G ? NQ1 : NQ0;
    const uint32_t t0 = clk32();
    const uint32_t rF = pin(rF_), rP = pin(rP_), rA = pin(rA_);
    const uint32_t tag = (s & 1) ^ 1;
    float dk[16], dv[16];
    const uint32_t dlo = pin(((sb + R_XT) >> 4) | 0x10000);
    const uint32_t wqS = rF + R_WQ + wid * (20 - NPQ) * 512;
    const uint32_t xa = rF + R_XT + w * 512;
    if constexpr (G == 1) {
      const bool duty = isred && !FIRST;
      mbar_wait(XBAR, (s + 1) & 1);
      wg_fence();
#pragma unroll
      for (int i = 0; i < WN1; i++) ISSUE(1, i);
      wg_commit();
      const uint32_t ln = (rF - sb) >> 4;
      const unsigned char* rp = g_comm + (lds32(sb + R_TAB + cta * 4) + w * 1024 + ln * 4);
      uint32_t x[8];
#pragma unroll
      for (int j = 0; j < 8; j++) x[j] = 0;
      if (duty) {
        spin_until(t0, PD1);
#pragma unroll
        for (int j = 0; j < 8; j++) x[j] = ldg_rlx32(rp + j * 128);
      }
      TR(9);
      wg_fence();
#pragma unroll
      for (int i = WN1; i < 40; i++) ISSUE(1, i);
      wg_commit();
      if (duty) {
        unsigned char* fp = g_comm + (lds32(sb + R_TAB + (90 + (ln & 1)) * 4) + (ln >> 1) * 8);
        const uint32_t sa = sb + R_RB + w * 256 + (((ln & 1) * 4 + (ln >> 3)) * 4 + ((ln >> 1) & 3)) * 8;
        int n = 0;
#pragma unroll 1
        while (true) {
          const uint32_t bad = ((((x[0] ^ tag) | (x[1] ^ tag)) | ((x[2] ^ tag) | (x[3] ^ tag))) | (((x[4] ^ tag) | (x[5] ^ tag)) | ((x[6] ^ tag) | (x[7] ^ tag)))) & 1;
          const float lo = ((bf_lo(x[0]) + bf_lo(x[1])) + (bf_lo(x[2]) + bf_lo(x[3]))) + ((bf_lo(x[4]) + bf_lo(x[5])) + (bf_lo(x[6]) + bf_lo(x[7])));
          const float hi = ((bf_hi(x[0]) + bf_hi(x[1])) + (bf_hi(x[2]) + bf_hi(x[3]))) + ((bf_hi(x[4]) + bf_hi(x[5])) + (bf_hi(x[6]) + bf_hi(x[7])));
          sts64f(sa, lo, hi);
          if (!__any_sync(~0u, bad)) break;
#pragma unroll
          for (int j = 0; j < 8; j++) x[j] = ldg_rlx32(rp + j * 128);
          if (++n > SPIN_MAX) { g_err = 4; break; }
        }
        TR(10);
        if (w == 0) {
          bar_sync(2, 128);
          const uint32_t a = sb + R_RB + (ln >> 1) * 16;
          const float4 p0 = lds128f(a), p1 = lds128f(a + 256), p2 = lds128f(a + 512), p3 = lds128f(a + 768);
          const uint32_t w0 = pack2((p0.x + p1.x) + (p2.x + p3.x), (p0.y + p1.y) + (p2.y + p3.y));
          const uint32_t w1 = pack2((p0.z + p1.z) + (p2.z + p3.z), (p0.w + p1.w) + (p2.w + p3.w));
          stg_rlx64(fp, (w0 & ~1u) | tag, w1);
        } else {
          bar_arrive(2, 128);
        }
        TR(11);
      }
      wg_wait0();
#pragma unroll
      for (int q = 0; q < 4; q++) sts128f(xa + 20480 + q * 2048, dv[4 * q], dv[4 * q + 1], dv[4 * q + 2], dv[4 * q + 3]);
#pragma unroll
      for (int f = 0; f < NQ - 4; f++) ldsm4t(wqt[f], wqS + f * 512);
    } else {
      if (!FIRST) {
        fence_async_smem();
        if (w == 3) {
          const uint32_t a = rF + (rF - sb);
          const uint4 a0 = lds128(a + R_KT), a1 = lds128(a + R_KT + 16), c0 = lds128(a + R_KB), c1 = lds128(a + R_KB + 16);
          sts128(a + R_KT, hadd2(a0.x, c0.x), hadd2(a0.y, c0.y), hadd2(a0.z, c0.z), hadd2(a0.w, c0.w));
          sts128(a + R_KT + 16, hadd2(a1.x, c1.x), hadd2(a1.y, c1.y), hadd2(a1.z, c1.z), hadd2(a1.w, c1.w));
          fence_async_smem();
          bar_sync(4, 128);
          if (rF == sb) {
            if (s > 0) {
              bulk_wait0();
              asm volatile("red.relaxed.gpu.global.add.u32 [%0], 1;" ::"l"(&g_segcnt[s - 1]) : "memory");
            }
            tma_store2(&tmK, sb + R_KT, D0, s * LK);
            tma_store2(&tmV, sb + R_VT, D0, s * LK);
            bulk_commit();
          }
          __syncwarp();
        } else {
          bar_arrive(4, 128);
        }
      }
#pragma unroll
      for (int f = 0; f < NQ_WIN; f++) ldsm4t(wqt[f], wqS + f * 512);
      mbar_wait(XBAR, (s + 1) & 1);
      if (!FIRST) spin_until(t0, PW0);
      wg_fence();
#pragma unroll
      for (int i = 0; i < 40; i++) ISSUE(0, i);
      wg_commit();
      if (!FIRST && w == 3) { if (rF == sb) bulk_wait_read0(); __syncwarp(); }
    }
    const unsigned char* yp = g_comm + (lds32(sb + R_TAB + 86 * 4 + G * 4) + (rF - sb) + w * 512);
    const unsigned char* yp2 = g_comm + (lds32(sb + R_TAB + 88 * 4) + (rF - sb) + w * 512 + G * 1024);
    uint4 y0, y1, y2;
    if (!FIRST) {
      spin_until(t0, PD0);
      y0 = ldg_rlx128(yp);
      y1 = ldg_rlx128(yp + 2048);
      y2 = make_uint4(tag, 0, tag, 0);
      if (w < 2) y2 = ldg_rlx128(yp2);
    }
    TR(13);
    if constexpr (G == 0) {
      wg_wait0();
#pragma unroll
      for (int q = 0; q < 4; q++) sts128f(xa + q * 2048, dk[4 * q], dk[4 * q + 1], dk[4 * q + 2], dk[4 * q + 3]);
    }
    TR(12);
    __syncthreads();
    {
      const float* d = G ? dk : dv;
      uint32_t pk[8];
#pragma unroll
      for (int q = 0; q < 4; q++) {
        const float4 o = lds128f(xa + (G ^ 1) * 20480 + q * 2048);
        pk[2 * q] = pack2(d[4 * q] + o.x, d[4 * q + 1] + o.y); pk[2 * q + 1] = pack2(d[4 * q + 2] + o.z, d[4 * q + 3] + o.w);
      }
      stsm4t(rP + (G == 0 ? R_VT : R_KT) + 1024, pk[0], pk[1], pk[2], pk[3]);
      stsm4t(rP + (G == 0 ? R_VT : R_KT) + 3072, pk[4], pk[5], pk[6], pk[7]);
    }
#pragma unroll
    for (int f = (G ? NQ - 4 : NQ_WIN); f < NQ; f++) ldsm4t(wqt[f], wqS + f * 512);
    TR(14);
    if (FIRST) {
      const int i = tid & 127, col = G * 320 + (i >> 4) * 16 + ((i >> 2) & 1) * 8 + ((i >> 3) & 1) * 4 + (i & 3);
      const unsigned short* m = (const unsigned short*)mem0 + col;
#pragma unroll 1
      for (int j = 0; j < (w < 2 ? 3 : 2); j++) {
        uint32_t v[4];
#pragma unroll
        for (int q = 0; q < 4; q++) v[q] = (uint32_t)m[(2 * q) * DM + j * 128] | ((uint32_t)m[(2 * q + 1) * DM + j * 128] << 16);
        sts128(rA + j * 2048, v[0], v[1], v[2], v[3]);
      }
    } else {
      int n = 0;
#pragma unroll 1
      while (true) {
        sts128(rA, y0.x, y0.y, y0.z, y0.w);
        sts128(rA + 2048, y1.x, y1.y, y1.z, y1.w);
        if (w < 2) sts128(rA + 4096, y2.x, y2.y, y2.z, y2.w);
        const uint32_t b0 = (y0.x ^ tag) | (y0.z ^ tag), b1 = (y1.x ^ tag) | (y1.z ^ tag), b2 = (y2.x ^ tag) | (y2.z ^ tag);
        if (!__any_sync(~0u, (b0 | b1 | b2) & 1)) break;
        if (b0 & 1) y0 = ldg_rlx128(yp);
        if (b1 & 1) y1 = ldg_rlx128(yp + 2048);
        if (b2 & 1) y2 = ldg_rlx128(yp2);
        if (++n > SPIN_MAX) { g_err = 5; break; }
      }
    }
    TR(0);
    bar_sync(5 + G, 128);
  };

  auto oproj = [&](auto TWO_, uint32_t (&wot)[12][4], const uint32_t rF, const uint32_t woA, auto&& between) {
    constexpr bool TWO = decltype(TWO_)::value;
    const uint32_t tag = (s & 1) ^ 1;
    float c[4][4];
#pragma unroll
    for (int q = 0; q < 4; q++) c[q][0] = c[q][1] = c[q][2] = c[q][3] = 0.f;
    unsigned char* spA = g_comm + pin(oA_);
    unsigned char* spB = g_comm + pin(oB_);
    bar_sync(3, 256);
    uint4 ob[6];
    ob[0] = lds128(rF + R_QB); ob[1] = lds128(rF + R_QB + 512);
    between();
#pragma unroll
    for (int p = 0; p < 6; p++) {
      if (p == 2) {
        mbar_wait(OBAR, s & 1);
        TR(8);
        ob[2] = lds128(rF + R_QA); ob[3] = lds128(rF + R_QA + 512); ob[4] = lds128(rF + R_O2); ob[5] = lds128(rF + R_O2 + 512);
      }
#pragma unroll
      for (int e = 0; e < 2; e++) {
        const int ks = 2 * p + e;
        const uint32_t b0 = e ? ob[p].z : ob[p].x, b1 = e ? ob[p].w : ob[p].y;
        if (TWO) {
          const int iA = (2 * ks) % 12, iB = iA + 1;
          mma16816(c[e], wot[iA], b0, b1);
          if (ks < 6) ldsm4t(wot[iA], woA + (ks + 6) * 512);
          mma16816(c[2 + e], wot[iB], b0, b1);
          if (ks < 6) ldsm4t(wot[iB], woA + 6144 + (ks + 6) * 512);
        } else {
          mma16816(c[ks & 3], wot[ks % 6 * 2 + ks / 6], b0, b1);
        }
      }
    }
    if (TWO) {
      stg_rlx64(spA, (pack2(c[0][0] + c[1][0], c[0][1] + c[1][1]) & ~1u) | tag, (pack2(c[0][2] + c[1][2], c[0][3] + c[1][3]) & ~1u) | tag);
      stg_rlx64(spB, (pack2(c[2][0] + c[3][0], c[2][1] + c[3][1]) & ~1u) | tag, (pack2(c[2][2] + c[3][2], c[2][3] + c[3][3]) & ~1u) | tag);
    } else {
      stg_rlx64(spA, (pack2((c[0][0] + c[1][0]) + (c[2][0] + c[3][0]), (c[0][1] + c[1][1]) + (c[2][1] + c[3][1])) & ~1u) | tag,
                (pack2((c[0][2] + c[1][2]) + (c[2][2] + c[3][2]), (c[0][3] + c[1][3]) + (c[2][3] + c[3][3])) & ~1u) | tag);
    }
    TR(15);
  };

  auto step0 = [&](auto LAST_) {
    constexpr bool LAST = decltype(LAST_)::value;
    const uint32_t rF = pin(rF_), rP = pin(rP_), rM = pin(rM_);
    TR(1);
    uint32_t bb[10][4];
    {
      const uint32_t wqS = rF + R_WQ + wid * (20 - NPQ) * 512;
      float aq[4] = {0.f, 0.f, 0.f, 0.f}, ak[4] = {0.f, 0.f, 0.f, 0.f}, aq2[4] = {0.f, 0.f, 0.f, 0.f}, ak2[4] = {0.f, 0.f, 0.f, 0.f};
      ldsm4t(bb[0], rM);
      ldsm4t(bb[1], rM + 512);
#pragma unroll
      for (int i = 0; i < 10; i++) {
        if (i + 2 < 10) ldsm4t(bb[i + 2], rM + (i + 2) * 512);
#pragma unroll
        for (int e = 0; e < 2; e++) {
          const int f = 2 * i + e;
          const uint32_t b0 = bb[i][2 * e], b1 = bb[i][2 * e + 1];
          mma16816(e ? ak2 : ak, wk[f], b0, b1);
          if (!LAST) {
            if (f < NPQ) mma16816(e ? aq2 : aq, wqp[f], b0, b1);
            else {
              const int slot = (f - NPQ) % NQ0;
              mma16816(e ? aq2 : aq, wqt[slot], b0, b1);
              if (f + NQ0 < 20) ldsm4t(wqt[slot], wqS + (f - NPQ + NQ0) * 512);
            }
          }
        }
      }
      TR(2);
      stsm4t(rP + R_QA, pack2(aq[0] + aq2[0], aq[1] + aq2[1]), pack2(aq[2] + aq2[2], aq[3] + aq2[3]),
             pack2(ak[0] + ak2[0], ak[1] + ak2[1]), pack2(ak[2] + ak2[2], ak[3] + ak2[3]));
    }
    __syncthreads();
    TR(3);
    uint32_t vm0, vm1;
    {
      const float4 vb = lds128f(rF + R_RB + w * 512);
      float av[4] = {vb.x, vb.y, vb.z, vb.w}, av1[4] = {0.f, 0.f, 0.f, 0.f}, av2[4] = {0.f, 0.f, 0.f, 0.f};
#pragma unroll
      for (int f = 0; f < 20; f++) mma16816(f % 3 == 2 ? av : (f % 3 == 1 ? av1 : av2), wv[f], bb[f >> 1][2 * (f & 1)], bb[f >> 1][2 * (f & 1) + 1]);
      vm0 = pack2(av[0] + av1[0] + av2[0], av[1] + av1[1] + av2[1]);
      vm1 = pack2(av[2] + av1[2] + av2[2], av[3] + av1[3] + av2[3]);
    }
    stsm2t(rP + R_VT, vm0, vm1);
    TR(5);
    if (LAST) return;
    const uint32_t woA = rF + R_WO + tA * 6144, woB = woA + (two ? 6144 : 3072);
    uint32_t wot[12][4], va[8];
    ldsm4t(va, rP + R_VT + 1024); ldsm4t(va + 4, rP + R_VT + 3072);
#pragma unroll
    for (int i = 0; i < NO_EARLY; i++) ldsm4t(wot[i], ((i & 1) ? woB : woA) + (i >> 1) * 512);
    const uint32_t l8 = sb + ((rF - sb) >> 1);
    const uint32_t dst = rF + (w >> 1) * 512 + (w & 1) * 8;
    const uint32_t d1 = mapa(dst + R_O2, r1), d2 = mapa(dst + R_QA, r2);
    mbar_wait(SBAR, s & 1);
    TR(6);
    float sc[10];
    {
      const float4 a0 = lds128f(rF + R_SX), b0 = lds128f(rF + R_SX + 1280), c0 = lds128f(rF + R_SX + 2560);
      const float4 a1 = lds128f(rF + R_SX + 512), b1 = lds128f(rF + R_SX + 1792), c1 = lds128f(rF + R_SX + 3072);
      const float2 a2 = lds64f(l8 + R_SX + 1024), b2 = lds64f(l8 + R_SX + 2304), c2 = lds64f(l8 + R_SX + 3584);
      sc[0] = a0.x + b0.x + c0.x; sc[1] = a0.y + b0.y + c0.y; sc[2] = a0.z + b0.z + c0.z; sc[3] = a0.w + b0.w + c0.w;
      sc[4] = a1.x + b1.x + c1.x; sc[5] = a1.y + b1.y + c1.y; sc[6] = a1.z + b1.z + c1.z; sc[7] = a1.w + b1.w + c1.w;
      sc[8] = a2.x + b2.x + c2.x; sc[9] = a2.y + b2.y + c2.y;
    }
    float mx = fmaxf(fmaxf(fmaxf(sc[0], sc[1]), fmaxf(sc[2], sc[3])), fmaxf(fmaxf(sc[4], sc[5]), fmaxf(sc[6], sc[7])));
    mx = fmaxf(mx, fmaxf(sc[8], sc[9]));
    mx = fmaxf(mx, __shfl_xor_sync(~0u, mx, 1));
    mx = fmaxf(mx, __shfl_xor_sync(~0u, mx, 2));
    constexpr float SCL = 0.07216878364870322f * 1.4426950408889634f;
    const float mo = mx * SCL;
    uint32_t pb[5];
    pb[4] = pack2(ex2(fmaf(sc[8], SCL, -mo)), ex2(fmaf(sc[9], SCL, -mo)));
#pragma unroll
    for (int j = 0; j < 4; j++) pb[j] = pack2(ex2(fmaf(sc[2 * j], SCL, -mo)), ex2(fmaf(sc[2 * j + 1], SCL, -mo)));
    const uint32_t ones[4] = {0x3F803F80u, 0x3F803F80u, 0x3F803F80u, 0x3F803F80u};
    float o[4] = {0.f, 0.f, 0.f, 0.f}, sm[4] = {0.f, 0.f, 0.f, 0.f};
    mma1688(sm, ones[0], ones[1], pb[4]);
    mma1688(o, vm0, vm1, pb[4]);
    mma16816(sm, ones, pb[0], pb[1]);
    mma16816(o, va, pb[0], pb[1]);
    mma16816(sm, ones, pb[2], pb[3]);
    mma16816(o, va + 4, pb[2], pb[3]);
    const float i0 = rcp(sm[0]), i1 = rcp(sm[1]);
    const uint32_t b0 = movmat(pack2(o[0] * i0, o[1] * i1)), b1 = movmat(pack2(o[2] * i0, o[3] * i1));
    st_async2(d1, b0, b1, mapa(OBAR, r1));
    st_async2(d2, b0, b1, mapa(OBAR, r2));
    sts64(dst + R_QB, b0, b1);
    TR(7);
    auto rest = [&]() {
#pragma unroll
      for (int i = NO_EARLY; i < 12; i++) ldsm4t(wot[i], ((i & 1) ? woB : woA) + (i >> 1) * 512);
    };
    if (two) oproj(std::true_type{}, wot, rF, woA, rest);
    else oproj(std::false_type{}, wot, rF, woA, rest);
  };

  auto step1 = [&](auto LAST_) {
    constexpr bool LAST = decltype(LAST_)::value;
    const uint32_t rF = pin(rF_), rP = pin(rP_), rM = pin(rM_);
    TR(1);
    {
      const uint32_t wqS = rF + R_WQ + wid * (20 - NPQ) * 512;
      float aq[4] = {0.f, 0.f, 0.f, 0.f}, ak[4] = {0.f, 0.f, 0.f, 0.f}, av[4] = {0.f, 0.f, 0.f, 0.f};
      uint32_t bb[3][4];
      ldsm4t(bb[0], rM);
      ldsm4t(bb[1], rM + 512);
#pragma unroll
      for (int i = 0; i < 10; i++) {
        if (i + 2 < 10) ldsm4t(bb[(i + 2) % 3], rM + (i + 2) * 512);
#pragma unroll
        for (int e = 0; e < 2; e++) {
          const int f = 2 * i + e;
          const uint32_t b0 = bb[i % 3][2 * e], b1 = bb[i % 3][2 * e + 1];
          mma16816(ak, wk[f], b0, b1);
          if (!LAST) {
            if (f < NPQ) mma16816(aq, wqp[f], b0, b1);
            else {
              const int slot = (f - NPQ) % NQ1;
              mma16816(aq, wqt[slot], b0, b1);
              if (f + NQ1 < 20) ldsm4t(wqt[slot], wqS + (f - NPQ + NQ1) * 512);
            }
          }
          mma16816(av, wv[f], b0, b1);
        }
      }
      TR(2);
      stsm4t(rP + R_QB, pack2(aq[0], aq[1]), pack2(aq[2], aq[3]), pack2(ak[0], ak[1]), pack2(ak[2], ak[3]));
      sts128f(rF + R_RB + w * 512, av[0], av[1], av[2], av[3]);
    }
    if (LAST) { __syncthreads(); return; }
    if (w < 3) {
      const uint32_t rD1 = pin(rD1_), rD2 = pin(rD2_);
      const uint32_t ry = rD2 + (w == 0 ? 2048 : 1024);
      const uint32_t a1 = rD1 ^ 32, a2 = rD1 ^ 64, a3 = rD1 ^ 96, rx2 = rD2 ^ 64, ry2 = ry ^ 64;
      const uint32_t dst = w == 0 ? sb + R_SX + rank * 1280 + 1024 + ((rF - sb) >> 1) : rF + R_SX + rank * 1280 + (w - 1) * 512;
      const uint32_t e0 = mapa(dst, 0), e1 = mapa(dst, 1), e2 = mapa(dst, 2);
      __syncthreads();
      TR(3);
      uint32_t qa[4][4], kx[8], ky[8];
      ldsm4(qa[0], rD1); ldsm4(kx, rD2); ldsm4(ky, ry);
      ldsm4(qa[1], a1); ldsm4(qa[2], a2); ldsm4(kx + 4, rx2); ldsm4(ky + 4, ry2);
      ldsm4(qa[3], a3);
      float x0[4] = {0.f, 0.f, 0.f, 0.f}, x1[4] = {0.f, 0.f, 0.f, 0.f}, z0[4] = {0.f, 0.f, 0.f, 0.f}, z1[4] = {0.f, 0.f, 0.f, 0.f};
      mma16816(x0, qa[0], kx[0], kx[1]); mma16816(z0, qa[0], ky[0], ky[1]);
      mma16816(x1, qa[1], kx[2], kx[3]); mma16816(z1, qa[1], ky[2], ky[3]);
      mma16816(x0, qa[2], kx[4], kx[5]); mma16816(z0, qa[2], ky[4], ky[5]);
      mma16816(x1, qa[3], kx[6], kx[7]); mma16816(z1, qa[3], ky[6], ky[7]);
      const float u0 = (x0[0] + x0[2]) + (x1[0] + x1[2]), u1 = (x0[1] + x0[3]) + (x1[1] + x1[3]);
      const float u2 = (z0[0] + z0[2]) + (z1[0] + z1[2]), u3 = (z0[1] + z0[3]) + (z1[1] + z1[3]);
      if (w == 0) {
        st_async2(e0, __float_as_uint(u0 + u2), __float_as_uint(u1 + u3), mapa(SBAR, 0));
        st_async2(e1, __float_as_uint(u0 + u2), __float_as_uint(u1 + u3), mapa(SBAR, 1));
        st_async2(e2, __float_as_uint(u0 + u2), __float_as_uint(u1 + u3), mapa(SBAR, 2));
      } else {
        st_async4(e0, __float_as_uint(u0), __float_as_uint(u1), __float_as_uint(u2), __float_as_uint(u3), mapa(SBAR, 0));
        st_async4(e1, __float_as_uint(u0), __float_as_uint(u1), __float_as_uint(u2), __float_as_uint(u3), mapa(SBAR, 1));
        st_async4(e2, __float_as_uint(u0), __float_as_uint(u1), __float_as_uint(u2), __float_as_uint(u3), mapa(SBAR, 2));
      }
    } else {
      __syncthreads();
      TR(3);
      if (rF == sb) {
        mbar_expect(SBAR, 3840); mbar_expect(OBAR, 2048);
        mbar_expect(XBAR, 40960); tma_load3(sb + R_XT, &tmX, 0, (s + 1) * SEG, 0, XBAR);
      }
      __syncwarp();
    }
    TR(4);
    const uint32_t woA = rF + R_WO + tA * 6144;
    uint32_t wot[12][4];
#pragma unroll
    for (int i = 0; i < 12; i++) ldsm4t(wot[i], woA + (i & 1) * 6144 + (i >> 1) * 512);
    fence_async_smem();
    TR(5);
    oproj(std::true_type{}, wot, rF, woA, []() {});
  };

  if (g == 0) {
    window(std::integral_constant<int, 0>{}, std::true_type{});
#pragma unroll 1
    for (s = 0; s < NSEG - 1; s++) {
      step0(std::false_type{});
      window(std::integral_constant<int, 0>{}, std::false_type{});
    }
    step0(std::true_type{});
  } else {
    window(std::integral_constant<int, 1>{}, std::true_type{});
#pragma unroll 1
    for (s = 0; s < NSEG - 1; s++) {
      step1(std::false_type{});
      window(std::integral_constant<int, 1>{}, std::false_type{});
    }
    step1(std::true_type{});
  }
  __syncthreads();
  if (wid == 3) {
    const uint32_t a = rF_ + (rF_ - sb);
    const uint4 a0 = lds128(a + R_KT), a1 = lds128(a + R_KT + 16), c0 = lds128(a + R_KB), c1 = lds128(a + R_KB + 16);
    sts128(a + R_KT, hadd2(a0.x, c0.x), hadd2(a0.y, c0.y), hadd2(a0.z, c0.z), hadd2(a0.w, c0.w));
    sts128(a + R_KT + 16, hadd2(a1.x, c1.x), hadd2(a1.y, c1.y), hadd2(a1.z, c1.z), hadd2(a1.w, c1.w));
  }
  fence_async_smem();
  __syncthreads();
  if (tid == 96) {
    tma_store2(&tmK, sb + R_KT, D0, (NSEG - 1) * LK);
    tma_store2(&tmV, sb + R_VT, D0, (NSEG - 1) * LK);
    bulk_commit();
    bulk_wait0();
    asm volatile("red.relaxed.gpu.global.add.u32 [%0], 1;" ::"l"(&g_segcnt[NSEG - 2]) : "memory");
    asm volatile("red.relaxed.gpu.global.add.u32 [%0], 1;" ::"l"(&g_segcnt[NSEG - 1]) : "memory");
  }
  cluster_sync();
}

__global__ void fin_kernel() { g_epoch = g_epoch + 1; }

typedef CUresult (*EncFn)(CUtensorMap*, CUtensorMapDataType, cuuint32_t, void*, const cuuint64_t*, const cuuint64_t*, const cuuint32_t*,
                          const cuuint32_t*, CUtensorMapInterleave, CUtensorMapSwizzle, CUtensorMapL2promotion, CUtensorMapFloatOOBfill);

void make_map(EncFn enc, CUtensorMap* tm, const void* base, int rank, const cuuint64_t* dims, const cuuint64_t* strides, const cuuint32_t* box) {
  const cuuint32_t es[5] = {1, 1, 1, 1, 1};
  enc(tm, CU_TENSOR_MAP_DATA_TYPE_BFLOAT16, rank, const_cast<void*>(base), dims, strides, box, es, CU_TENSOR_MAP_INTERLEAVE_NONE,
      CU_TENSOR_MAP_SWIZZLE_128B, CU_TENSOR_MAP_L2_PROMOTION_L2_128B, CU_TENSOR_MAP_FLOAT_OOB_FILL_NONE);
}

}

extern "C" void kernel_launch(void* const* d_in, const int* in_sizes, int n_in, void* d_out, int out_size) {
  const bf16* x = (const bf16*)d_in[0];
  const bf16* mem0 = (const bf16*)d_in[1];
  const bf16* Wq = (const bf16*)d_in[2];
  const bf16* Wk = (const bf16*)d_in[3];
  const bf16* Wv = (const bf16*)d_in[4];
  const bf16* Wo = (const bf16*)d_in[5];
  static EncFn enc = nullptr;
  static void *pK = nullptr, *pV = nullptr;
  if (!enc) {
    void* fn = nullptr;
    cudaDriverEntryPointQueryResult qr;
    cudaGetDriverEntryPoint("cuTensorMapEncodeTiled", &fn, cudaEnableDefault, &qr);
    enc = (EncFn)fn;
    cudaGetSymbolAddress(&pK, g_K);
    cudaGetSymbolAddress(&pV, g_V);
    cudaFuncSetAttribute(rec_kernel, cudaFuncAttributeMaxDynamicSharedMemorySize, R_SMEM_ALLOC);
  }
  CUtensorMap tmX, tmK, tmV;
  { const cuuint64_t d[3] = {64, S_TOK, 10}, st[2] = {DM * 2, 128}; const cuuint32_t b[3] = {64, 32, 10}; make_map(enc, &tmX, x, 3, d, st, b); }
  { const cuuint64_t d[2] = {HD, NSEG * LK}, st[1] = {HD * 2}; const cuuint32_t b[2] = {64, LK}; make_map(enc, &tmK, pK, 2, d, st, b); make_map(enc, &tmV, pV, 2, d, st, b); }
  rec_kernel<<<96, 256, R_SMEM_ALLOC, cudaStreamPerThread>>>(tmX, tmK, tmV, Wq, Wk, Wv, Wo, mem0);
  fin_kernel<<<1, 1, 0, cudaStreamPerThread>>>();
}
```

```cpp
#include <cuda_runtime.h>
#include <cuda_bf16.h>
#include <cuda.h>
#include <stdint.h>
#include <type_traits>

typedef __nv_bfloat16 bf16;

namespace {

constexpr int S_TOK = 2048, DM = 640, NH = 32, DH = 192, HD = NH * DH, SEG = 32, NSEG = 64, MT = 8, LK = 40;
constexpr int SPIN_MAX = 1 << 20;

constexpr int NCAND = 8;
constexpr int NFCAND = 16;
constexpr int COMM_CHUNKS = 80 * NCAND + NFCAND;
__device__ __align__(4096) unsigned char g_comm[COMM_CHUNKS * 4096];
__device__ uint32_t g_tab[96];
__device__ uint32_t g_epoch;
__device__ uint32_t g_err;
__device__ uint32_t g_segcnt[NSEG];
__device__ __align__(1024) bf16 g_K[NSEG * LK * HD];
__device__ __align__(1024) bf16 g_V[NSEG * LK * HD];
__device__ __align__(1024) bf16 g_O[S_TOK * HD];
__device__ __align__(1024) bf16 g_qkv[S_TOK * 3 * DM];
__device__ __align__(1024) bf16 g_Ob[S_TOK * DM];
__device__ __align__(1024) float g_acc[S_TOK * DM];
__device__ float g_gate[2 * S_TOK];
__device__ uint32_t g_cnt[512 * 8];
__device__ uint32_t g_queue;

__device__ __forceinline__ uint32_t smem_u32(const void* p) { return (uint32_t)__cvta_generic_to_shared(p); }
__device__ __forceinline__ uint32_t clk32() { uint32_t t; asm volatile("mov.u32 %0, %%clock;" : "=r"(t)::"memory"); return t; }
__device__ __forceinline__ uint32_t mapa(uint32_t a, uint32_t r) { uint32_t o; asm("mapa.shared::cluster.u32 %0, %1, %2;" : "=r"(o) : "r"(a), "r"(r)); return o; }
__device__ __forceinline__ void mbar_init(uint32_t b, uint32_t c) { asm volatile("mbarrier.init.shared::cta.b64 [%0], %1;" ::"r"(b), "r"(c) : "memory"); }
__device__ __forceinline__ void mbar_expect(uint32_t b, uint32_t bytes) { asm volatile("mbarrier.arrive.expect_tx.shared::cta.b64 _, [%0], %1;" ::"r"(b), "r"(bytes) : "memory"); }
__device__ __forceinline__ void mbar_arrive(uint32_t b) { asm volatile("mbarrier.arrive.shared::cta.b64 _, [%0];" ::"r"(b) : "memory"); }
__device__ __forceinline__ bool mbar_try(uint32_t b, uint32_t par) {
  uint32_t p;
  asm volatile("{.reg .pred p; mbarrier.try_wait.parity.shared::cta.b64 p, [%1], %2; selp.u32 %0,1,0,p;}" : "=r"(p) : "r"(b), "r"(par) : "memory");
  return p;
}
__device__ __forceinline__ bool mbar_try_cl(uint32_t b, uint32_t par) {
  uint32_t p;
  asm volatile("{.reg .pred p; mbarrier.try_wait.parity.acquire.cluster.shared::cta.b64 p, [%1], %2; selp.u32 %0,1,0,p;}" : "=r"(p) : "r"(b), "r"(par) : "memory");
  return p;
}
__device__ __forceinline__ void mbar_wait(uint32_t b, uint32_t par) {
  int n = 0;
#pragma unroll 1
  while (!mbar_try(b, par)) { if (++n > SPIN_MAX) { g_err = 1; break; } }
}
__device__ __forceinline__ void mbar_wait_cl(uint32_t b, uint32_t par) {
  int n = 0;
#pragma unroll 1
  while (!mbar_try_cl(b, par)) { if (++n > SPIN_MAX) { g_err = 2; break; } }
}
__device__ __forceinline__ void cluster_sync() { asm volatile("barrier.cluster.arrive.release.aligned; barrier.cluster.wait.acquire.aligned;" ::: "memory"); }
__device__ __forceinline__ void bar_sync(int id, int n) { asm volatile("bar.sync %0, %1;" ::"r"(id), "r"(n) : "memory"); }
__device__ __forceinline__ void bar_arrive(int id, int n) { asm volatile("bar.arrive %0, %1;" ::"r"(id), "r"(n) : "memory"); }
__device__ __forceinline__ void fence_async_smem() { asm volatile("fence.proxy.async.shared::cta;" ::: "memory"); }
__device__ __forceinline__ void ldsm4(uint32_t* r, uint32_t a) {
  asm volatile("ldmatrix.sync.aligned.m8n8.x4.shared.b16 {%0,%1,%2,%3}, [%4];" : "=r"(r[0]), "=r"(r[1]), "=r"(r[2]), "=r"(r[3]) : "r"(a) : "memory");
}
__device__ __forceinline__ void ldsm4t(uint32_t* r, uint32_t a) {
  asm volatile("ldmatrix.sync.aligned.m8n8.x4.trans.shared.b16 {%0,%1,%2,%3}, [%4];" : "=r"(r[0]), "=r"(r[1]), "=r"(r[2]), "=r"(r[3]) : "r"(a) : "memory");
}
__device__ __forceinline__ void ldsm2t(uint32_t* r, uint32_t a) {
  asm volatile("ldmatrix.sync.aligned.m8n8.x2.trans.shared.b16 {%0,%1}, [%2];" : "=r"(r[0]), "=r"(r[1]) : "r"(a) : "memory");
}
__device__ __forceinline__ void stsm4t(uint32_t a, uint32_t r0, uint32_t r1, uint32_t r2, uint32_t r3) {
  asm volatile("stmatrix.sync.aligned.m8n8.x4.trans.shared.b16 [%0], {%1,%2,%3,%4};" ::"r"(a), "r"(r0), "r"(r1), "r"(r2), "r"(r3) : "memory");
}
__device__ __forceinline__ void stsm2t(uint32_t a, uint32_t r0, uint32_t r1) {
  asm volatile("stmatrix.sync.aligned.m8n8.x2.trans.shared.b16 [%0], {%1,%2};" ::"r"(a), "r"(r0), "r"(r1) : "memory");
}
__device__ __forceinline__ uint32_t movmat(uint32_t a) { uint32_t d; asm volatile("movmatrix.sync.aligned.m8n8.trans.b16 %0, %1;" : "=r"(d) : "r"(a)); return d; }
__device__ __forceinline__ void mma16816(float* d, const uint32_t* a, uint32_t b0, uint32_t b1) {
  asm volatile("mma.sync.aligned.m16n8k16.row.col.f32.bf16.bf16.f32 {%0,%1,%2,%3}, {%4,%5,%6,%7}, {%8,%9}, {%0,%1,%2,%3};"
               : "+f"(d[0]), "+f"(d[1]), "+f"(d[2]), "+f"(d[3]) : "r"(a[0]), "r"(a[1]), "r"(a[2]), "r"(a[3]), "r"(b0), "r"(b1));
}
__device__ __forceinline__ void mma1688(float* d, uint32_t a0, uint32_t a1, uint32_t b0) {
  asm volatile("mma.sync.aligned.m16n8k8.row.col.f32.bf16.bf16.f32 {%0,%1,%2,%3}, {%4,%5}, {%6}, {%0,%1,%2,%3};"
               : "+f"(d[0]), "+f"(d[1]), "+f"(d[2]), "+f"(d[3]) : "r"(a0), "r"(a1), "r"(b0));
}
__device__ __forceinline__ uint32_t pack2(float lo, float hi) { uint32_t r; asm("cvt.rn.bf16x2.f32 %0, %1, %2;" : "=r"(r) : "f"(hi), "f"(lo)); return r; }
__device__ __forceinline__ float bf_lo(uint32_t w) { return __uint_as_float(w << 16); }
__device__ __forceinline__ float bf_hi(uint32_t w) { return __uint_as_float(w & 0xffff0000u); }
__device__ __forceinline__ float ex2(float x) { float y; asm("ex2.approx.ftz.f32 %0, %1;" : "=f"(y) : "f"(x)); return y; }
__device__ __forceinline__ void sts128(uint32_t a, uint32_t x, uint32_t y, uint32_t z, uint32_t w) { asm volatile("st.shared.v4.b32 [%0], {%1,%2,%3,%4};" ::"r"(a), "r"(x), "r"(y), "r"(z), "r"(w) : "memory"); }
__device__ __forceinline__ void sts128f(uint32_t a, float x, float y, float z, float w) { asm volatile("st.shared.v4.f32 [%0], {%1,%2,%3,%4};" ::"r"(a), "f"(x), "f"(y), "f"(z), "f"(w) : "memory"); }
__device__ __forceinline__ void sts64f(uint32_t a, float x, float y) { asm volatile("st.shared.v2.f32 [%0], {%1,%2};" ::"r"(a), "f"(x), "f"(y) : "memory"); }
__device__ __forceinline__ void sts32(uint32_t a, uint32_t x) { asm volatile("st.shared.b32 [%0], %1;" ::"r"(a), "r"(x) : "memory"); }
__device__ __forceinline__ uint32_t lds32(uint32_t a) { uint32_t v; asm volatile("ld.shared.b32 %0, [%1];" : "=r"(v) : "r"(a) : "memory"); return v; }
__device__ __forceinline__ float4 lds128f(uint32_t a) { float4 v; asm volatile("ld.shared.v4.f32 {%0,%1,%2,%3}, [%4];" : "=f"(v.x), "=f"(v.y), "=f"(v.z), "=f"(v.w) : "r"(a) : "memory"); return v; }
__device__ __forceinline__ uint4 lds128(uint32_t a) { uint4 v; asm volatile("ld.shared.v4.b32 {%0,%1,%2,%3}, [%4];" : "=r"(v.x), "=r"(v.y), "=r"(v.z), "=r"(v.w) : "r"(a) : "memory"); return v; }
__device__ __forceinline__ float2 lds64f(uint32_t a) { float2 v; asm volatile("ld.shared.v2.f32 {%0,%1}, [%2];" : "=f"(v.x), "=f"(v.y) : "r"(a) : "memory"); return v; }
__device__ __forceinline__ void st_async2(uint32_t a, uint32_t x, uint32_t y, uint32_t bar) {
  asm volatile("st.async.weak.shared::cluster.mbarrier::complete_tx::bytes.v2.b32 [%0], {%1,%2}, [%3];" ::"r"(a), "r"(x), "r"(y), "r"(bar) : "memory");
}
__device__ __forceinline__ void st_async4(uint32_t a, uint32_t x, uint32_t y, uint32_t z, uint32_t w, uint32_t bar) {
  asm volatile("st.async.weak.shared::cluster.mbarrier::complete_tx::bytes.v4.b32 [%0], {%1,%2,%3,%4}, [%5];" ::"r"(a), "r"(x), "r"(y), "r"(z), "r"(w), "r"(bar) : "memory");
}
__device__ __forceinline__ void sts64(uint32_t a, uint32_t x, uint32_t y) { asm volatile("st.shared.v2.b32 [%0], {%1,%2};" ::"r"(a), "r"(x), "r"(y) : "memory"); }
__device__ __forceinline__ bool bar_red_or(int id, int n, bool q) {
  uint32_t r;
  asm volatile("{.reg .pred p, q; setp.ne.u32 q, %3, 0; barrier.cta.red.or.aligned.pred p, %1, %2, q; selp.u32 %0,1,0,p;}" : "=r"(r) : "r"(id), "r"(n), "r"((uint32_t)q) : "memory");
  return r;
}
__device__ __forceinline__ float rcp(float x) { float y; asm("rcp.approx.ftz.f32 %0, %1;" : "=f"(y) : "f"(x)); return y; }
__device__ __forceinline__ uint32_t hadd2(uint32_t a, uint32_t b) { uint32_t r; asm("add.rn.bf16x2 %0, %1, %2;" : "=r"(r) : "r"(a), "r"(b)); return r; }
__device__ __forceinline__ uint32_t pin(uint32_t v) { asm volatile("" : "+r"(v)); return v; }
__device__ __forceinline__ uint32_t opaque(uint32_t v) { return __shfl_sync(~0u, v, threadIdx.x & 31); }
__device__ __forceinline__ uint4 ldg_rlx128(const void* p) {
  uint4 v; asm volatile("ld.relaxed.gpu.global.v4.b32 {%0,%1,%2,%3}, [%4];" : "=r"(v.x), "=r"(v.y), "=r"(v.z), "=r"(v.w) : "l"(p) : "memory"); return v;
}
__device__ __forceinline__ uint32_t ldg_rlx32(const void* p) {
  uint32_t v; asm volatile("ld.relaxed.gpu.global.b32 %0, [%1];" : "=r"(v) : "l"(p) : "memory"); return v;
}
__device__ __forceinline__ void spin_until(uint32_t t0, uint32_t d) {
#pragma unroll 1
  while (clk32() - t0 < d) {}
}
__device__ __forceinline__ void stg_rlx64(void* p, uint32_t a, uint32_t b) {
  asm volatile("{.reg .b64 t; mov.b64 t, {%1,%2}; st.relaxed.gpu.global.b64 [%0], t;}" ::"l"(p), "r"(a), "r"(b) : "memory");
}
__device__ __forceinline__ uint32_t ldg_acq32(const void* p) { uint32_t v; asm volatile("ld.acquire.gpu.global.b32 %0, [%1];" : "=r"(v) : "l"(p) : "memory"); return v; }
__device__ __forceinline__ void stg_rel32(void* p, uint32_t v) { asm volatile("st.release.gpu.global.b32 [%0], %1;" ::"l"(p), "r"(v) : "memory"); }
__device__ __forceinline__ void cp_async16(uint32_t dst, const void* src) { asm volatile("cp.async.cg.shared.global [%0], [%1], 16;" ::"r"(dst), "l"(src) : "memory"); }
__device__ __forceinline__ void cp_async_wait_all() { asm volatile("cp.async.wait_all;" ::: "memory"); }
__device__ __forceinline__ void prefetch_l2(const void* p) { asm volatile("prefetch.global.L2 [%0];" ::"l"(p)); }
__device__ __forceinline__ void tma_load3(uint32_t dst, const CUtensorMap* tm, int c0, int c1, int c2, uint32_t bar) {
  asm volatile("cp.async.bulk.tensor.3d.shared::cluster.global.mbarrier::complete_tx::bytes [%0], [%1, {%3,%4,%5}], [%2];"
               ::"r"(dst), "l"(tm), "r"(bar), "r"(c0), "r"(c1), "r"(c2) : "memory");
}
__device__ __forceinline__ void tma_load2(uint32_t dst, const CUtensorMap* tm, int c0, int c1, uint32_t bar) {
  asm volatile("cp.async.bulk.tensor.2d.shared::cluster.global.mbarrier::complete_tx::bytes [%0], [%1, {%3,%4}], [%2];"
               ::"r"(dst), "l"(tm), "r"(bar), "r"(c0), "r"(c1) : "memory");
}
__device__ __forceinline__ void tma_store2(const CUtensorMap* tm, uint32_t src, int c0, int c1) {
  asm volatile("cp.async.bulk.tensor.2d.global.shared::cta.bulk_group [%0, {%2,%3}], [%1];" ::"l"(tm), "r"(src), "r"(c0), "r"(c1) : "memory");
}
__device__ __forceinline__ void bulk_commit() { asm volatile("cp.async.bulk.commit_group;" ::: "memory"); }
__device__ __forceinline__ void bulk_wait0() { asm volatile("cp.async.bulk.wait_group 0;" ::: "memory"); }
__device__ __forceinline__ void bulk_wait_read0() { asm volatile("cp.async.bulk.wait_group.read 0;" ::: "memory"); }
__device__ __forceinline__ void wg_fence() { asm volatile("wgmma.fence.sync.aligned;" ::: "memory"); }
__device__ __forceinline__ void wg_commit() { asm volatile("wgmma.commit_group.sync.aligned;" ::: "memory"); }
__device__ __forceinline__ void wg_wait0() { asm volatile("wgmma.wait_group.sync.aligned 0;" ::: "memory"); }
__device__ __forceinline__ uint64_t desc_sw128(uint32_t addr) {
  return (uint64_t)((addr & 0x3FFFF) >> 4) | ((uint64_t)1 << 16) | ((uint64_t)64 << 32) | ((uint64_t)1 << 62);
}
template <int ACC>
__device__ __forceinline__ void wgmma_rs32(float* d, const uint32_t* a, uint64_t db) {
  asm volatile("{.reg .pred p; setp.ne.b32 p, %21, 0;\n"
               "wgmma.mma_async.sync.aligned.m64n32k16.f32.bf16.bf16 {%0,%1,%2,%3,%4,%5,%6,%7,%8,%9,%10,%11,%12,%13,%14,%15}, {%16,%17,%18,%19}, %20, p, 1, 1, 0;}"
               : "+f"(d[0]), "+f"(d[1]), "+f"(d[2]), "+f"(d[3]), "+f"(d[4]), "+f"(d[5]), "+f"(d[6]), "+f"(d[7]), "+f"(d[8]), "+f"(d[9]),
                 "+f"(d[10]), "+f"(d[11]), "+f"(d[12]), "+f"(d[13]), "+f"(d[14]), "+f"(d[15])
               : "r"(a[0]), "r"(a[1]), "r"(a[2]), "r"(a[3]), "l"(db), "n"(ACC));
}

template <int N> __device__ __forceinline__ void fence_regs(float* d) {
#pragma unroll
  for (int i = 0; i < N; i++) asm volatile("" : "+f"(d[i])::"memory");
}
__device__ __forceinline__ void wg_wait1() { asm volatile("wgmma.wait_group.sync.aligned 1;" ::: "memory"); }
__device__ __forceinline__ void tma_store3(const CUtensorMap* tm, uint32_t src, int c0, int c1, int c2) {
  asm volatile("cp.async.bulk.tensor.3d.global.shared::cta.bulk_group [%0, {%2,%3,%4}], [%1];" ::"l"(tm), "r"(src), "r"(c0), "r"(c1), "r"(c2) : "memory");
}
__device__ __forceinline__ void tma_red3(const CUtensorMap* tm, uint32_t src, int c0, int c1, int c2) {
  asm volatile("cp.reduce.async.bulk.tensor.3d.global.shared::cta.add.bulk_group [%0, {%2,%3,%4}], [%1];" ::"l"(tm), "r"(src), "r"(c0), "r"(c1), "r"(c2) : "memory");
}
__device__ __forceinline__ void stsm4(uint32_t a, uint32_t r0, uint32_t r1, uint32_t r2, uint32_t r3) {
  asm volatile("stmatrix.sync.aligned.m8n8.x4.shared.b16 [%0], {%1,%2,%3,%4};" ::"r"(a), "r"(r0), "r"(r1), "r"(r2), "r"(r3) : "memory");
}
__device__ __forceinline__ uint2 lds64(uint32_t a) { uint2 v; asm volatile("ld.shared.v2.b32 {%0,%1}, [%2];" : "=r"(v.x), "=r"(v.y) : "r"(a) : "memory"); return v; }
__device__ __forceinline__ uint32_t hmul2(uint32_t a, uint32_t b) { uint32_t r; asm("mul.rn.bf16x2 %0, %1, %2;" : "=r"(r) : "r"(a), "r"(b)); return r; }
__device__ __forceinline__ void wgmma_ss192t(float* d, uint64_t da, uint64_t db, int acc) {
  asm volatile("{.reg .pred p; setp.ne.b32 p, %98, 0;\n"
    "wgmma.mma_async.sync.aligned.m64n192k16.f32.bf16.bf16 "
    "{%0,%1,%2,%3,%4,%5,%6,%7,%8,%9,%10,%11,%12,%13,%14,%15,%16,%17,%18,%19,%20,%21,%22,%23,%24,%25,%26,%27,%28,%29,%30,%31,%32,%33,%34,%35,%36,%37,%38,%39,%40,%41,%42,%43,%44,%45,%46,%47,%48,%49,%50,%51,%52,%53,%54,%55,%56,%57,%58,%59,%60,%61,%62,%63,%64,%65,%66,%67,%68,%69,%70,%71,%72,%73,%74,%75,%76,%77,%78,%79,%80,%81,%82,%83,%84,%85,%86,%87,%88,%89,%90,%91,%92,%93,%94,%95}, %96, %97, p, 1, 1, 0, 1;}"
    : "+f"(d[0]), "+f"(d[1]), "+f"(d[2]), "+f"(d[3]), "+f"(d[4]), "+f"(d[5]), "+f"(d[6]), "+f"(d[7]), "+f"(d[8]), "+f"(d[9]), "+f"(d[10]), "+f"(d[11]),
      "+f"(d[12]), "+f"(d[13]), "+f"(d[14]), "+f"(d[15]), "+f"(d[16]), "+f"(d[17]), "+f"(d[18]), "+f"(d[19]), "+f"(d[20]), "+f"(d[21]), "+f"(d[22]),
      "+f"(d[23]), "+f"(d[24]), "+f"(d[25]), "+f"(d[26]), "+f"(d[27]), "+f"(d[28]), "+f"(d[29]), "+f"(d[30]), "+f"(d[31]), "+f"(d[32]), "+f"(d[33]),
      "+f"(d[34]), "+f"(d[35]), "+f"(d[36]), "+f"(d[37]), "+f"(d[38]), "+f"(d[39]), "+f"(d[40]), "+f"(d[41]), "+f"(d[42]), "+f"(d[43]), "+f"(d[44]),
      "+f"(d[45]), "+f"(d[46]), "+f"(d[47]), "+f"(d[48]), "+f"(d[49]), "+f"(d[50]), "+f"(d[51]), "+f"(d[52]), "+f"(d[53]), "+f"(d[54]), "+f"(d[55]),
      "+f"(d[56]), "+f"(d[57]), "+f"(d[58]), "+f"(d[59]), "+f"(d[60]), "+f"(d[61]), "+f"(d[62]), "+f"(d[63]), "+f"(d[64]), "+f"(d[65]), "+f"(d[66]),
      "+f"(d[67]), "+f"(d[68]), "+f"(d[69]), "+f"(d[70]), "+f"(d[71]), "+f"(d[72]), "+f"(d[73]), "+f"(d[74]), "+f"(d[75]), "+f"(d[76]), "+f"(d[77]),
      "+f"(d[78]), "+f"(d[79]), "+f"(d[80]), "+f"(d[81]), "+f"(d[82]), "+f"(d[83]), "+f"(d[84]), "+f"(d[85]), "+f"(d[86]), "+f"(d[87]), "+f"(d[88]),
      "+f"(d[89]), "+f"(d[90]), "+f"(d[91]), "+f"(d[92]), "+f"(d[93]), "+f"(d[94]), "+f"(d[95])
    : "l"(da), "l"(db), "r"(acc));
}
__device__ __forceinline__ void wgmma_ss128t(float* d, uint64_t da, uint64_t db, int acc) {
  asm volatile("{.reg .pred p; setp.ne.b32 p, %66, 0;\n"
    "wgmma.mma_async.sync.aligned.m64n128k16.f32.bf16.bf16 "
    "{%0,%1,%2,%3,%4,%5,%6,%7,%8,%9,%10,%11,%12,%13,%14,%15,%16,%17,%18,%19,%20,%21,%22,%23,%24,%25,%26,%27,%28,%29,%30,%31,%32,%33,%34,%35,%36,%37,%38,%39,%40,%41,%42,%43,%44,%45,%46,%47,%48,%49,%50,%51,%52,%53,%54,%55,%56,%57,%58,%59,%60,%61,%62,%63}, %64, %65, p, 1, 1, 0, 1;}"
    : "+f"(d[0]), "+f"(d[1]), "+f"(d[2]), "+f"(d[3]), "+f"(d[4]), "+f"(d[5]), "+f"(d[6]), "+f"(d[7]), "+f"(d[8]), "+f"(d[9]), "+f"(d[10]), "+f"(d[11]),
      "+f"(d[12]), "+f"(d[13]), "+f"(d[14]), "+f"(d[15]), "+f"(d[16]), "+f"(d[17]), "+f"(d[18]), "+f"(d[19]), "+f"(d[20]), "+f"(d[21]), "+f"(d[22]),
      "+f"(d[23]), "+f"(d[24]), "+f"(d[25]), "+f"(d[26]), "+f"(d[27]), "+f"(d[28]), "+f"(d[29]), "+f"(d[30]), "+f"(d[31]), "+f"(d[32]), "+f"(d[33]),
      "+f"(d[34]), "+f"(d[35]), "+f"(d[36]), "+f"(d[37]), "+f"(d[38]), "+f"(d[39]), "+f"(d[40]), "+f"(d[41]), "+f"(d[42]), "+f"(d[43]), "+f"(d[44]),
      "+f"(d[45]), "+f"(d[46]), "+f"(d[47]), "+f"(d[48]), "+f"(d[49]), "+f"(d[50]), "+f"(d[51]), "+f"(d[52]), "+f"(d[53]), "+f"(d[54]), "+f"(d[55]),
      "+f"(d[56]), "+f"(d[57]), "+f"(d[58]), "+f"(d[59]), "+f"(d[60]), "+f"(d[61]), "+f"(d[62]), "+f"(d[63])
    : "l"(da), "l"(db), "r"(acc));
}
__device__ __forceinline__ void wgmma_rs80(float* d, const uint32_t* a, uint64_t db, int acc) {
  asm volatile("{.reg .pred p; setp.ne.b32 p, %45, 0;\n"
    "wgmma.mma_async.sync.aligned.m64n80k16.f32.bf16.bf16 "
    "{%0,%1,%2,%3,%4,%5,%6,%7,%8,%9,%10,%11,%12,%13,%14,%15,%16,%17,%18,%19,%20,%21,%22,%23,%24,%25,%26,%27,%28,%29,%30,%31,%32,%33,%34,%35,%36,%37,%38,%39}, {%40,%41,%42,%43}, %44, p, 1, 1, 0;}"
    : "+f"(d[0]), "+f"(d[1]), "+f"(d[2]), "+f"(d[3]), "+f"(d[4]), "+f"(d[5]), "+f"(d[6]), "+f"(d[7]), "+f"(d[8]), "+f"(d[9]), "+f"(d[10]), "+f"(d[11]),
      "+f"(d[12]), "+f"(d[13]), "+f"(d[14]), "+f"(d[15]), "+f"(d[16]), "+f"(d[17]), "+f"(d[18]), "+f"(d[19]), "+f"(d[20]), "+f"(d[21]), "+f"(d[22]),
      "+f"(d[23]), "+f"(d[24]), "+f"(d[25]), "+f"(d[26]), "+f"(d[27]), "+f"(d[28]), "+f"(d[29]), "+f"(d[30]), "+f"(d[31]), "+f"(d[32]), "+f"(d[33]),
      "+f"(d[34]), "+f"(d[35]), "+f"(d[36]), "+f"(d[37]), "+f"(d[38]), "+f"(d[39])
    : "r"(a[0]), "r"(a[1]), "r"(a[2]), "r"(a[3]), "l"(db), "r"(acc));
}
__device__ __forceinline__ void wgmma_rs192t(float* d, const uint32_t* a, uint64_t db, int acc) {
  asm volatile("{.reg .pred p; setp.ne.b32 p, %101, 0;\n"
    "wgmma.mma_async.sync.aligned.m64n192k16.f32.bf16.bf16 "
    "{%0,%1,%2,%3,%4,%5,%6,%7,%8,%9,%10,%11,%12,%13,%14,%15,%16,%17,%18,%19,%20,%21,%22,%23,%24,%25,%26,%27,%28,%29,%30,%31,%32,%33,%34,%35,%36,%37,%38,%39,%40,%41,%42,%43,%44,%45,%46,%47,%48,%49,%50,%51,%52,%53,%54,%55,%56,%57,%58,%59,%60,%61,%62,%63,%64,%65,%66,%67,%68,%69,%70,%71,%72,%73,%74,%75,%76,%77,%78,%79,%80,%81,%82,%83,%84,%85,%86,%87,%88,%89,%90,%91,%92,%93,%94,%95}, {%96,%97,%98,%99}, %100, p, 1, 1, 1;}"
    : "+f"(d[0]), "+f"(d[1]), "+f"(d[2]), "+f"(d[3]), "+f"(d[4]), "+f"(d[5]), "+f"(d[6]), "+f"(d[7]), "+f"(d[8]), "+f"(d[9]), "+f"(d[10]), "+f"(d[11]),
      "+f"(d[12]), "+f"(d[13]), "+f"(d[14]), "+f"(d[15]), "+f"(d[16]), "+f"(d[17]), "+f"(d[18]), "+f"(d[19]), "+f"(d[20]), "+f"(d[21]), "+f"(d[22]),
      "+f"(d[23]), "+f"(d[24]), "+f"(d[25]), "+f"(d[26]), "+f"(d[27]), "+f"(d[28]), "+f"(d[29]), "+f"(d[30]), "+f"(d[31]), "+f"(d[32]), "+f"(d[33]),
      "+f"(d[34]), "+f"(d[35]), "+f"(d[36]), "+f"(d[37]), "+f"(d[38]), "+f"(d[39]), "+f"(d[40]), "+f"(d[41]), "+f"(d[42]), "+f"(d[43]), "+f"(d[44]),
      "+f"(d[45]), "+f"(d[46]), "+f"(d[47]), "+f"(d[48]), "+f"(d[49]), "+f"(d[50]), "+f"(d[51]), "+f"(d[52]), "+f"(d[53]), "+f"(d[54]), "+f"(d[55]),
      "+f"(d[56]), "+f"(d[57]), "+f"(d[58]), "+f"(d[59]), "+f"(d[60]), "+f"(d[61]), "+f"(d[62]), "+f"(d[63]), "+f"(d[64]), "+f"(d[65]), "+f"(d[66]),
      "+f"(d[67]), "+f"(d[68]), "+f"(d[69]), "+f"(d[70]), "+f"(d[71]), "+f"(d[72]), "+f"(d[73]), "+f"(d[74]), "+f"(d[75]), "+f"(d[76]), "+f"(d[77]),
      "+f"(d[78]), "+f"(d[79]), "+f"(d[80]), "+f"(d[81]), "+f"(d[82]), "+f"(d[83]), "+f"(d[84]), "+f"(d[85]), "+f"(d[86]), "+f"(d[87]), "+f"(d[88]),
      "+f"(d[89]), "+f"(d[90]), "+f"(d[91]), "+f"(d[92]), "+f"(d[93]), "+f"(d[94]), "+f"(d[95])
    : "r"(a[0]), "r"(a[1]), "r"(a[2]), "r"(a[3]), "l"(db), "r"(acc));
}

constexpr int NPQ = 2;
#define NQ0 10
#define NQ1 12
#define NO_EARLY 6
#define WN1 14
#define PD0 1450
#define PD1 280
#define PW0 700
#define NQ_WIN 4
constexpr int NQM = NQ0 > NQ1 ? NQ0 : NQ1;
constexpr int R_WQ = 0;
constexpr int R_WO = R_WQ + 8 * (20 - NPQ) * 512;
constexpr int R_XT = R_WO + 14 * 12 * 512;
constexpr int R_QB = R_XT + 40960;
constexpr int R_KB = R_QB + 1024;
constexpr int R_QA = R_KB + 1024;
constexpr int R_KT = R_QA + 1024;
constexpr int R_VT = R_KT + 5120;
constexpr int R_MEM = R_VT + 5120;
constexpr int R_SX = R_MEM + 10240;
constexpr int R_O2 = R_SX + 3840;
constexpr int R_RB = R_O2 + 1024;
constexpr int R_TAB = R_RB + 2048;
constexpr int R_BAR = R_TAB + 384;
constexpr int R_MISC = R_BAR + 64;
constexpr int R_SMEM = R_MISC + 128;
static_assert(R_XT % 1024 == 0 && R_KT % 1024 == 0 && R_VT % 1024 == 0, "align");
constexpr int R_SMEM_ALLOC = R_SMEM;
static_assert(R_SMEM_ALLOC <= 232448, "smem");

#define TR(i) do {} while (0)

__device__ __forceinline__ int probe_lat(unsigned char* p) {
  int best = 1 << 30;
  uint32_t v = 0;
#pragma unroll 1
  for (int r = 0; r < 4; r++) {
    uint32_t t0 = clk32();
    asm volatile("atom.relaxed.gpu.global.exch.b32 %0, [%1], %2;" : "=r"(v) : "l"(p + (v & 0)), "r"(0u) : "memory");
    uint32_t t1 = clk32() + (v & 0);
    if (v == 0x12345678u) t1++;
    best = min(best, (int)(t1 - t0));
  }
  return best;
}

__global__ void __cluster_dims__(3, 1, 1) __launch_bounds__(256, 1)
rec_kernel(const __grid_constant__ CUtensorMap tmX, const __grid_constant__ CUtensorMap tmK, const __grid_constant__ CUtensorMap tmV,
           const bf16* __restrict__ Wq, const bf16* __restrict__ Wk, const bf16* __restrict__ Wv, const bf16* __restrict__ Wo,
           const bf16* __restrict__ mem0) {
  extern __shared__ __align__(1024) unsigned char smem[];
  const uint32_t sb = smem_u32(smem);
  const int tid = threadIdx.x, lane = tid & 31, wid = __shfl_sync(~0u, tid >> 5, 0), g = wid >> 2, w = wid & 3;
  const int cta = blockIdx.x, head = cta / 3, rank = cta % 3;
  const int D0 = head * DH + rank * 64;
  const int tile0 = rank == 0 ? 0 : (rank == 1 ? 14 : 27), ntile = rank == 0 ? 14 : 13;
  const uint32_t XBAR = sb + R_BAR, SBAR = XBAR + 8, OBAR = XBAR + 16;
  const uint32_t epoch = (*(volatile uint32_t*)&g_epoch + 1) & 0xFFFFF;
  asm volatile("griddepcontrol.launch_dependents;" ::: "memory");

  if (tid == 0) {
    mbar_init(XBAR, 1); mbar_init(SBAR, 1); mbar_init(OBAR, 1);
    asm volatile("fence.mbarrier_init.release.cluster;" ::: "memory");
  }
  {
    const int c = tid & 7, kr = tid >> 3;
#pragma unroll 4
    for (int i = 0; i < 20; i++) {
      const int k = kr + 32 * i, gg = k / 320, f = (k % 320) >> 4;
      const uint32_t o = ((gg * 4 + (c >> 1)) * 20 + f) * 512 + ((c & 1) + 2 * ((k >> 3) & 1)) * 128 + (k & 7) * 16;
      const size_t go = (size_t)k * HD + D0 + c * 8;
      cp_async16(sb + o, Wk + go);
      cp_async16(sb + 81920 + o, Wv + go);
      if (f < NPQ) cp_async16(sb + 163840 + ((gg * 4 + (c >> 1)) * NPQ + f) * 512 + ((c & 1) + 2 * ((k >> 3) & 1)) * 128 + (k & 7) * 16, Wq + go);
    }
    for (int k = tid; k < 640; k += 256) prefetch_l2(Wq + (size_t)k * HD + D0);
    for (int i = tid; i < 192 * 4; i += 256) prefetch_l2(Wo + (size_t)(head * DH + (i >> 2)) * DM + tile0 * 16 + min((i & 3) * 64, ntile * 16 - 8));
  }
  if (cta < 80 || cta == 80) {
    const int nc = cta < 80 ? 1 : 2;
    for (int j = 0; j < nc; j++) {
      const int ch = cta < 80 ? cta * NCAND + wid : 80 * NCAND + wid * 2 + j;
      if (lane == 0) {
        unsigned char* p = g_comm + (size_t)ch * 4096;
        *(volatile uint32_t*)p = 0;
        sts32(sb + R_MISC + (wid * nc + j) * 4, (uint32_t)probe_lat(p));
      }
    }
    __syncthreads();
    if (cta < 80) {
      int best = 1 << 30, bc = 0;
      for (int j = 0; j < NCAND; j++) { int l = (int)lds32(sb + R_MISC + j * 4); if (l < best) { best = l; bc = j; } }
      const int ch = cta * NCAND + bc;
      *(uint4*)(g_comm + (size_t)ch * 4096 + tid * 16) = make_uint4(0, 0, 0, 0);
      __threadfence();
      __syncthreads();
      if (tid == 0) stg_rel32(&g_tab[cta], (epoch << 12) | ch);
    } else {
      int mn = 1 << 30, mx = 0;
      for (int j = 0; j < NFCAND; j++) { int l = (int)lds32(sb + R_MISC + j * 4); mn = min(mn, l); mx = max(mx, l); }
      const int thr = (mn + mx) >> 1;
      uint32_t near = 0;
      for (int j = 0; j < NFCAND; j++) if ((int)lds32(sb + R_MISC + j * 4) <= thr) near |= 1u << j;
      uint32_t far = ~near & ((1u << NFCAND) - 1);
      while (__popc(near) < 3) { const uint32_t t = 1u << (31 - __clz(far)); far ^= t; near |= t; }
      while (__popc(far) < 3) { const uint32_t t = 1u << (31 - __clz(near)); near ^= t; far |= t; }
      int mine = 0;
#pragma unroll 1
      for (int q = 0; q < 6; q++) {
        const int c = __fns(q < 3 ? near : far, 0, q % 3 + 1);
        *(uint4*)(g_comm + (size_t)(80 * NCAND + c) * 4096 + tid * 16) = make_uint4(0, 0, 0, 0);
        if (q == tid) mine = c;
      }
      __threadfence();
      __syncthreads();
      if (tid < 6) stg_rel32(&g_tab[80 + tid], (epoch << 12) | (80 * NCAND + mine));
    }
  }
  cp_async_wait_all();
  __syncthreads();
  uint32_t wk[20][4], wv[20][4], wqp[NPQ][4];
#pragma unroll
  for (int f = 0; f < 20; f++) { ldsm4t(wk[f], sb + (wid * 20 + f) * 512 + lane * 16); ldsm4t(wv[f], sb + 81920 + (wid * 20 + f) * 512 + lane * 16); }
#pragma unroll
  for (int f = 0; f < NPQ; f++) ldsm4t(wqp[f], sb + 163840 + (wid * NPQ + f) * 512 + lane * 16);
  fence_async_smem();
  __syncthreads();
  if (tid == 0) { mbar_expect(XBAR, 40960); tma_load3(sb + R_XT, &tmX, 0, 0, 0, XBAR); }
  {
    const int c = tid & 7, kr = tid >> 3;
#pragma unroll 4
    for (int i = 0; i < 20; i++) {
      const int k = kr + 32 * i, gg = k / 320, f = (k % 320) >> 4;
      if (f >= NPQ)
        cp_async16(sb + R_WQ + ((gg * 4 + (c >> 1)) * (20 - NPQ) + (f - NPQ)) * 512 + ((c & 1) + 2 * ((k >> 3) & 1)) * 128 + (k & 7) * 16,
                   Wq + (size_t)k * HD + D0 + c * 8);
    }
    const int nch = ntile * 2;
#pragma unroll 1
    for (int p = tid; p < 192 * nch; p += 256) {
      const int j = p / nch, cc = p % nch;
      cp_async16(sb + R_WO + ((cc >> 1) * 12 + ((j >> 4) + 12 - 4 * rank) % 12) * 512 + ((cc & 1) + 2 * ((j >> 3) & 1)) * 128 + (j & 7) * 16,
                 Wo + (size_t)(head * DH + j) * DM + tile0 * 16 + cc * 8);
    }
  }
  if (tid < 86) {
    uint32_t e; int n = 0;
    while (((e = ldg_acq32(&g_tab[tid])) >> 12) != epoch) { if (++n > SPIN_MAX) { g_err = 3; break; } }
    sts32(sb + R_TAB + tid * 4, (e & 0xFFF) * 4096u);
  }
  __syncthreads();
  if (wid < 2 && lane == 0) sts32(sb + R_MISC + wid * 4, (uint32_t)probe_lat(g_comm + lds32(sb + R_TAB + (80 + wid * 3 + 2) * 4) + 2048 + (cta & 15) * 128));
  cp_async_wait_all();
  __syncthreads();
  if (tid < 3) {
    const int cp = lds32(sb + R_MISC) <= lds32(sb + R_MISC + 4) ? 0 : 1;
    sts32(sb + R_TAB + (86 + tid) * 4, lds32(sb + R_TAB + (80 + cp * 3 + tid) * 4));
    if (tid < 2) {
      const int hh = cta / 40, ix = cta % 40;
      sts32(sb + R_TAB + (90 + tid) * 4, ix < 32 ? lds32(sb + R_TAB + (80 + tid * 3 + hh) * 4) + ix * 128
                                                 : lds32(sb + R_TAB + (80 + tid * 3 + 2) * 4) + hh * 1024 + (ix - 32) * 128);
    }
  }
  cluster_sync();

  const uint32_t rF_ = opaque(sb + lane * 16);
  const uint32_t rM_ = opaque(sb + R_MEM + g * 5120 + (lane >> 3) * 128 + (((lane & 7) ^ (((lane >> 3) & 1) << 2)) << 4));
  const uint32_t rP_ = opaque(sb + (lane >> 4) * 1024 + (lane & 7) * 128 + (((2 * w + ((lane >> 3) & 1)) ^ (lane & 7)) << 4));
  const uint32_t rA_ = opaque(sb + R_MEM + g * 5120 + (((tid & 127) >> 4) * 2 + ((tid >> 2) & 1)) * 128 +
                             (((((tid >> 3) & 1) * 4 + (tid & 3)) ^ (((tid >> 2) & 1) << 2)) << 4));
  const uint32_t rD1_ = opaque(sb + ((lane & 8) ? R_QB : R_QA) + (lane & 7) * 128 + (((lane >> 4) ^ (lane & 7)) << 4));
  const uint32_t rD2_ = opaque(sb + R_KT + (w == 0 ? -2048 : 2048 * w - 1024) + (lane & 7) * 128 + (((lane >> 3) ^ (lane & 7)) << 4));
  const bool isred = cta < 80;
  const int tA = g == 1 ? 2 * w : (rank == 0 ? (w < 2 ? 8 + 2 * w : 10 + w) : (w == 0 ? 8 : 9 + w));
  const bool two = g == 1 || w == 0 || (w == 1 && rank == 0);
  const uint32_t r1 = rank == 2 ? 0 : rank + 1, r2 = rank == 0 ? 2 : rank - 1;
  const uint32_t oA_ = opaque(lds32(sb + R_TAB + (tile0 + tA) * 8 + (lane >> 4) * 4) + head * 128 + (lane & 15) * 8);
  const uint32_t oB_ = opaque(lds32(sb + R_TAB + (tile0 + tA) * 8 + 8 + (lane >> 4) * 4) + head * 128 + (lane & 15) * 8);
  uint32_t wqt[NQM][4];
  int s = -1;

#define ISSUE(G, i) do { const int j_ = (i) >> 1; \
      const uint64_t d_ = ((uint64_t)0x40000040 << 32) | (dlo + (((G) * 20480 + (j_ >> 2) * 4096 + (j_ & 3) * 32) >> 4)); \
      if ((i) & 1) { if (j_ == 0) wgmma_rs32<0>(dv, wv[j_], d_); else wgmma_rs32<1>(dv, wv[j_], d_); } \
      else { if (j_ == 0) wgmma_rs32<0>(dk, wk[j_], d_); else wgmma_rs32<1>(dk, wk[j_], d_); } } while (0)

  auto window = [&](auto G_, auto FIRST_) {
    constexpr int G = decltype(G_)::value;
    constexpr bool FIRST = decltype(FIRST_)::value;
    constexpr int NQ = G ? NQ1 : NQ0;
    const uint32_t t0 = clk32();
    const uint32_t rF = pin(rF_), rP = pin(rP_), rA = pin(rA_);
    const uint32_t tag = (s & 1) ^ 1;
    float dk[16], dv[16];
    const uint32_t dlo = pin(((sb + R_XT) >> 4) | 0x10000);
    const uint32_t wqS = rF + R_WQ + wid * (20 - NPQ) * 512;
    const uint32_t xa = rF + R_XT + w * 512;
    if constexpr (G == 1) {
      const bool duty = isred && !FIRST;
      mbar_wait(XBAR, (s + 1) & 1);
      wg_fence();
#pragma unroll
      for (int i = 0; i < WN1; i++) ISSUE(1, i);
      wg_commit();
      const uint32_t ln = (rF - sb) >> 4;
      const unsigned char* rp = g_comm + (lds32(sb + R_TAB + cta * 4) + w * 1024 + ln * 4);
      uint32_t x[8];
#pragma unroll
      for (int j = 0; j < 8; j++) x[j] = 0;
      if (duty) {
        spin_until(t0, PD1);
#pragma unroll
        for (int j = 0; j < 8; j++) x[j] = ldg_rlx32(rp + j * 128);
      }
      TR(9);
      wg_fence();
#pragma unroll
      for (int i = WN1; i < 40; i++) ISSUE(1, i);
      wg_commit();
      if (duty) {
        unsigned char* fp = g_comm + (lds32(sb + R_TAB + (90 + (ln & 1)) * 4) + (ln >> 1) * 8);
        const uint32_t sa = sb + R_RB + w * 256 + (((ln & 1) * 4 + (ln >> 3)) * 4 + ((ln >> 1) & 3)) * 8;
        int n = 0;
#pragma unroll 1
        while (true) {
          const uint32_t bad = ((((x[0] ^ tag) | (x[1] ^ tag)) | ((x[2] ^ tag) | (x[3] ^ tag))) | (((x[4] ^ tag) | (x[5] ^ tag)) | ((x[6] ^ tag) | (x[7] ^ tag)))) & 1;
          const float lo = ((bf_lo(x[0]) + bf_lo(x[1])) + (bf_lo(x[2]) + bf_lo(x[3]))) + ((bf_lo(x[4]) + bf_lo(x[5])) + (bf_lo(x[6]) + bf_lo(x[7])));
          const float hi = ((bf_hi(x[0]) + bf_hi(x[1])) + (bf_hi(x[2]) + bf_hi(x[3]))) + ((bf_hi(x[4]) + bf_hi(x[5])) + (bf_hi(x[6]) + bf_hi(x[7])));
          sts64f(sa, lo, hi);
          if (!__any_sync(~0u, bad)) break;
#pragma unroll
          for (int j = 0; j < 8; j++) x[j] = ldg_rlx32(rp + j * 128);
          if (++n > SPIN_MAX) { g_err = 4; break; }
        }
        TR(10);
        if (w == 0) {
          bar_sync(2, 128);
          const uint32_t a = sb + R_RB + (ln >> 1) * 16;
          const float4 p0 = lds128f(a), p1 = lds128f(a + 256), p2 = lds128f(a + 512), p3 = lds128f(a + 768);
          const uint32_t w0 = pack2((p0.x + p1.x) + (p2.x + p3.x), (p0.y + p1.y) + (p2.y + p3.y));
          const uint32_t w1 = pack2((p0.z + p1.z) + (p2.z + p3.z), (p0.w + p1.w) + (p2.w + p3.w));
          stg_rlx64(fp, (w0 & ~1u) | tag, w1);
        } else {
          bar_arrive(2, 128);
        }
        TR(11);
      }
      wg_wait0();
#pragma unroll
      for (int q = 0; q < 4; q++) sts128f(xa + 20480 + q * 2048, dv[4 * q], dv[4 * q + 1], dv[4 * q + 2], dv[4 * q + 3]);
#pragma unroll
      for (int f = 0; f < NQ - 4; f++) ldsm4t(wqt[f], wqS + f * 512);
    } else {
      if (!FIRST) {
        fence_async_smem();
        if (w == 3) {
          const uint32_t a = rF + (rF - sb);
          const uint4 a0 = lds128(a + R_KT), a1 = lds128(a + R_KT + 16), c0 = lds128(a + R_KB), c1 = lds128(a + R_KB + 16);
          sts128(a + R_KT, hadd2(a0.x, c0.x), hadd2(a0.y, c0.y), hadd2(a0.z, c0.z), hadd2(a0.w, c0.w));
          sts128(a + R_KT + 16, hadd2(a1.x, c1.x), hadd2(a1.y, c1.y), hadd2(a1.z, c1.z), hadd2(a1.w, c1.w));
          fence_async_smem();
          bar_sync(4, 128);
          if (rF == sb) {
            if (s > 0) {
              bulk_wait0();
              asm volatile("red.relaxed.gpu.global.add.u32 [%0], 1;" ::"l"(&g_segcnt[s - 1]) : "memory");
            }
            tma_store2(&tmK, sb + R_KT, D0, s * LK);
            tma_store2(&tmV, sb + R_VT, D0, s * LK);
            bulk_commit();
          }
          __syncwarp();
        } else {
          bar_arrive(4, 128);
        }
      }
#pragma unroll
      for (int f = 0; f < NQ_WIN; f++) ldsm4t(wqt[f], wqS + f * 512);
      mbar_wait(XBAR, (s + 1) & 1);
      if (!FIRST) spin_until(t0, PW0);
      wg_fence();
#pragma unroll
      for (int i = 0; i < 40; i++) ISSUE(0, i);
      wg_commit();
      if (!FIRST && w == 3) { if (rF == sb) bulk_wait_read0(); __syncwarp(); }
    }
    const unsigned char* yp = g_comm + (lds32(sb + R_TAB + 86 * 4 + G * 4) + (rF - sb) + w * 512);
    const unsigned char* yp2 = g_comm + (lds32(sb + R_TAB + 88 * 4) + (rF - sb) + w * 512 + G * 1024);
    uint4 y0, y1, y2;
    if (!FIRST) {
      spin_until(t0, PD0);
      y0 = ldg_rlx128(yp);
      y1 = ldg_rlx128(yp + 2048);
      y2 = make_uint4(tag, 0, tag, 0);
      if (w < 2) y2 = ldg_rlx128(yp2);
    }
    TR(13);
    if constexpr (G == 0) {
      wg_wait0();
#pragma unroll
      for (int q = 0; q < 4; q++) sts128f(xa + q * 2048, dk[4 * q], dk[4 * q + 1], dk[4 * q + 2], dk[4 * q + 3]);
    }
    TR(12);
    __syncthreads();
    {
      const float* d = G ? dk : dv;
      uint32_t pk[8];
#pragma unroll
      for (int q = 0; q < 4; q++) {
        const float4 o = lds128f(xa + (G ^ 1) * 20480 + q * 2048);
        pk[2 * q] = pack2(d[4 * q] + o.x, d[4 * q + 1] + o.y); pk[2 * q + 1] = pack2(d[4 * q + 2] + o.z, d[4 * q + 3] + o.w);
      }
      stsm4t(rP + (G == 0 ? R_VT : R_KT) + 1024, pk[0], pk[1], pk[2], pk[3]);
      stsm4t(rP + (G == 0 ? R_VT : R_KT) + 3072, pk[4], pk[5], pk[6], pk[7]);
    }
#pragma unroll
    for (int f = (G ? NQ - 4 : NQ_WIN); f < NQ; f++) ldsm4t(wqt[f], wqS + f * 512);
    TR(14);
    if (FIRST) {
      const int i = tid & 127, col = G * 320 + (i >> 4) * 16 + ((i >> 2) & 1) * 8 + ((i >> 3) & 1) * 4 + (i & 3);
      const unsigned short* m = (const unsigned short*)mem0 + col;
#pragma unroll 1
      for (int j = 0; j < (w < 2 ? 3 : 2); j++) {
        uint32_t v[4];
#pragma unroll
        for (int q = 0; q < 4; q++) v[q] = (uint32_t)m[(2 * q) * DM + j * 128] | ((uint32_t)m[(2 * q + 1) * DM + j * 128] << 16);
        sts128(rA + j * 2048, v[0], v[1], v[2], v[3]);
      }
    } else {
      int n = 0;
#pragma unroll 1
      while (true) {
        sts128(rA, y0.x, y0.y, y0.z, y0.w);
        sts128(rA + 2048, y1.x, y1.y, y1.z, y1.w);
        if (w < 2) sts128(rA + 4096, y2.x, y2.y, y2.z, y2.w);
        const uint32_t b0 = (y0.x ^ tag) | (y0.z ^ tag), b1 = (y1.x ^ tag) | (y1.z ^ tag), b2 = (y2.x ^ tag) | (y2.z ^ tag);
        if (!__any_sync(~0u, (b0 | b1 | b2) & 1)) break;
        if (b0 & 1) y0 = ldg_rlx128(yp);
        if (b1 & 1) y1 = ldg_rlx128(yp + 2048);
        if (b2 & 1) y2 = ldg_rlx128(yp2);
        if (++n > SPIN_MAX) { g_err = 5; break; }
      }
    }
    TR(0);
    bar_sync(5 + G, 128);
  };

  auto oproj = [&](auto TWO_, uint32_t (&wot)[12][4], const uint32_t rF, const uint32_t woA, auto&& between) {
    constexpr bool TWO = decltype(TWO_)::value;
    const uint32_t tag = (s & 1) ^ 1;
    float c[4][4];
#pragma unroll
    for (int q = 0; q < 4; q++) c[q][0] = c[q][1] = c[q][2] = c[q][3] = 0.f;
    unsigned char* spA = g_comm + pin(oA_);
    unsigned char* spB = g_comm + pin(oB_);
    bar_sync(3, 256);
    uint4 ob[6];
    ob[0] = lds128(rF + R_QB); ob[1] = lds128(rF + R_QB + 512);
    between();
#pragma unroll
    for (int p = 0; p < 6; p++) {
      if (p == 2) {
        mbar_wait(OBAR, s & 1);
        TR(8);
        ob[2] = lds128(rF + R_QA); ob[3] = lds128(rF + R_QA + 512); ob[4] = lds128(rF + R_O2); ob[5] = lds128(rF + R_O2 + 512);
      }
#pragma unroll
      for (int e = 0; e < 2; e++) {
        const int ks = 2 * p + e;
        const uint32_t b0 = e ? ob[p].z : ob[p].x, b1 = e ? ob[p].w : ob[p].y;
        if (TWO) {
          const int iA = (2 * ks) % 12, iB = iA + 1;
          mma16816(c[e], wot[iA], b0, b1);
          if (ks < 6) ldsm4t(wot[iA], woA + (ks + 6) * 512);
          mma16816(c[2 + e], wot[iB], b0, b1);
          if (ks < 6) ldsm4t(wot[iB], woA + 6144 + (ks + 6) * 512);
        } else {
          mma16816(c[ks & 3], wot[ks % 6 * 2 + ks / 6], b0, b1);
        }
      }
    }
    if (TWO) {
      stg_rlx64(spA, (pack2(c[0][0] + c[1][0], c[0][1] + c[1][1]) & ~1u) | tag, (pack2(c[0][2] + c[1][2], c[0][3] + c[1][3]) & ~1u) | tag);
      stg_rlx64(spB, (pack2(c[2][0] + c[3][0], c[2][1] + c[3][1]) & ~1u) | tag, (pack2(c[2][2] + c[3][2], c[2][3] + c[3][3]) & ~1u) | tag);
    } else {
      stg_rlx64(spA, (pack2((c[0][0] + c[1][0]) + (c[2][0] + c[3][0]), (c[0][1] + c[1][1]) + (c[2][1] + c[3][1])) & ~1u) | tag,
                (pack2((c[0][2] + c[1][2]) + (c[2][2] + c[3][2]), (c[0][3] + c[1][3]) + (c[2][3] + c[3][3])) & ~1u) | tag);
    }
    TR(15);
  };

  auto step0 = [&](auto LAST_) {
    constexpr bool LAST = decltype(LAST_)::value;
    const uint32_t rF = pin(rF_), rP = pin(rP_), rM = pin(rM_);
    TR(1);
    uint32_t bb[10][4];
    {
      const uint32_t wqS = rF + R_WQ + wid * (20 - NPQ) * 512;
      float aq[4] = {0.f, 0.f, 0.f, 0.f}, ak[4] = {0.f, 0.f, 0.f, 0.f}, aq2[4] = {0.f, 0.f, 0.f, 0.f}, ak2[4] = {0.f, 0.f, 0.f, 0.f};
      ldsm4t(bb[0], rM);
      ldsm4t(bb[1], rM + 512);
#pragma unroll
      for (int i = 0; i < 10; i++) {
        if (i + 2 < 10) ldsm4t(bb[i + 2], rM + (i + 2) * 512);
#pragma unroll
        for (int e = 0; e < 2; e++) {
          const int f = 2 * i + e;
          const uint32_t b0 = bb[i][2 * e], b1 = bb[i][2 * e + 1];
          mma16816(e ? ak2 : ak, wk[f], b0, b1);
          if (!LAST) {
            if (f < NPQ) mma16816(e ? aq2 : aq, wqp[f], b0, b1);
            else {
              const int slot = (f - NPQ) % NQ0;
              mma16816(e ? aq2 : aq, wqt[slot], b0, b1);
              if (f + NQ0 < 20) ldsm4t(wqt[slot], wqS + (f - NPQ + NQ0) * 512);
            }
          }
        }
      }
      TR(2);
      stsm4t(rP + R_QA, pack2(aq[0] + aq2[0], aq[1] + aq2[1]), pack2(aq[2] + aq2[2], aq[3] + aq2[3]),
             pack2(ak[0] + ak2[0], ak[1] + ak2[1]), pack2(ak[2] + ak2[2], ak[3] + ak2[3]));
    }
    __syncthreads();
    TR(3);
    uint32_t vm0, vm1;
    {
      const float4 vb = lds128f(rF + R_RB + w * 512);
      float av[4] = {vb.x, vb.y, vb.z, vb.w}, av1[4] = {0.f, 0.f, 0.f, 0.f}, av2[4] = {0.f, 0.f, 0.f, 0.f};
#pragma unroll
      for (int f = 0; f < 20; f++) mma16816(f % 3 == 2 ? av : (f % 3 == 1 ? av1 : av2), wv[f], bb[f >> 1][2 * (f & 1)], bb[f >> 1][2 * (f & 1) + 1]);
      vm0 = pack2(av[0] + av1[0] + av2[0], av[1] + av1[1] + av2[1]);
      vm1 = pack2(av[2] + av1[2] + av2[2], av[3] + av1[3] + av2[3]);
    }
    stsm2t(rP + R_VT, vm0, vm1);
    TR(5);
    if (LAST) return;
    const uint32_t woA = rF + R_WO + tA * 6144, woB = woA + (two ? 6144 : 3072);
    uint32_t wot[12][4], va[8];
    ldsm4t(va, rP + R_VT + 1024); ldsm4t(va + 4, rP + R_VT + 3072);
#pragma unroll
    for (int i = 0; i < NO_EARLY; i++) ldsm4t(wot[i], ((i & 1) ? woB : woA) + (i >> 1) * 512);
    const uint32_t l8 = sb + ((rF - sb) >> 1);
    const uint32_t dst = rF + (w >> 1) * 512 + (w & 1) * 8;
    const uint32_t d1 = mapa(dst + R_O2, r1), d2 = mapa(dst + R_QA, r2);
    mbar_wait(SBAR, s & 1);
    TR(6);
    float sc[10];
    {
      const float4 a0 = lds128f(rF + R_SX), b0 = lds128f(rF + R_SX + 1280), c0 = lds128f(rF + R_SX + 2560);
      const float4 a1 = lds128f(rF + R_SX + 512), b1 = lds128f(rF + R_SX + 1792), c1 = lds128f(rF + R_SX + 3072);
      const float2 a2 = lds64f(l8 + R_SX + 1024), b2 = lds64f(l8 + R_SX + 2304), c2 = lds64f(l8 + R_SX + 3584);
      sc[0] = a0.x + b0.x + c0.x; sc[1] = a0.y + b0.y + c0.y; sc[2] = a0.z + b0.z + c0.z; sc[3] = a0.w + b0.w + c0.w;
      sc[4] = a1.x + b1.x + c1.x; sc[5] = a1.y + b1.y + c1.y; sc[6] = a1.z + b1.z + c1.z; sc[7] = a1.w + b1.w + c1.w;
      sc[8] = a2.x + b2.x + c2.x; sc[9] = a2.y + b2.y + c2.y;
    }
    float mx = fmaxf(fmaxf(fmaxf(sc[0], sc[1]), fmaxf(sc[2], sc[3])), fmaxf(fmaxf(sc[4], sc[5]), fmaxf(sc[6], sc[7])));
    mx = fmaxf(mx, fmaxf(sc[8], sc[9]));
    mx = fmaxf(mx, __shfl_xor_sync(~0u, mx, 1));
    mx = fmaxf(mx, __shfl_xor_sync(~0u, mx, 2));
    constexpr float SCL = 0.07216878364870322f * 1.4426950408889634f;
    const float mo = mx * SCL;
    uint32_t pb[5];
    pb[4] = pack2(ex2(fmaf(sc[8], SCL, -mo)), ex2(fmaf(sc[9], SCL, -mo)));
#pragma unroll
    for (int j = 0; j < 4; j++) pb[j] = pack2(ex2(fmaf(sc[2 * j], SCL, -mo)), ex2(fmaf(sc[2 * j + 1], SCL, -mo)));
    const uint32_t ones[4] = {0x3F803F80u, 0x3F803F80u, 0x3F803F80u, 0x3F803F80u};
    float o[4] = {0.f, 0.f, 0.f, 0.f}, sm[4] = {0.f, 0.f, 0.f, 0.f};
    mma1688(sm, ones[0], ones[1], pb[4]);
    mma1688(o, vm0, vm1, pb[4]);
    mma16816(sm, ones, pb[0], pb[1]);
    mma16816(o, va, pb[0], pb[1]);
    mma16816(sm, ones, pb[2], pb[3]);
    mma16816(o, va + 4, pb[2], pb[3]);
    const float i0 = rcp(sm[0]), i1 = rcp(sm[1]);
    const uint32_t b0 = movmat(pack2(o[0] * i0, o[1] * i1)), b1 = movmat(pack2(o[2] * i0, o[3] * i1));
    st_async2(d1, b0, b1, mapa(OBAR, r1));
    st_async2(d2, b0, b1, mapa(OBAR, r2));
    sts64(dst + R_QB, b0, b1);
    TR(7);
    auto rest = [&]() {
#pragma unroll
      for (int i = NO_EARLY; i < 12; i++) ldsm4t(wot[i], ((i & 1) ? woB : woA) + (i >> 1) * 512);
    };
    if (two) oproj(std::true_type{}, wot, rF, woA, rest);
    else oproj(std::false_type{}, wot, rF, woA, rest);
  };

  auto step1 = [&](auto LAST_) {
    constexpr bool LAST = decltype(LAST_)::value;
    const uint32_t rF = pin(rF_), rP = pin(rP_), rM = pin(rM_);
    TR(1);
    {
      const uint32_t wqS = rF + R_WQ + wid * (20 - NPQ) * 512;
      float aq[4] = {0.f, 0.f, 0.f, 0.f}, ak[4] = {0.f, 0.f, 0.f, 0.f}, av[4] = {0.f, 0.f, 0.f, 0.f};
      uint32_t bb[3][4];
      ldsm4t(bb[0], rM);
      ldsm4t(bb[1], rM + 512);
#pragma unroll
      for (int i = 0; i < 10; i++) {
        if (i + 2 < 10) ldsm4t(bb[(i + 2) % 3], rM + (i + 2) * 512);
#pragma unroll
        for (int e = 0; e < 2; e++) {
          const int f = 2 * i + e;
          const uint32_t b0 = bb[i % 3][2 * e], b1 = bb[i % 3][2 * e + 1];
          mma16816(ak, wk[f], b0, b1);
          if (!LAST) {
            if (f < NPQ) mma16816(aq, wqp[f], b0, b1);
            else {
              const int slot = (f - NPQ) % NQ1;
              mma16816(aq, wqt[slot], b0, b1);
              if (f + NQ1 < 20) ldsm4t(wqt[slot], wqS + (f - NPQ + NQ1) * 512);
            }
          }
          mma16816(av, wv[f], b0, b1);
        }
      }
      TR(2);
      stsm4t(rP + R_QB, pack2(aq[0], aq[1]), pack2(aq[2], aq[3]), pack2(ak[0], ak[1]), pack2(ak[2], ak[3]));
      sts128f(rF + R_RB + w * 512, av[0], av[1], av[2], av[3]);
    }
    if (LAST) { __syncthreads(); return; }
    if (w < 3) {
      const uint32_t rD1 = pin(rD1_), rD2 = pin(rD2_);
      const uint32_t ry = rD2 + (w == 0 ? 2048 : 1024);
      const uint32_t a1 = rD1 ^ 32, a2 = rD1 ^ 64, a3 = rD1 ^ 96, rx2 = rD2 ^ 64, ry2 = ry ^ 64;
      const uint32_t dst = w == 0 ? sb + R_SX + rank * 1280 + 1024 + ((rF - sb) >> 1) : rF + R_SX + rank * 1280 + (w - 1) * 512;
      const uint32_t e0 = mapa(dst, 0), e1 = mapa(dst, 1), e2 = mapa(dst, 2);
      __syncthreads();
      TR(3);
      uint32_t qa[4][4], kx[8], ky[8];
      ldsm4(qa[0], rD1); ldsm4(kx, rD2); ldsm4(ky, ry);
      ldsm4(qa[1], a1); ldsm4(qa[2], a2); ldsm4(kx + 4, rx2); ldsm4(ky + 4, ry2);
      ldsm4(qa[3], a3);
      float x0[4] = {0.f, 0.f, 0.f, 0.f}, x1[4] = {0.f, 0.f, 0.f, 0.f}, z0[4] = {0.f, 0.f, 0.f, 0.f}, z1[4] = {0.f, 0.f, 0.f, 0.f};
      mma16816(x0, qa[0], kx[0], kx[1]); mma16816(z0, qa[0], ky[0], ky[1]);
      mma16816(x1, qa[1], kx[2], kx[3]); mma16816(z1, qa[1], ky[2], ky[3]);
      mma16816(x0, qa[2], kx[4], kx[5]); mma16816(z0, qa[2], ky[4], ky[5]);
      mma16816(x1, qa[3], kx[6], kx[7]); mma16816(z1, qa[3], ky[6], ky[7]);
      const float u0 = (x0[0] + x0[2]) + (x1[0] + x1[2]), u1 = (x0[1] + x0[3]) + (x1[1] + x1[3]);
      const float u2 = (z0[0] + z0[2]) + (z1[0] + z1[2]), u3 = (z0[1] + z0[3]) + (z1[1] + z1[3]);
      if (w == 0) {
        st_async2(e0, __float_as_uint(u0 + u2), __float_as_uint(u1 + u3), mapa(SBAR, 0));
        st_async2(e1, __float_as_uint(u0 + u2), __float_as_uint(u1 + u3), mapa(SBAR, 1));
        st_async2(e2, __float_as_uint(u0 + u2), __float_as_uint(u1 + u3), mapa(SBAR, 2));
      } else {
        st_async4(e0, __float_as_uint(u0), __float_as_uint(u1), __float_as_uint(u2), __float_as_uint(u3), mapa(SBAR, 0));
        st_async4(e1, __float_as_uint(u0), __float_as_uint(u1), __float_as_uint(u2), __float_as_uint(u3), mapa(SBAR, 1));
        st_async4(e2, __float_as_uint(u0), __float_as_uint(u1), __float_as_uint(u2), __float_as_uint(u3), mapa(SBAR, 2));
      }
    } else {
      __syncthreads();
      TR(3);
      if (rF == sb) {
        mbar_expect(SBAR, 3840); mbar_expect(OBAR, 2048);
        mbar_expect(XBAR, 40960); tma_load3(sb + R_XT, &tmX, 0, (s + 1) * SEG, 0, XBAR);
      }
      __syncwarp();
    }
    TR(4);
    const uint32_t woA = rF + R_WO + tA * 6144;
    uint32_t wot[12][4];
#pragma unroll
    for (int i = 0; i < 12; i++) ldsm4t(wot[i], woA + (i & 1) * 6144 + (i >> 1) * 512);
    fence_async_smem();
    TR(5);
    oproj(std::true_type{}, wot, rF, woA, []() {});
  };

  if (g == 0) {
    window(std::integral_constant<int, 0>{}, std::true_type{});
#pragma unroll 1
    for (s = 0; s < NSEG - 1; s++) {
      step0(std::false_type{});
      window(std::integral_constant<int, 0>{}, std::false_type{});
    }
    step0(std::true_type{});
  } else {
    window(std::integral_constant<int, 1>{}, std::true_type{});
#pragma unroll 1
    for (s = 0; s < NSEG - 1; s++) {
      step1(std::false_type{});
      window(std::integral_constant<int, 1>{}, std::false_type{});
    }
    step1(std::true_type{});
  }
  __syncthreads();
  if (wid == 3) {
    const uint32_t a = rF_ + (rF_ - sb);
    const uint4 a0 = lds128(a + R_KT), a1 = lds128(a + R_KT + 16), c0 = lds128(a + R_KB), c1 = lds128(a + R_KB + 16);
    sts128(a + R_KT, hadd2(a0.x, c0.x), hadd2(a0.y, c0.y), hadd2(a0.z, c0.z), hadd2(a0.w, c0.w));
    sts128(a + R_KT + 16, hadd2(a1.x, c1.x), hadd2(a1.y, c1.y), hadd2(a1.z, c1.z), hadd2(a1.w, c1.w));
  }
  fence_async_smem();
  __syncthreads();
  if (tid == 96) {
    tma_store2(&tmK, sb + R_KT, D0, (NSEG - 1) * LK);
    tma_store2(&tmV, sb + R_VT, D0, (NSEG - 1) * LK);
    bulk_commit();
    bulk_wait0();
    asm volatile("red.relaxed.gpu.global.add.u32 [%0], 1;" ::"l"(&g_segcnt[NSEG - 2]) : "memory");
    asm volatile("red.relaxed.gpu.global.add.u32 [%0], 1;" ::"l"(&g_segcnt[NSEG - 1]) : "memory");
  }
  cluster_sync();
}

enum { IT_GATE = 0, IT_QKV = 1, IT_XATT = 2, IT_OUT = 3, IT_BATT = 4, IT_CVT = 5, IT_INIT = 6, IT_END = 7 };
constexpr int C_GATE = 0, C_QKV = 16, C_OB = 32, C_INIT = 48, C_ACC = 80, C_O = 96, C_NUM = 96 + 256;
__host__ __device__ constexpr int nsplit(int t) { return t >= 14 ? 8 : 4; }
constexpr uint32_t mk_item(int ty, int t, int a, int b = 0, int c = 0) { return ty | (t << 3) | (a << 8) | (b << 16) | (c << 24); }
struct ItemTab { uint32_t v[1024]; int n; };
constexpr ItemTab make_items() {
  ItemTab T{};
  int n = 0;
  for (int t = 0; t < 16; t++) T.v[n++] = mk_item(IT_GATE, t, 0);
  for (int t = 0; t < 16; t++) for (int a = 0; a < 5; a++) T.v[n++] = mk_item(IT_QKV, t, a);
  for (int t = 0; t < 32; t++) for (int a = 0; a < 4; a++) T.v[n++] = mk_item(IT_BATT, t, a);
  for (int t = 0; t < 16; t++) for (int a = 0; a < 2; a++) T.v[n++] = mk_item(IT_INIT, t, a);
  for (int t = 0; t < 16 + 4; t++) {
    if (t < 16) for (int a = 0; a < 16; a++) T.v[n++] = mk_item(IT_XATT, t, a);
    const int u = t - 2;
    if (u >= 0 && u < 16) {
      const int ns = nsplit(u);
      for (int q = 0; q < ns; q++) for (int a = 0; a < 2; a++) T.v[n++] = mk_item(IT_OUT, u, a, q * 16 / ns, (q + 1) * 16 / ns);
    }
    const int v = t - 4;
    if (v >= 0) for (int a = 0; a < 4; a++) T.v[n++] = mk_item(IT_CVT, v, a);
  }
  T.n = n;
  return T;
}
constexpr ItemTab k_items_host = make_items();
constexpr int NITEMS = k_items_host.n;
__constant__ ItemTab c_items = make_items();

constexpr int AUX_GRID = 132, NST = 7, STG = 32768;
constexpr int A_FULL = NST * STG, A_EMPTY = A_FULL + 64, A_ITEM = A_EMPTY + 64, A_QBAR = A_ITEM + 32, A_QENT = A_QBAR + 128, A_MISC = A_QENT + 256,
              A_SMEM = A_MISC + 32;
static_assert(A_SMEM <= 232448, "smem");
enum { OP_END = 0, OP_O = 1, OP_QKV = 2, OP_OB = 3, OP_ACC = 4, OP_RED = 5 };

struct AuxMaps { CUtensorMap xA, wq, wqkv, wo, wob, k, v, oA, oS, obA, obS, qkvS, qkvQ, qkvK, acc; };

__device__ __forceinline__ void wait_cnt(const uint32_t* p, uint32_t target) {
  int n = 0;
#pragma unroll 1
  while ((int)(ldg_acq32(p) - target) < 0) { if (++n > SPIN_MAX) { g_err = 7; break; } __nanosleep(64); }
}
__device__ __forceinline__ void mbar_wait_long(uint32_t b, uint32_t par) {
  int n = 0;
#pragma unroll 1
  while (!mbar_try(b, par)) { if (++n > (SPIN_MAX << 4)) { g_err = 8; break; } }
}
__device__ __forceinline__ uint64_t mk_desc(uint32_t addr, uint32_t lbo, uint32_t sbo, uint32_t mode) {
  return (uint64_t)((addr & 0x3FFFF) >> 4) | ((uint64_t)(lbo >> 4) << 16) | ((uint64_t)(sbo >> 4) << 32) | ((uint64_t)mode << 62);
}

__global__ void __launch_bounds__(384, 1)
aux_kernel(const __grid_constant__ AuxMaps tm, const bf16* __restrict__ x, const bf16* __restrict__ gate_w, bf16* __restrict__ out) {
  extern __shared__ __align__(1024) unsigned char smem[];
  const uint32_t sb = smem_u32(smem);
  const int tid = threadIdx.x, lane = tid & 31, wid = __shfl_sync(~0u, tid >> 5, 0);
  if (tid == 0) {
    for (int i = 0; i < NST; i++) { mbar_init(sb + A_FULL + i * 8, 1); mbar_init(sb + A_EMPTY + i * 8, 8); }
    for (int i = 0; i < 16; i++) mbar_init(sb + A_QBAR + i * 8, 4);
    asm volatile("fence.mbarrier_init.release.cluster;" ::: "memory");
    sts32(sb + A_MISC, *(volatile uint32_t*)&g_epoch + 1);
  }
  __syncthreads();
  const uint32_t epoch = lds32(sb + A_MISC);
  uint32_t st = 0, ph = 0;
  auto advance = [&]() { if (++st == NST) { st = 0; ph ^= 1; } };

  if (wid >= 8) {
    asm volatile("setmaxnreg.dec.sync.aligned.u32 40;");
    if (wid == 8 && lane == 0) {
      const uint32_t qbase = (epoch - 1) * (uint32_t)(NITEMS + AUX_GRID);
      while (true) {
        const uint32_t idx = atomicAdd(&g_queue, 1u) - qbase;
        const uint32_t item = idx < (uint32_t)NITEMS ? c_items.v[idx] : (uint32_t)IT_END;
        const int ty = item & 7, t = (item >> 3) & 31, a = (item >> 8) & 255, b = (item >> 16) & 255, c = item >> 24;
        auto slot = [&](uint32_t bytes) -> uint32_t {
          mbar_wait_long(sb + A_EMPTY + st * 8, ph ^ 1);
          sts32(sb + A_ITEM + st * 4, item);
          if (bytes) mbar_expect(sb + A_FULL + st * 8, bytes); else mbar_arrive(sb + A_FULL + st * 8);
          return sb + st * STG;
        };
        if (ty == IT_QKV || ty == IT_XATT) {
          const CUtensorMap* w = ty == IT_QKV ? &tm.wqkv : &tm.wq;
          for (int k = 0; k < 20; k++) {
            const uint32_t d = slot(32768), fb = sb + A_FULL + st * 8;
            tma_load2(d, &tm.xA, k * 32, t * 128, fb);
            tma_load3(d + 8192, w, 0, k * 32, a * 6, fb);
            advance();
          }
          if (ty == IT_QKV) {
            for (int k = 0; k < 4; k++) { slot(0); advance(); }
          } else {
            wait_cnt(&g_cnt[(C_GATE + t) * 8], epoch);
            for (int k = 0; k < 4; k++) wait_cnt(&g_segcnt[4 * t + k], epoch * 96);
            asm volatile("fence.proxy.async;" ::: "memory");
            for (int k = 0; k < 8; k++) {
              const uint32_t d = slot(30720);
              tma_load3(d, k < 4 ? &tm.k : &tm.v, 0, (4 * t + (k & 2)) * LK, (2 * a + (k & 1)) * 3, sb + A_FULL + st * 8);
              advance();
            }
          }
        } else if (ty == IT_OUT || ty == IT_INIT) {
          const CUtensorMap *ma = ty == IT_OUT ? &tm.oA : &tm.obA, *mb = ty == IT_OUT ? &tm.wo : &tm.wob;
          const int k0 = ty == IT_OUT ? b * 12 : 0, k1 = ty == IT_OUT ? c * 12 : 20;
          for (int k = k0; k < k1; k++) {
            if (ty == IT_OUT ? k % 12 == 0 : k == 0) {
              if (ty == IT_OUT) wait_cnt(&g_cnt[(C_O + t * 16 + k / 12) * 8], epoch * 2);
              else wait_cnt(&g_cnt[(C_OB + t) * 8], epoch * 8);
              asm volatile("fence.proxy.async;" ::: "memory");
            }
            const uint32_t d = slot(28672), fb = sb + A_FULL + st * 8;
            tma_load2(d, ma, k * 32, t * 128, fb);
            tma_load3(d + 8192, mb, 0, k * 32, a * 5, fb);
            advance();
          }
          for (int k = 0; k < 6; k++) { slot(0); advance(); }
        } else if (ty == IT_BATT) {
          wait_cnt(&g_cnt[(C_GATE + (t >> 1)) * 8], epoch);
          wait_cnt(&g_cnt[(C_QKV + (t >> 1)) * 8], epoch * 10);
          if (t > 0) wait_cnt(&g_cnt[(C_QKV + ((t - 1) >> 1)) * 8], epoch * 10);
          asm volatile("fence.proxy.async;" ::: "memory");
          { const uint32_t d = slot(20480); tma_load2(d, &tm.qkvQ, a * 160, t * 64, sb + A_FULL + st * 8); advance(); }
          { const uint32_t d = slot(25600); tma_load2(d, &tm.qkvK, 640 + a * 160, t * 64 - 16, sb + A_FULL + st * 8); advance(); }
          { const uint32_t d = slot(25600); tma_load2(d, &tm.qkvK, 1280 + a * 160, t * 64 - 16, sb + A_FULL + st * 8); advance(); }
        } else {
          if (ty == IT_CVT) wait_cnt(&g_cnt[(C_ACC + t) * 8], epoch * (4 * nsplit(t)));
          slot(0); advance();
          if (ty == IT_END) {
            if (idx == (uint32_t)(NITEMS + AUX_GRID - 1)) g_epoch = epoch;
            break;
          }
        }
      }
      asm volatile("griddepcontrol.wait;" ::: "memory");
    } else if ((wid == 9 || wid == 10) && lane == 0) {
      const uint32_t qb = sb + A_QBAR + (wid - 9) * 64, qe = sb + A_QENT + (wid - 9) * 128;
      for (uint32_t e = 0;; e++) {
        mbar_wait_long(qb + (e & 7) * 8, (e >> 3) & 1);
        const uint4 en = lds128(qe + (e & 7) * 16);
        const int op = en.x & 15, sg = (en.x >> 4) & 15, rel = (en.x >> 8) & 15, nb = (en.x >> 12) & 15;
        if (op == OP_END) break;
        const uint32_t src = sb + sg * STG;
        if (op == OP_O) tma_store3(&tm.oS, src, 0, en.y, en.z);
        else if (op == OP_QKV) tma_store3(&tm.qkvS, src, 0, en.y, en.z);
        else if (op == OP_OB) tma_store2(&tm.obS, src, en.z, en.y);
        else if (op == OP_ACC) { for (int i = 0; i < nb; i++) tma_store3(&tm.acc, src + i * 16384, 0, en.y, en.z + 2 * i); }
        else {
          wait_cnt(&g_cnt[(en.x >> 16) * 8], epoch * 2);
          asm volatile("fence.proxy.async;" ::: "memory");
          for (int i = 0; i < nb; i++) tma_red3(&tm.acc, src + i * 16384, 0, en.y, en.z + 2 * i);
        }
        bulk_commit();
        bulk_wait_read0();
        asm volatile("mbarrier.arrive.shared::cta.b64 _, [%0], %1;" ::"r"(sb + A_EMPTY + sg * 8), "r"(rel) : "memory");
        if (en.w) {
          bulk_wait0();
          asm volatile("fence.proxy.async;" ::: "memory");
          asm volatile("red.release.gpu.global.add.u32 [%0], 1;" ::"l"(&g_cnt[(en.w - 1) * 8]) : "memory");
        }
      }
      bulk_wait0();
    }
  } else {
    asm volatile("setmaxnreg.inc.sync.aligned.u32 232;");
    const int g = wid >> 2, w = wid & 3;
    uint32_t qn = 0;
    auto wait_full = [&]() { mbar_wait_long(sb + A_FULL + st * 8, ph); };
    auto release = [&](uint32_t s_) { if (lane == 0) mbar_arrive(sb + A_EMPTY + s_ * 8); };
    auto take_pair = [&]() -> uint32_t {
      wait_full();
      const uint32_t s0 = st; advance();
      wait_full();
      const uint32_t s1 = st; advance();
      release(g ? s0 : s1);
      return g ? s1 : s0;
    };
    auto push = [&](uint32_t w0, uint32_t w1, uint32_t w2, uint32_t w3) {
      fence_async_smem();
      if (w == 0 && lane == 0) sts128(sb + A_QENT + g * 128 + (qn & 7) * 16, w0, w1, w2, w3);
      __syncwarp();
      if (lane == 0) mbar_arrive(sb + A_QBAR + g * 64 + (qn & 7) * 8);
      qn++;
    };
    const uint32_t stm = (16 * w + (lane & 7) + (lane & 8)) * 128, stx = lane & 7, sth = lane >> 4;
    auto stage_bf16 = [&](uint32_t dst, const float* d, float s0, float s1) {
#pragma unroll
      for (int ks = 0; ks < 12; ks++)
        stsm4(dst + (ks >> 2) * 8192 + stm + (((2 * (ks & 3) + sth) ^ stx) << 4), pack2(d[8 * ks] * s0, d[8 * ks + 1] * s0), pack2(d[8 * ks + 2] * s1, d[8 * ks + 3] * s1),
              pack2(d[8 * ks + 4] * s0, d[8 * ks + 5] * s0), pack2(d[8 * ks + 6] * s1, d[8 * ks + 7] * s1));
    };
#pragma unroll 1
    while (true) {
      wait_full();
      const uint32_t item = lds32(sb + A_ITEM + st * 4);
      const int ty = item & 7, t = (item >> 3) & 31, a = (item >> 8) & 255;
      if (ty == IT_QKV || ty == IT_XATT) {
        float acc[192] = {};
        uint32_t prev = 0;
#pragma unroll 1
        for (int k = 0; k < 20; k++) {
          if (k) wait_full();
          const uint32_t s_ = sb + st * STG;
          const uint64_t da = mk_desc(s_, 16, 512, 2), db = mk_desc(s_ + 8192 + g * 12288, 4096, 1024, 1);
          wg_fence();
          wgmma_ss192t(acc, da, db, k);
          wgmma_ss192t(acc + 96, da + 256, db, k);
          wgmma_ss192t(acc, da + 2, db + 128, 1);
          wgmma_ss192t(acc + 96, da + 258, db + 128, 1);
          wg_commit();
          if (k) { wg_wait1(); release(prev); }
          prev = st; advance();
        }
        wg_wait0();
        fence_regs<192>(acc);
        release(prev);
        if (ty == IT_QKV) {
#pragma unroll
          for (int q = 0; q < 2; q++) {
            const uint32_t m = take_pair();
            stage_bf16(sb + m * STG, acc + q * 96, 1.f, 1.f);
            push(OP_QKV | (m << 4) | (4 << 8), t * 128 + q * 64, a * 6 + g * 3, q ? C_QKV + t + 1 : 0);
          }
        } else {
          uint32_t qf[24][4];
#pragma unroll
          for (int ks = 23; ks >= 0; ks--)
#pragma unroll
            for (int j = 0; j < 4; j++)
              asm volatile("cvt.rn.bf16x2.f32 %0, %1, %2;" : "=r"(qf[ks][j]) : "f"(acc[8 * ks + 2 * j + 1]), "f"(acc[8 * ks + 2 * j]));
          float sc[2][40] = {};
          uint32_t kst[2];
#pragma unroll
          for (int q = 0; q < 2; q++) {
            kst[q] = take_pair();
            const uint64_t db = mk_desc(sb + kst[q] * STG, 16, 1024, 1);
            wg_fence();
#pragma unroll
            for (int ks = 0; ks < 12; ks++) wgmma_rs80(sc[q], qf[q * 12 + ks], db + (((ks >> 2) * 10240 + (ks & 3) * 32) >> 4), ks);
            wg_commit();
          }
          const int tt = 16 * (w & 1) + (lane >> 2) - 2 * (lane & 3);
          const float* gp = g_gate + t * 128 + 16 * w + (lane >> 2);
          const float gt[4] = {__ldcg(gp), __ldcg(gp + 8), __ldcg(gp + 64), __ldcg(gp + 72)};
          uint32_t pf[2][5][4];
          float rs[2][2];
          auto softmax = [&](const float* s_, uint32_t (&p)[5][4], float* r) {
            constexpr float SCL = 0.07216878364870322f * 1.4426950408889634f;
            float v[20];
#pragma unroll
            for (int i = 0; i < 20; i++) {
              v[i] = w >= 2 ? s_[20 + i] : s_[i];
              if (i >= 4 && 8 * ((i >> 2) - 1) + (i & 1) > tt + ((i & 2) ? 8 : 0)) v[i] = -INFINITY;
            }
            uint32_t pt[5][2];
#pragma unroll
            for (int h = 0; h < 2; h++) {
              float mx = fmaxf(v[2 * h], v[2 * h + 1]);
#pragma unroll
              for (int j = 1; j < 5; j++) mx = fmaxf(mx, fmaxf(v[4 * j + 2 * h], v[4 * j + 2 * h + 1]));
              mx = fmaxf(mx, __shfl_xor_sync(~0u, mx, 1));
              mx = fmaxf(mx, __shfl_xor_sync(~0u, mx, 2));
              const float mo = mx * SCL;
              float sum = 0.f;
#pragma unroll
              for (int j = 0; j < 5; j++) {
                const float e0 = ex2(fmaf(v[4 * j + 2 * h], SCL, -mo)), e1 = ex2(fmaf(v[4 * j + 2 * h + 1], SCL, -mo));
                pt[j][h] = pack2(e0, e1);
                sum += bf_lo(pt[j][h]) + bf_hi(pt[j][h]);
              }
              sum += __shfl_xor_sync(~0u, sum, 1);
              sum += __shfl_xor_sync(~0u, sum, 2);
              r[h] = rcp(sum);
            }
#pragma unroll
            for (int J = 0; J < 10; J++)
#pragma unroll
              for (int h = 0; h < 2; h++) p[J >> 1][(J & 1) * 2 + h] = (J >= 5) == (w >= 2) ? pt[J % 5][h] : 0u;
          };
          wg_wait1();
          fence_regs<40>(sc[0]);
          release(kst[0]);
          softmax(sc[0], pf[0], rs[0]);
#pragma unroll
          for (int q = 0; q < 2; q++) {
            const uint32_t m = take_pair();
            const uint64_t db = mk_desc(sb + m * STG, 10240, 1024, 1);
            float o[96] = {};
            wg_fence();
#pragma unroll
            for (int ks = 0; ks < 5; ks++) wgmma_rs192t(o, pf[q][ks], db + ks * 128, ks);
            wg_commit();
            if (q == 0) {
              wg_wait1();
              fence_regs<40>(sc[1]);
              release(kst[1]);
              softmax(sc[1], pf[1], rs[1]);
            }
            wg_wait0();
            fence_regs<96>(o);
            bar_sync(1 + g, 128);
            stage_bf16(sb + m * STG, o, rs[q][0] * gt[2 * q], rs[q][1] * gt[2 * q + 1]);
            push(OP_O | (m << 4) | (4 << 8), t * 128 + q * 64, a * 6 + g * 3, q ? C_O + t * 16 + a + 1 : 0);
          }
        }
      } else if (ty == IT_OUT || ty == IT_INIT) {
        float acc[160] = {};
        const int nk = ty == IT_OUT ? ((item >> 24) - ((item >> 16) & 255)) * 12 : 20;
        uint32_t prev = 0;
#pragma unroll 1
        for (int k = 0; k < nk; k++) {
          if (k) wait_full();
          const uint32_t s_ = sb + st * STG;
          const uint64_t da = mk_desc(s_ + g * 4096, 16, 512, 2), db = mk_desc(s_ + 8192, 4096, 1024, 1);
          wg_fence();
          wgmma_ss192t(acc, da, db, k);
          wgmma_ss128t(acc + 96, da, db + 768, k);
          wgmma_ss192t(acc, da + 2, db + 128, 1);
          wgmma_ss128t(acc + 96, da + 2, db + 896, 1);
          wg_commit();
          if (k) { wg_wait1(); release(prev); }
          prev = st; advance();
        }
        wg_wait0();
        fence_regs<160>(acc);
        release(prev);
        const uint32_t ro = (16 * w + (lane >> 2)) * 128 + (lane & 1) * 8, xr = lane >> 2, ch = (lane >> 1) & 1;
#pragma unroll
        for (int q = 0; q < 3; q++) {
          const uint32_t m = take_pair();
          const uint32_t dst = sb + m * STG + ro;
#pragma unroll
          for (int j = 0; j < 16; j++) {
            const int nt = q * 16 + j;
            if (nt < 40) {
              const uint32_t ad = dst + (j >> 2) * 8192 + (((2 * (j & 3) + ch) ^ xr) << 4);
              sts64f(ad, acc[4 * nt], acc[4 * nt + 1]);
              sts64f(ad + 1024, acc[4 * nt + 2], acc[4 * nt + 3]);
            }
          }
          const uint32_t fl = q < 2 ? 0 : (ty == IT_OUT ? C_ACC + t + 1 : C_INIT + 2 * t + a + 1);
          push((ty == IT_OUT ? OP_RED : OP_ACC) | (m << 4) | (4 << 8) | ((q < 2 ? 2 : 1) << 12) | ((C_INIT + 2 * t + a) << 16), t * 128 + g * 64,
               a * 10 + q * 4, fl);
        }
      } else if (ty == IT_BATT) {
        const uint32_t sq = st; advance();
        wait_full();
        const uint32_t sk = st; advance();
        wait_full();
        const uint32_t sv = st; advance();
        const int h = tid & 7;
#pragma unroll 1
        for (int p = 0; p < 2; p++) {
          const int tok = (tid >> 3) + 32 * p, pos = t * 64 + tok;
          const uint32_t qa = sb + sq * STG + tok * 320 + h * 40, ka = sb + sk * STG + (tok + 16) * 320 + h * 40, va = sb + sv * STG + (tok + 16) * 320 + h * 40;
          const float gt = __ldcg(g_gate + 2048 + pos);
          float q[20], l[8];
#pragma unroll
          for (int i = 0; i < 5; i++) { const uint2 u = lds64(qa + i * 8); q[4 * i] = bf_lo(u.x); q[4 * i + 1] = bf_hi(u.x); q[4 * i + 2] = bf_lo(u.y); q[4 * i + 3] = bf_hi(u.y); }
          float mx = -INFINITY;
#pragma unroll
          for (int j = 0; j < 8; j++) {
            float s0 = 0.f, s1 = 0.f;
#pragma unroll
            for (int i = 0; i < 5; i++) {
              const uint2 u = lds64(ka - j * 640 + i * 8);
              s0 = fmaf(q[4 * i], bf_lo(u.x), s0); s1 = fmaf(q[4 * i + 1], bf_hi(u.x), s1);
              s0 = fmaf(q[4 * i + 2], bf_lo(u.y), s0); s1 = fmaf(q[4 * i + 3], bf_hi(u.y), s1);
            }
            l[j] = pos - 2 * j >= 0 ? s0 + s1 : -INFINITY;
            mx = fmaxf(mx, l[j]);
          }
          constexpr float SCL = 0.22360679774997896f * 1.4426950408889634f;
          const float mo = mx * SCL;
          float sum = 0.f;
#pragma unroll
          for (int j = 0; j < 8; j++) { l[j] = ex2(fmaf(l[j], SCL, -mo)); sum += l[j]; }
          const float r = gt * rcp(sum);
#pragma unroll
          for (int i = 0; i < 20; i++) q[i] = 0.f;
#pragma unroll
          for (int j = 0; j < 8; j++) {
#pragma unroll
            for (int i = 0; i < 5; i++) {
              const uint2 u = lds64(va - j * 640 + i * 8);
              q[4 * i] = fmaf(l[j], bf_lo(u.x), q[4 * i]); q[4 * i + 1] = fmaf(l[j], bf_hi(u.x), q[4 * i + 1]);
              q[4 * i + 2] = fmaf(l[j], bf_lo(u.y), q[4 * i + 2]); q[4 * i + 3] = fmaf(l[j], bf_hi(u.y), q[4 * i + 3]);
            }
          }
#pragma unroll
          for (int i = 0; i < 5; i++) sts64(qa + i * 8, pack2(q[4 * i] * r, q[4 * i + 1] * r), pack2(q[4 * i + 2] * r, q[4 * i + 3] * r));
        }
        __syncwarp();
        release(sk); release(sv);
        fence_async_smem();
        bar_sync(3, 256);
        if (g == 0) push(OP_OB | (sq << 4) | (8 << 8), t * 64, a * 160, C_OB + (t >> 1) + 1);
      } else if (ty == IT_GATE) {
        release(st); advance();
        uint4 gw[3];
#pragma unroll
        for (int i = 0; i < 3; i++) gw[i] = (i < 2 || lane < 16) ? __ldg((const uint4*)gate_w + lane + 32 * i) : make_uint4(0, 0, 0, 0);
#pragma unroll 4
        for (int r = 0; r < 16; r++) {
          const int row = t * 128 + wid * 16 + r;
          float s_ = 0.f;
#pragma unroll
          for (int i = 0; i < 3; i++) {
            const uint4 v = (i < 2 || lane < 16) ? __ldg((const uint4*)(x + (size_t)row * DM) + lane + 32 * i) : make_uint4(0, 0, 0, 0);
            const uint32_t p0 = hmul2(v.x, gw[i].x), p1 = hmul2(v.y, gw[i].y), p2 = hmul2(v.z, gw[i].z), p3 = hmul2(v.w, gw[i].w);
            s_ += ((bf_lo(p0) + bf_hi(p0)) + (bf_lo(p1) + bf_hi(p1))) + ((bf_lo(p2) + bf_hi(p2)) + (bf_lo(p3) + bf_hi(p3)));
          }
#pragma unroll
          for (int o = 16; o; o >>= 1) s_ += __shfl_xor_sync(~0u, s_, o);
          const float z = bf_lo(pack2(s_, 0.f));
          const float gv = bf_lo(pack2(1.f / (1.f + __expf(-z)), 0.f));
          if (lane == 0) { g_gate[row] = gv; g_gate[2048 + row] = bf_lo(pack2(1.f - gv, 0.f)); }
        }
        __threadfence();
        bar_sync(3, 256);
        if (tid == 0) asm volatile("red.release.gpu.global.add.u32 [%0], 1;" ::"l"(&g_cnt[(C_GATE + t) * 8]) : "memory");
      } else if (ty == IT_CVT) {
        release(st); advance();
        const size_t o = (size_t)(t * 128 + a * 32) * DM + tid * 8;
        float4 v[10][2];
#pragma unroll
        for (int i = 0; i < 10; i++) { v[i][0] = __ldcg((const float4*)(g_acc + o + i * 2048)); v[i][1] = __ldcg((const float4*)(g_acc + o + i * 2048 + 4)); }
#pragma unroll
        for (int i = 0; i < 10; i++)
          *(uint4*)(out + o + i * 2048) = make_uint4(pack2(v[i][0].x, v[i][0].y), pack2(v[i][0].z, v[i][0].w), pack2(v[i][1].x, v[i][1].y), pack2(v[i][1].z, v[i][1].w));
      } else {
        push(OP_END, 0, 0, 0);
        break;
      }
    }
  }
}

typedef CUresult (*EncFn)(CUtensorMap*, CUtensorMapDataType, cuuint32_t, void*, const cuuint64_t*, const cuuint64_t*, const cuuint32_t*,
                          const cuuint32_t*, CUtensorMapInterleave, CUtensorMapSwizzle, CUtensorMapL2promotion, CUtensorMapFloatOOBfill);

void make_map(EncFn enc, CUtensorMap* tm, const void* base, int rank, const cuuint64_t* dims, const cuuint64_t* strides, const cuuint32_t* box,
              CUtensorMapSwizzle sw = CU_TENSOR_MAP_SWIZZLE_128B, CUtensorMapDataType dt = CU_TENSOR_MAP_DATA_TYPE_BFLOAT16) {
  const cuuint32_t es[5] = {1, 1, 1, 1, 1};
  enc(tm, dt, rank, const_cast<void*>(base), dims, strides, box, es, CU_TENSOR_MAP_INTERLEAVE_NONE, sw, CU_TENSOR_MAP_L2_PROMOTION_L2_128B,
      CU_TENSOR_MAP_FLOAT_OOB_FILL_NONE);
}
void map_blk(EncFn enc, CUtensorMap* tm, const void* base, int rows, int cols, int brows, int bblk) {
  const cuuint64_t d[3] = {64, (cuuint64_t)rows, (cuuint64_t)cols / 64}, st[2] = {(cuuint64_t)cols * 2, 128};
  const cuuint32_t b[3] = {64, (cuuint32_t)brows, (cuuint32_t)bblk};
  make_map(enc, tm, base, 3, d, st, b);
}
void map_2d(EncFn enc, CUtensorMap* tm, const void* base, int rows, int cols, int brows, int bcols, CUtensorMapSwizzle sw) {
  const cuuint64_t d[2] = {(cuuint64_t)cols, (cuuint64_t)rows}, st[1] = {(cuuint64_t)cols * 2};
  const cuuint32_t b[2] = {(cuuint32_t)bcols, (cuuint32_t)brows};
  make_map(enc, tm, base, 2, d, st, b, sw);
}

}

extern "C" void kernel_launch(void* const* d_in, const int* in_sizes, int n_in, void* d_out, int out_size) {
  const bf16* x = (const bf16*)d_in[0];
  const bf16* mem0 = (const bf16*)d_in[1];
  const bf16* Wq = (const bf16*)d_in[2];
  const bf16* Wk = (const bf16*)d_in[3];
  const bf16* Wv = (const bf16*)d_in[4];
  const bf16* Wo = (const bf16*)d_in[5];
  const bf16* wqkv = (const bf16*)d_in[8];
  const bf16* wob = (const bf16*)d_in[9];
  const bf16* gate_w = (const bf16*)d_in[10];
  static EncFn enc = nullptr;
  static void *pK = nullptr, *pV = nullptr, *pO = nullptr, *pQ = nullptr, *pB = nullptr, *pA = nullptr;
  if (!enc) {
    void* fn = nullptr;
    cudaDriverEntryPointQueryResult qr;
    cudaGetDriverEntryPoint("cuTensorMapEncodeTiled", &fn, cudaEnableDefault, &qr);
    enc = (EncFn)fn;
    cudaGetSymbolAddress(&pK, g_K);
    cudaGetSymbolAddress(&pV, g_V);
    cudaGetSymbolAddress(&pO, g_O);
    cudaGetSymbolAddress(&pQ, g_qkv);
    cudaGetSymbolAddress(&pB, g_Ob);
    cudaGetSymbolAddress(&pA, g_acc);
    cudaFuncSetAttribute(rec_kernel, cudaFuncAttributeMaxDynamicSharedMemorySize, R_SMEM_ALLOC);
    cudaFuncSetAttribute(aux_kernel, cudaFuncAttributeMaxDynamicSharedMemorySize, A_SMEM);
  }
  CUtensorMap tmX, tmK, tmV;
  map_blk(enc, &tmX, x, S_TOK, DM, 32, 10);
  map_2d(enc, &tmK, pK, NSEG * LK, HD, LK, 64, CU_TENSOR_MAP_SWIZZLE_128B);
  map_2d(enc, &tmV, pV, NSEG * LK, HD, LK, 64, CU_TENSOR_MAP_SWIZZLE_128B);
  AuxMaps am;
  map_2d(enc, &am.xA, x, S_TOK, DM, 128, 32, CU_TENSOR_MAP_SWIZZLE_64B);
  map_blk(enc, &am.wq, Wq, DM, HD, 32, 6);
  map_blk(enc, &am.wqkv, wqkv, DM, 3 * DM, 32, 6);
  map_blk(enc, &am.wo, Wo, HD, DM, 32, 5);
  map_blk(enc, &am.wob, wob, DM, DM, 32, 5);
  map_blk(enc, &am.k, pK, NSEG * LK, HD, 80, 3);
  map_blk(enc, &am.v, pV, NSEG * LK, HD, 80, 3);
  map_2d(enc, &am.oA, pO, S_TOK, HD, 128, 32, CU_TENSOR_MAP_SWIZZLE_64B);
  map_blk(enc, &am.oS, pO, S_TOK, HD, 64, 3);
  map_2d(enc, &am.obA, pB, S_TOK, DM, 128, 32, CU_TENSOR_MAP_SWIZZLE_64B);
  map_2d(enc, &am.obS, pB, S_TOK, DM, 64, 160, CU_TENSOR_MAP_SWIZZLE_NONE);
  map_blk(enc, &am.qkvS, pQ, S_TOK, 3 * DM, 64, 3);
  map_2d(enc, &am.qkvQ, pQ, S_TOK, 3 * DM, 64, 160, CU_TENSOR_MAP_SWIZZLE_NONE);
  map_2d(enc, &am.qkvK, pQ, S_TOK, 3 * DM, 80, 160, CU_TENSOR_MAP_SWIZZLE_NONE);
  {
    const cuuint64_t d[3] = {32, S_TOK, 20}, st[2] = {DM * 4, 128};
    const cuuint32_t b[3] = {32, 64, 2};
    make_map(enc, &am.acc, pA, 3, d, st, b, CU_TENSOR_MAP_SWIZZLE_128B, CU_TENSOR_MAP_DATA_TYPE_FLOAT32);
  }
  rec_kernel<<<96, 256, R_SMEM_ALLOC, cudaStreamPerThread>>>(tmX, tmK, tmV, Wq, Wk, Wv, Wo, mem0);
  cudaLaunchConfig_t cfg = {};
  cfg.gridDim = dim3(AUX_GRID); cfg.blockDim = dim3(384); cfg.dynamicSmemBytes = A_SMEM; cfg.stream = cudaStreamPerThread;
  cudaLaunchAttribute at[1];
  at[0].id = cudaLaunchAttributeProgrammaticStreamSerialization;
  at[0].val.programmaticStreamSerializationAllowed = 1;
  cfg.attrs = at;
  cfg.numAttrs = 1;
  cudaLaunchKernelEx(&cfg, aux_kernel, am, x, gate_w, (bf16*)d_out);
}
```

```cpp
#include <cuda_runtime.h>
#include <cuda_bf16.h>
#include <cuda.h>
#include <stdint.h>
#include <type_traits>

typedef __nv_bfloat16 bf16;

namespace {

constexpr int S_TOK = 2048, DM = 640, NH = 32, DH = 192, HD = NH * DH, SEG = 32, NSEG = 64, MT = 8, LK = 40;
constexpr int SPIN_MAX = 1 << 20;

constexpr int BC_BASE = 80 * 4096, BC_COPY = 3 * 4096;
__device__ __align__(4096) unsigned char g_comm[BC_BASE + 2 * BC_COPY];
__device__ uint32_t g_epoch;
__device__ uint32_t g_err;
__device__ uint32_t g_segcnt[NSEG];
__device__ __align__(1024) bf16 g_K[NSEG * LK * HD];
__device__ __align__(1024) bf16 g_V[NSEG * LK * HD];
__device__ __align__(1024) bf16 g_O[S_TOK * HD];
__device__ __align__(1024) bf16 g_qkv[S_TOK * 3 * DM];
__device__ __align__(1024) bf16 g_Ob[S_TOK * DM];
__device__ __align__(1024) float g_acc[S_TOK * DM];
__device__ float g_gate[2 * S_TOK];
__device__ uint32_t g_cnt[512 * 8];
__device__ uint32_t g_queue;
#define GTR(i) do {} while (0)

__device__ __forceinline__ uint32_t smem_u32(const void* p) { return (uint32_t)__cvta_generic_to_shared(p); }
__device__ __forceinline__ uint32_t clk32() { uint32_t t; asm volatile("mov.u32 %0, %%clock;" : "=r"(t)::"memory"); return t; }
__device__ __forceinline__ uint32_t mapa(uint32_t a, uint32_t r) { uint32_t o; asm("mapa.shared::cluster.u32 %0, %1, %2;" : "=r"(o) : "r"(a), "r"(r)); return o; }
__device__ __forceinline__ void mbar_init(uint32_t b, uint32_t c) { asm volatile("mbarrier.init.shared::cta.b64 [%0], %1;" ::"r"(b), "r"(c) : "memory"); }
__device__ __forceinline__ void mbar_expect(uint32_t b, uint32_t bytes) { asm volatile("mbarrier.arrive.expect_tx.shared::cta.b64 _, [%0], %1;" ::"r"(b), "r"(bytes) : "memory"); }
__device__ __forceinline__ void mbar_arrive(uint32_t b) { asm volatile("mbarrier.arrive.shared::cta.b64 _, [%0];" ::"r"(b) : "memory"); }
__device__ __forceinline__ bool mbar_try(uint32_t b, uint32_t par) {
  uint32_t p;
  asm volatile("{.reg .pred p; mbarrier.try_wait.parity.shared::cta.b64 p, [%1], %2; selp.u32 %0,1,0,p;}" : "=r"(p) : "r"(b), "r"(par) : "memory");
  return p;
}
__device__ __forceinline__ bool mbar_try_cl(uint32_t b, uint32_t par) {
  uint32_t p;
  asm volatile("{.reg .pred p; mbarrier.try_wait.parity.acquire.cluster.shared::cta.b64 p, [%1], %2; selp.u32 %0,1,0,p;}" : "=r"(p) : "r"(b), "r"(par) : "memory");
  return p;
}
__device__ __forceinline__ void mbar_wait(uint32_t b, uint32_t par) {
  int n = 0;
#pragma unroll 1
  while (!mbar_try(b, par)) { if (++n > SPIN_MAX) { g_err = 1; break; } }
}
__device__ __forceinline__ void mbar_wait_cl(uint32_t b, uint32_t par) {
  int n = 0;
#pragma unroll 1
  while (!mbar_try_cl(b, par)) { if (++n > SPIN_MAX) { g_err = 2; break; } }
}
__device__ __forceinline__ void cluster_sync() { asm volatile("barrier.cluster.arrive.release.aligned; barrier.cluster.wait.acquire.aligned;" ::: "memory"); }
__device__ __forceinline__ void bar_sync(int id, int n) { asm volatile("bar.sync %0, %1;" ::"r"(id), "r"(n) : "memory"); }
__device__ __forceinline__ void bar_arrive(int id, int n) { asm volatile("bar.arrive %0, %1;" ::"r"(id), "r"(n) : "memory"); }
__device__ __forceinline__ void fence_async_smem() { asm volatile("fence.proxy.async.shared::cta;" ::: "memory"); }
__device__ __forceinline__ void ldsm4(uint32_t* r, uint32_t a) {
  asm volatile("ldmatrix.sync.aligned.m8n8.x4.shared.b16 {%0,%1,%2,%3}, [%4];" : "=r"(r[0]), "=r"(r[1]), "=r"(r[2]), "=r"(r[3]) : "r"(a) : "memory");
}
__device__ __forceinline__ void ldsm4t(uint32_t* r, uint32_t a) {
  asm volatile("ldmatrix.sync.aligned.m8n8.x4.trans.shared.b16 {%0,%1,%2,%3}, [%4];" : "=r"(r[0]), "=r"(r[1]), "=r"(r[2]), "=r"(r[3]) : "r"(a) : "memory");
}
__device__ __forceinline__ void ldsm2t(uint32_t* r, uint32_t a) {
  asm volatile("ldmatrix.sync.aligned.m8n8.x2.trans.shared.b16 {%0,%1}, [%2];" : "=r"(r[0]), "=r"(r[1]) : "r"(a) : "memory");
}
__device__ __forceinline__ void stsm4t(uint32_t a, uint32_t r0, uint32_t r1, uint32_t r2, uint32_t r3) {
  asm volatile("stmatrix.sync.aligned.m8n8.x4.trans.shared.b16 [%0], {%1,%2,%3,%4};" ::"r"(a), "r"(r0), "r"(r1), "r"(r2), "r"(r3) : "memory");
}
__device__ __forceinline__ void stsm2t(uint32_t a, uint32_t r0, uint32_t r1) {
  asm volatile("stmatrix.sync.aligned.m8n8.x2.trans.shared.b16 [%0], {%1,%2};" ::"r"(a), "r"(r0), "r"(r1) : "memory");
}
__device__ __forceinline__ uint32_t movmat(uint32_t a) { uint32_t d; asm volatile("movmatrix.sync.aligned.m8n8.trans.b16 %0, %1;" : "=r"(d) : "r"(a)); return d; }
__device__ __forceinline__ void mma16816(float* d, const uint32_t* a, uint32_t b0, uint32_t b1) {
  asm volatile("mma.sync.aligned.m16n8k16.row.col.f32.bf16.bf16.f32 {%0,%1,%2,%3}, {%4,%5,%6,%7}, {%8,%9}, {%0,%1,%2,%3};"
               : "+f"(d[0]), "+f"(d[1]), "+f"(d[2]), "+f"(d[3]) : "r"(a[0]), "r"(a[1]), "r"(a[2]), "r"(a[3]), "r"(b0), "r"(b1));
}
__device__ __forceinline__ void mma1688(float* d, uint32_t a0, uint32_t a1, uint32_t b0) {
  asm volatile("mma.sync.aligned.m16n8k8.row.col.f32.bf16.bf16.f32 {%0,%1,%2,%3}, {%4,%5}, {%6}, {%0,%1,%2,%3};"
               : "+f"(d[0]), "+f"(d[1]), "+f"(d[2]), "+f"(d[3]) : "r"(a0), "r"(a1), "r"(b0));
}
__device__ __forceinline__ uint32_t pack2(float lo, float hi) { uint32_t r; asm("cvt.rn.bf16x2.f32 %0, %1, %2;" : "=r"(r) : "f"(hi), "f"(lo)); return r; }
__device__ __forceinline__ float bf_lo(uint32_t w) { return __uint_as_float(w << 16); }
__device__ __forceinline__ float bf_hi(uint32_t w) { return __uint_as_float(w & 0xffff0000u); }
__device__ __forceinline__ float ex2(float x) { float y; asm("ex2.approx.ftz.f32 %0, %1;" : "=f"(y) : "f"(x)); return y; }
__device__ __forceinline__ void sts128(uint32_t a, uint32_t x, uint32_t y, uint32_t z, uint32_t w) { asm volatile("st.shared.v4.b32 [%0], {%1,%2,%3,%4};" ::"r"(a), "r"(x), "r"(y), "r"(z), "r"(w) : "memory"); }
__device__ __forceinline__ void sts128f(uint32_t a, float x, float y, float z, float w) { asm volatile("st.shared.v4.f32 [%0], {%1,%2,%3,%4};" ::"r"(a), "f"(x), "f"(y), "f"(z), "f"(w) : "memory"); }
__device__ __forceinline__ void sts64f(uint32_t a, float x, float y) { asm volatile("st.shared.v2.f32 [%0], {%1,%2};" ::"r"(a), "f"(x), "f"(y) : "memory"); }
__device__ __forceinline__ void sts32(uint32_t a, uint32_t x) { asm volatile("st.shared.b32 [%0], %1;" ::"r"(a), "r"(x) : "memory"); }
__device__ __forceinline__ uint32_t lds32(uint32_t a) { uint32_t v; asm volatile("ld.shared.b32 %0, [%1];" : "=r"(v) : "r"(a) : "memory"); return v; }
__device__ __forceinline__ float4 lds128f(uint32_t a) { float4 v; asm volatile("ld.shared.v4.f32 {%0,%1,%2,%3}, [%4];" : "=f"(v.x), "=f"(v.y), "=f"(v.z), "=f"(v.w) : "r"(a) : "memory"); return v; }
__device__ __forceinline__ uint4 lds128(uint32_t a) { uint4 v; asm volatile("ld.shared.v4.b32 {%0,%1,%2,%3}, [%4];" : "=r"(v.x), "=r"(v.y), "=r"(v.z), "=r"(v.w) : "r"(a) : "memory"); return v; }
__device__ __forceinline__ float2 lds64f(uint32_t a) { float2 v; asm volatile("ld.shared.v2.f32 {%0,%1}, [%2];" : "=f"(v.x), "=f"(v.y) : "r"(a) : "memory"); return v; }
__device__ __forceinline__ void st_async2(uint32_t a, uint32_t x, uint32_t y, uint32_t bar) {
  asm volatile("st.async.weak.shared::cluster.mbarrier::complete_tx::bytes.v2.b32 [%0], {%1,%2}, [%3];" ::"r"(a), "r"(x), "r"(y), "r"(bar) : "memory");
}
__device__ __forceinline__ void st_async4(uint32_t a, uint32_t x, uint32_t y, uint32_t z, uint32_t w, uint32_t bar) {
  asm volatile("st.async.weak.shared::cluster.mbarrier::complete_tx::bytes.v4.b32 [%0], {%1,%2,%3,%4}, [%5];" ::"r"(a), "r"(x), "r"(y), "r"(z), "r"(w), "r"(bar) : "memory");
}
__device__ __forceinline__ void sts64(uint32_t a, uint32_t x, uint32_t y) { asm volatile("st.shared.v2.b32 [%0], {%1,%2};" ::"r"(a), "r"(x), "r"(y) : "memory"); }
__device__ __forceinline__ bool bar_red_or(int id, int n, bool q) {
  uint32_t r;
  asm volatile("{.reg .pred p, q; setp.ne.u32 q, %3, 0; barrier.cta.red.or.aligned.pred p, %1, %2, q; selp.u32 %0,1,0,p;}" : "=r"(r) : "r"(id), "r"(n), "r"((uint32_t)q) : "memory");
  return r;
}
__device__ __forceinline__ float rcp(float x) { float y; asm("rcp.approx.ftz.f32 %0, %1;" : "=f"(y) : "f"(x)); return y; }
__device__ __forceinline__ uint32_t hadd2(uint32_t a, uint32_t b) { uint32_t r; asm("add.rn.bf16x2 %0, %1, %2;" : "=r"(r) : "r"(a), "r"(b)); return r; }
__device__ __forceinline__ uint32_t pin(uint32_t v) { asm volatile("" : "+r"(v)); return v; }
__device__ __forceinline__ uint32_t opaque(uint32_t v) { return __shfl_sync(~0u, v, threadIdx.x & 31); }
__device__ __forceinline__ uint4 ldg_rlx128(const void* p) {
  uint4 v; asm volatile("ld.relaxed.gpu.global.v4.b32 {%0,%1,%2,%3}, [%4];" : "=r"(v.x), "=r"(v.y), "=r"(v.z), "=r"(v.w) : "l"(p) : "memory"); return v;
}
__device__ __forceinline__ uint32_t ldg_rlx32(const void* p) {
  uint32_t v; asm volatile("ld.relaxed.gpu.global.b32 %0, [%1];" : "=r"(v) : "l"(p) : "memory"); return v;
}
__device__ __forceinline__ void spin_until(uint32_t t0, uint32_t d) {
#pragma unroll 1
  while (clk32() - t0 < d) {}
}
__device__ __forceinline__ void stg_rlx64(void* p, uint32_t a, uint32_t b) {
  asm volatile("{.reg .b64 t; mov.b64 t, {%1,%2}; st.relaxed.gpu.global.b64 [%0], t;}" ::"l"(p), "r"(a), "r"(b) : "memory");
}
__device__ __forceinline__ uint32_t ldg_acq32(const void* p) { uint32_t v; asm volatile("ld.acquire.gpu.global.b32 %0, [%1];" : "=r"(v) : "l"(p) : "memory"); return v; }
__device__ __forceinline__ void stg_rel32(void* p, uint32_t v) { asm volatile("st.release.gpu.global.b32 [%0], %1;" ::"l"(p), "r"(v) : "memory"); }
__device__ __forceinline__ void cp_async16(uint32_t dst, const void* src) { asm volatile("cp.async.cg.shared.global [%0], [%1], 16;" ::"r"(dst), "l"(src) : "memory"); }
__device__ __forceinline__ void cp_async_wait_all() { asm volatile("cp.async.wait_all;" ::: "memory"); }
__device__ __forceinline__ void prefetch_l2(const void* p) { asm volatile("prefetch.global.L2 [%0];" ::"l"(p)); }
__device__ __forceinline__ void tma_load3(uint32_t dst, const CUtensorMap* tm, int c0, int c1, int c2, uint32_t bar) {
  asm volatile("cp.async.bulk.tensor.3d.shared::cluster.global.mbarrier::complete_tx::bytes [%0], [%1, {%3,%4,%5}], [%2];"
               ::"r"(dst), "l"(tm), "r"(bar), "r"(c0), "r"(c1), "r"(c2) : "memory");
}
__device__ __forceinline__ void tma_load2(uint32_t dst, const CUtensorMap* tm, int c0, int c1, uint32_t bar) {
  asm volatile("cp.async.bulk.tensor.2d.shared::cluster.global.mbarrier::complete_tx::bytes [%0], [%1, {%3,%4}], [%2];"
               ::"r"(dst), "l"(tm), "r"(bar), "r"(c0), "r"(c1) : "memory");
}
__device__ __forceinline__ void prefetch_map(const CUtensorMap* tm) { asm volatile("prefetch.tensormap [%0];" ::"l"(tm) : "memory"); }
__device__ __forceinline__ void tma_store2(const CUtensorMap* tm, uint32_t src, int c0, int c1) {
  asm volatile("cp.async.bulk.tensor.2d.global.shared::cta.bulk_group [%0, {%2,%3}], [%1];" ::"l"(tm), "r"(src), "r"(c0), "r"(c1) : "memory");
}
__device__ __forceinline__ void bulk_commit() { asm volatile("cp.async.bulk.commit_group;" ::: "memory"); }
__device__ __forceinline__ void bulk_wait0() { asm volatile("cp.async.bulk.wait_group 0;" ::: "memory"); }
__device__ __forceinline__ void bulk_wait_read0() { asm volatile("cp.async.bulk.wait_group.read 0;" ::: "memory"); }
__device__ __forceinline__ void wg_fence() { asm volatile("wgmma.fence.sync.aligned;" ::: "memory"); }
__device__ __forceinline__ void wg_commit() { asm volatile("wgmma.commit_group.sync.aligned;" ::: "memory"); }
__device__ __forceinline__ void wg_wait0() { asm volatile("wgmma.wait_group.sync.aligned 0;" ::: "memory"); }
__device__ __forceinline__ uint64_t desc_sw128(uint32_t addr) {
  return (uint64_t)((addr & 0x3FFFF) >> 4) | ((uint64_t)1 << 16) | ((uint64_t)64 << 32) | ((uint64_t)1 << 62);
}
template <int ACC>
__device__ __forceinline__ void wgmma_rs32(float* d, const uint32_t* a, uint64_t db) {
  asm volatile("{.reg .pred p; setp.ne.b32 p, %21, 0;\n"
               "wgmma.mma_async.sync.aligned.m64n32k16.f32.bf16.bf16 {%0,%1,%2,%3,%4,%5,%6,%7,%8,%9,%10,%11,%12,%13,%14,%15}, {%16,%17,%18,%19}, %20, p, 1, 1, 0;}"
               : "+f"(d[0]), "+f"(d[1]), "+f"(d[2]), "+f"(d[3]), "+f"(d[4]), "+f"(d[5]), "+f"(d[6]), "+f"(d[7]), "+f"(d[8]), "+f"(d[9]),
                 "+f"(d[10]), "+f"(d[11]), "+f"(d[12]), "+f"(d[13]), "+f"(d[14]), "+f"(d[15])
               : "r"(a[0]), "r"(a[1]), "r"(a[2]), "r"(a[3]), "l"(db), "n"(ACC));
}

template <int N> __device__ __forceinline__ void fence_regs(float* d) {
#pragma unroll
  for (int i = 0; i < N; i++) asm volatile("" : "+f"(d[i])::"memory");
}
__device__ __forceinline__ void wg_wait1() { asm volatile("wgmma.wait_group.sync.aligned 1;" ::: "memory"); }
__device__ __forceinline__ void tma_store3(const CUtensorMap* tm, uint32_t src, int c0, int c1, int c2) {
  asm volatile("cp.async.bulk.tensor.3d.global.shared::cta.bulk_group [%0, {%2,%3,%4}], [%1];" ::"l"(tm), "r"(src), "r"(c0), "r"(c1), "r"(c2) : "memory");
}
__device__ __forceinline__ void tma_red3(const CUtensorMap* tm, uint32_t src, int c0, int c1, int c2) {
  asm volatile("cp.reduce.async.bulk.tensor.3d.global.shared::cta.add.bulk_group [%0, {%2,%3,%4}], [%1];" ::"l"(tm), "r"(src), "r"(c0), "r"(c1), "r"(c2) : "memory");
}
__device__ __forceinline__ void stsm4(uint32_t a, uint32_t r0, uint32_t r1, uint32_t r2, uint32_t r3) {
  asm volatile("stmatrix.sync.aligned.m8n8.x4.shared.b16 [%0], {%1,%2,%3,%4};" ::"r"(a), "r"(r0), "r"(r1), "r"(r2), "r"(r3) : "memory");
}
__device__ __forceinline__ uint2 lds64(uint32_t a) { uint2 v; asm volatile("ld.shared.v2.b32 {%0,%1}, [%2];" : "=r"(v.x), "=r"(v.y) : "r"(a) : "memory"); return v; }
__device__ __forceinline__ uint32_t hmul2(uint32_t a, uint32_t b) { uint32_t r; asm("mul.rn.bf16x2 %0, %1, %2;" : "=r"(r) : "r"(a), "r"(b)); return r; }
__device__ __forceinline__ void wgmma_ss192t(float* d, uint64_t da, uint64_t db, int acc) {
  asm volatile("{.reg .pred p; setp.ne.b32 p, %98, 0;\n"
    "wgmma.mma_async.sync.aligned.m64n192k16.f32.bf16.bf16 "
    "{%0,%1,%2,%3,%4,%5,%6,%7,%8,%9,%10,%11,%12,%13,%14,%15,%16,%17,%18,%19,%20,%21,%22,%23,%24,%25,%26,%27,%28,%29,%30,%31,%32,%33,%34,%35,%36,%37,%38,%39,%40,%41,%42,%43,%44,%45,%46,%47,%48,%49,%50,%51,%52,%53,%54,%55,%56,%57,%58,%59,%60,%61,%62,%63,%64,%65,%66,%67,%68,%69,%70,%71,%72,%73,%74,%75,%76,%77,%78,%79,%80,%81,%82,%83,%84,%85,%86,%87,%88,%89,%90,%91,%92,%93,%94,%95}, %96, %97, p, 1, 1, 0, 1;}"
    : "+f"(d[0]), "+f"(d[1]), "+f"(d[2]), "+f"(d[3]), "+f"(d[4]), "+f"(d[5]), "+f"(d[6]), "+f"(d[7]), "+f"(d[8]), "+f"(d[9]), "+f"(d[10]), "+f"(d[11]),
      "+f"(d[12]), "+f"(d[13]), "+f"(d[14]), "+f"(d[15]), "+f"(d[16]), "+f"(d[17]), "+f"(d[18]), "+f"(d[19]), "+f"(d[20]), "+f"(d[21]), "+f"(d[22]),
      "+f"(d[23]), "+f"(d[24]), "+f"(d[25]), "+f"(d[26]), "+f"(d[27]), "+f"(d[28]), "+f"(d[29]), "+f"(d[30]), "+f"(d[31]), "+f"(d[32]), "+f"(d[33]),
      "+f"(d[34]), "+f"(d[35]), "+f"(d[36]), "+f"(d[37]), "+f"(d[38]), "+f"(d[39]), "+f"(d[40]), "+f"(d[41]), "+f"(d[42]), "+f"(d[43]), "+f"(d[44]),
      "+f"(d[45]), "+f"(d[46]), "+f"(d[47]), "+f"(d[48]), "+f"(d[49]), "+f"(d[50]), "+f"(d[51]), "+f"(d[52]), "+f"(d[53]), "+f"(d[54]), "+f"(d[55]),
      "+f"(d[56]), "+f"(d[57]), "+f"(d[58]), "+f"(d[59]), "+f"(d[60]), "+f"(d[61]), "+f"(d[62]), "+f"(d[63]), "+f"(d[64]), "+f"(d[65]), "+f"(d[66]),
      "+f"(d[67]), "+f"(d[68]), "+f"(d[69]), "+f"(d[70]), "+f"(d[71]), "+f"(d[72]), "+f"(d[73]), "+f"(d[74]), "+f"(d[75]), "+f"(d[76]), "+f"(d[77]),
      "+f"(d[78]), "+f"(d[79]), "+f"(d[80]), "+f"(d[81]), "+f"(d[82]), "+f"(d[83]), "+f"(d[84]), "+f"(d[85]), "+f"(d[86]), "+f"(d[87]), "+f"(d[88]),
      "+f"(d[89]), "+f"(d[90]), "+f"(d[91]), "+f"(d[92]), "+f"(d[93]), "+f"(d[94]), "+f"(d[95])
    : "l"(da), "l"(db), "r"(acc));
}
__device__ __forceinline__ void wgmma_ss128t(float* d, uint64_t da, uint64_t db, int acc) {
  asm volatile("{.reg .pred p; setp.ne.b32 p, %66, 0;\n"
    "wgmma.mma_async.sync.aligned.m64n128k16.f32.bf16.bf16 "
    "{%0,%1,%2,%3,%4,%5,%6,%7,%8,%9,%10,%11,%12,%13,%14,%15,%16,%17,%18,%19,%20,%21,%22,%23,%24,%25,%26,%27,%28,%29,%30,%31,%32,%33,%34,%35,%36,%37,%38,%39,%40,%41,%42,%43,%44,%45,%46,%47,%48,%49,%50,%51,%52,%53,%54,%55,%56,%57,%58,%59,%60,%61,%62,%63}, %64, %65, p, 1, 1, 0, 1;}"
    : "+f"(d[0]), "+f"(d[1]), "+f"(d[2]), "+f"(d[3]), "+f"(d[4]), "+f"(d[5]), "+f"(d[6]), "+f"(d[7]), "+f"(d[8]), "+f"(d[9]), "+f"(d[10]), "+f"(d[11]),
      "+f"(d[12]), "+f"(d[13]), "+f"(d[14]), "+f"(d[15]), "+f"(d[16]), "+f"(d[17]), "+f"(d[18]), "+f"(d[19]), "+f"(d[20]), "+f"(d[21]), "+f"(d[22]),
      "+f"(d[23]), "+f"(d[24]), "+f"(d[25]), "+f"(d[26]), "+f"(d[27]), "+f"(d[28]), "+f"(d[29]), "+f"(d[30]), "+f"(d[31]), "+f"(d[32]), "+f"(d[33]),
      "+f"(d[34]), "+f"(d[35]), "+f"(d[36]), "+f"(d[37]), "+f"(d[38]), "+f"(d[39]), "+f"(d[40]), "+f"(d[41]), "+f"(d[42]), "+f"(d[43]), "+f"(d[44]),
      "+f"(d[45]), "+f"(d[46]), "+f"(d[47]), "+f"(d[48]), "+f"(d[49]), "+f"(d[50]), "+f"(d[51]), "+f"(d[52]), "+f"(d[53]), "+f"(d[54]), "+f"(d[55]),
      "+f"(d[56]), "+f"(d[57]), "+f"(d[58]), "+f"(d[59]), "+f"(d[60]), "+f"(d[61]), "+f"(d[62]), "+f"(d[63])
    : "l"(da), "l"(db), "r"(acc));
}
__device__ __forceinline__ void wgmma_rs80(float* d, const uint32_t* a, uint64_t db, int acc) {
  asm volatile("{.reg .pred p; setp.ne.b32 p, %45, 0;\n"
    "wgmma.mma_async.sync.aligned.m64n80k16.f32.bf16.bf16 "
    "{%0,%1,%2,%3,%4,%5,%6,%7,%8,%9,%10,%11,%12,%13,%14,%15,%16,%17,%18,%19,%20,%21,%22,%23,%24,%25,%26,%27,%28,%29,%30,%31,%32,%33,%34,%35,%36,%37,%38,%39}, {%40,%41,%42,%43}, %44, p, 1, 1, 0;}"
    : "+f"(d[0]), "+f"(d[1]), "+f"(d[2]), "+f"(d[3]), "+f"(d[4]), "+f"(d[5]), "+f"(d[6]), "+f"(d[7]), "+f"(d[8]), "+f"(d[9]), "+f"(d[10]), "+f"(d[11]),
      "+f"(d[12]), "+f"(d[13]), "+f"(d[14]), "+f"(d[15]), "+f"(d[16]), "+f"(d[17]), "+f"(d[18]), "+f"(d[19]), "+f"(d[20]), "+f"(d[21]), "+f"(d[22]),
      "+f"(d[23]), "+f"(d[24]), "+f"(d[25]), "+f"(d[26]), "+f"(d[27]), "+f"(d[28]), "+f"(d[29]), "+f"(d[30]), "+f"(d[31]), "+f"(d[32]), "+f"(d[33]),
      "+f"(d[34]), "+f"(d[35]), "+f"(d[36]), "+f"(d[37]), "+f"(d[38]), "+f"(d[39])
    : "r"(a[0]), "r"(a[1]), "r"(a[2]), "r"(a[3]), "l"(db), "r"(acc));
}
__device__ __forceinline__ void wgmma_rs192t(float* d, const uint32_t* a, uint64_t db, int acc) {
  asm volatile("{.reg .pred p; setp.ne.b32 p, %101, 0;\n"
    "wgmma.mma_async.sync.aligned.m64n192k16.f32.bf16.bf16 "
    "{%0,%1,%2,%3,%4,%5,%6,%7,%8,%9,%10,%11,%12,%13,%14,%15,%16,%17,%18,%19,%20,%21,%22,%23,%24,%25,%26,%27,%28,%29,%30,%31,%32,%33,%34,%35,%36,%37,%38,%39,%40,%41,%42,%43,%44,%45,%46,%47,%48,%49,%50,%51,%52,%53,%54,%55,%56,%57,%58,%59,%60,%61,%62,%63,%64,%65,%66,%67,%68,%69,%70,%71,%72,%73,%74,%75,%76,%77,%78,%79,%80,%81,%82,%83,%84,%85,%86,%87,%88,%89,%90,%91,%92,%93,%94,%95}, {%96,%97,%98,%99}, %100, p, 1, 1, 1;}"
    : "+f"(d[0]), "+f"(d[1]), "+f"(d[2]), "+f"(d[3]), "+f"(d[4]), "+f"(d[5]), "+f"(d[6]), "+f"(d[7]), "+f"(d[8]), "+f"(d[9]), "+f"(d[10]), "+f"(d[11]),
      "+f"(d[12]), "+f"(d[13]), "+f"(d[14]), "+f"(d[15]), "+f"(d[16]), "+f"(d[17]), "+f"(d[18]), "+f"(d[19]), "+f"(d[20]), "+f"(d[21]), "+f"(d[22]),
      "+f"(d[23]), "+f"(d[24]), "+f"(d[25]), "+f"(d[26]), "+f"(d[27]), "+f"(d[28]), "+f"(d[29]), "+f"(d[30]), "+f"(d[31]), "+f"(d[32]), "+f"(d[33]),
      "+f"(d[34]), "+f"(d[35]), "+f"(d[36]), "+f"(d[37]), "+f"(d[38]), "+f"(d[39]), "+f"(d[40]), "+f"(d[41]), "+f"(d[42]), "+f"(d[43]), "+f"(d[44]),
      "+f"(d[45]), "+f"(d[46]), "+f"(d[47]), "+f"(d[48]), "+f"(d[49]), "+f"(d[50]), "+f"(d[51]), "+f"(d[52]), "+f"(d[53]), "+f"(d[54]), "+f"(d[55]),
      "+f"(d[56]), "+f"(d[57]), "+f"(d[58]), "+f"(d[59]), "+f"(d[60]), "+f"(d[61]), "+f"(d[62]), "+f"(d[63]), "+f"(d[64]), "+f"(d[65]), "+f"(d[66]),
      "+f"(d[67]), "+f"(d[68]), "+f"(d[69]), "+f"(d[70]), "+f"(d[71]), "+f"(d[72]), "+f"(d[73]), "+f"(d[74]), "+f"(d[75]), "+f"(d[76]), "+f"(d[77]),
      "+f"(d[78]), "+f"(d[79]), "+f"(d[80]), "+f"(d[81]), "+f"(d[82]), "+f"(d[83]), "+f"(d[84]), "+f"(d[85]), "+f"(d[86]), "+f"(d[87]), "+f"(d[88]),
      "+f"(d[89]), "+f"(d[90]), "+f"(d[91]), "+f"(d[92]), "+f"(d[93]), "+f"(d[94]), "+f"(d[95])
    : "r"(a[0]), "r"(a[1]), "r"(a[2]), "r"(a[3]), "l"(db), "r"(acc));
}

constexpr int NPQ = 2;
#define NQ0 10
#define NQ1 12
#define NO_EARLY 6
#define WN1 14
#define PD0 1450
#define PD1 280
#define PW0 700
#define NQ_WIN 4
constexpr int NQM = NQ0 > NQ1 ? NQ0 : NQ1;
constexpr int R_WQ = 0;
constexpr int R_WO = R_WQ + 8 * (20 - NPQ) * 512;
constexpr int R_XT = R_WO + 14 * 12 * 512;
constexpr int R_QB = R_XT + 40960;
constexpr int R_KB = R_QB + 1024;
constexpr int R_QA = R_KB + 1024;
constexpr int R_KT = R_QA + 1024;
constexpr int R_VT = R_KT + 5120;
constexpr int R_MEM = R_VT + 5120;
constexpr int R_SX = R_MEM + 10240;
constexpr int R_O2 = R_SX + 3840;
constexpr int R_RB = R_O2 + 1024;
constexpr int R_BAR = R_RB + 2048;
constexpr int R_SMEM = R_BAR + 64;
static_assert(NPQ == 2 && R_XT % 1024 == 0 && R_KT % 1024 == 0 && R_VT % 1024 == 0 && R_SX % 1024 == 0 && R_MEM % 1024 == 0 && R_WO % 1024 == 0, "align");
constexpr int R_SMEM_ALLOC = R_SMEM;
static_assert(R_SMEM_ALLOC <= 232448, "smem");

#define TR(i) do {} while (0)

__global__ void __cluster_dims__(3, 1, 1) __launch_bounds__(256, 1)
rec_kernel(const __grid_constant__ CUtensorMap tmX, const __grid_constant__ CUtensorMap tmK, const __grid_constant__ CUtensorMap tmV,
           const __grid_constant__ CUtensorMap tmWq, const __grid_constant__ CUtensorMap tmWq2, const __grid_constant__ CUtensorMap tmWk,
           const __grid_constant__ CUtensorMap tmWv, const __grid_constant__ CUtensorMap tmWo, const bf16* __restrict__ mem0,
           const bf16* __restrict__ Wq, const bf16* __restrict__ Wo) {
  extern __shared__ __align__(1024) unsigned char smem[];
  const uint32_t sb = smem_u32(smem);
  const int tid = threadIdx.x, lane = tid & 31, wid = __shfl_sync(~0u, tid >> 5, 0), g = wid >> 2, w = wid & 3;
  const int cta = blockIdx.x, head = cta / 3, rank = cta % 3;
  const int D0 = head * DH + rank * 64;
  const int tile0 = rank == 0 ? 0 : (rank == 1 ? 14 : 26);
  const uint32_t XBAR = sb + R_BAR, SBAR = XBAR + 8, OBAR = XBAR + 16, WBAR = XBAR + 24;
  asm volatile("griddepcontrol.launch_dependents;" ::: "memory");
  GTR(0);
  if (wid == 0) {
    if (lane == 0) {
      mbar_init(XBAR, 1); mbar_init(SBAR, 1); mbar_init(OBAR, 1); mbar_init(WBAR, 1); mbar_init(WBAR + 8, 1); mbar_init(WBAR + 16, 1);
      asm volatile("fence.mbarrier_init.release.cluster;" ::: "memory");
      mbar_expect(WBAR, 81920); mbar_expect(WBAR + 8, 81920 + 2 * NPQ * 2048); mbar_expect(XBAR, 40960);
    }
    __syncwarp();
    if (lane < 5) tma_load2(sb + lane * 16384, &tmWk, D0, lane * 128, WBAR);
    if (lane == 5) tma_load3(sb + R_XT, &tmX, 0, 0, 0, XBAR);
    if (lane < 5) tma_load2(lane < 4 ? sb + 81920 + lane * 16384 : sb + R_QB, &tmWv, D0, lane * 128, WBAR + 8);
    if (lane < 2) tma_load2(sb + R_QB + 16384 + lane * 4096, &tmWq2, D0, lane * 320, WBAR + 8);
  }
  if (tid == 32) { prefetch_map(&tmWq); prefetch_map(&tmWo); prefetch_map(&tmK); prefetch_map(&tmV); }
  const uint32_t epoch = *(volatile uint32_t*)&g_epoch + 1;
  __syncthreads();
  GTR(1);
#pragma unroll
  for (int i = 0; i < 5; i++) { const int l = tid + i * 256; prefetch_l2((l < 640 ? Wq : Wo - 40960) + (size_t)cta * 40960 + l * 64); }
  uint32_t wk[20][4], wv[20][4], wqp[NPQ][4];
  uint32_t m0[3][4];
  {
    const int i = tid & 127, col = g * 320 + (i >> 4) * 16 + ((i >> 2) & 1) * 8 + ((i >> 3) & 1) * 4 + (i & 3);
    const unsigned short* m = (const unsigned short*)mem0 + col;
#pragma unroll
    for (int j = 0; j < 3; j++)
#pragma unroll
      for (int q = 0; q < 4; q++)
        m0[j][q] = (j < 2 || w < 2) ? (uint32_t)m[(2 * q) * DM + j * 128] | ((uint32_t)m[(2 * q + 1) * DM + j * 128] << 16) : 0u;
  }
  {
    const uint32_t p = sb + (lane >> 4) * 1024 + (lane & 7) * 128 + (((2 * w + ((lane >> 3) & 1)) ^ (lane & 7)) << 4);
    mbar_wait(WBAR, 0);
    GTR(2);
#pragma unroll
    for (int f = 0; f < 20; f++) ldsm4t(wk[f], p + g * 40960 + f * 2048);
    mbar_wait(WBAR + 8, 0);
    GTR(3);
#pragma unroll
    for (int f = 0; f < 20; f++) ldsm4t(wv[f], (f >= 12 && g == 1) ? p + R_QB + (f - 12) * 2048 : p + 81920 + g * 40960 + f * 2048);
#pragma unroll
    for (int f = 0; f < NPQ; f++) ldsm4t(wqp[f], p + R_QB + 16384 + g * 4096 + f * 2048);
  }
  __syncthreads();
  asm volatile("barrier.cluster.arrive.relaxed.aligned;" ::: "memory");
  if (wid == 0) {
    if (lane == 0) mbar_expect(WBAR + 16, 18 * 4096 + 21 * 4096);
    __syncwarp();
    if (lane < 4) tma_load2(sb + R_WQ + lane * 18432, &tmWq, D0, (lane >> 1) * 320 + 32 + (lane & 1) * 144, WBAR + 16);
    else if (lane < 7) tma_load3(sb + R_WO + ((lane - 1 - rank) % 3) * 28672, &tmWo, 0, head * DH + (lane - 4) * 64, tile0 >> 1, WBAR + 16);
    __syncwarp();
  }
  GTR(4);

  const uint32_t rF_ = opaque(sb + lane * 16);
  const uint32_t rM_ = opaque(sb + R_MEM + g * 5120 + (lane >> 3) * 128 + (((lane & 7) ^ (((lane >> 3) & 1) << 2)) << 4));
  const uint32_t rP_ = opaque(sb + (lane >> 4) * 1024 + (lane & 7) * 128 + (((2 * w + ((lane >> 3) & 1)) ^ (lane & 7)) << 4));
  const uint32_t rA_ = opaque(sb + R_MEM + g * 5120 + (((tid & 127) >> 4) * 2 + ((tid >> 2) & 1)) * 128 +
                             (((((tid >> 3) & 1) * 4 + (tid & 3)) ^ (((tid >> 2) & 1) << 2)) << 4));
#pragma unroll
  for (int j = 0; j < 3; j++) if (j < 2 || w < 2) sts128(rA_ + j * 2048, m0[j][0], m0[j][1], m0[j][2], m0[j][3]);
  const uint32_t rD1_ = opaque(sb + ((lane & 8) ? R_QB : R_QA) + (lane & 7) * 128 + (((lane >> 4) ^ (lane & 7)) << 4));
  const uint32_t rD2_ = opaque(sb + R_KT + (w == 0 ? -2048 : 2048 * w - 1024) + (lane & 7) * 128 + (((lane >> 3) ^ (lane & 7)) << 4));
  const bool isred = cta < 80;
  const uint32_t pubo = BC_BASE + (cta % 40 < 32 ? (cta / 40) * 4096 + (cta % 40) * 128 : 8192 + (cta / 40) * 1024 + (cta % 40 - 32) * 128);
  const int tA = g == 1 ? 2 * w : (rank != 1 ? (w < 2 ? 8 + 2 * w : 10 + w) : 8 + w);
  const bool two = g == 1 || (w < 2 && rank != 1);
  const uint32_t r1 = rank == 2 ? 0 : rank + 1, r2 = rank == 0 ? 2 : rank - 1;
  const uint32_t oA_ = opaque(((tile0 + tA) * 2 + (lane >> 4)) * 4096 + head * 128 + (lane & 15) * 8 + (epoch & 1));
  const uint32_t rW_ = opaque(sb + R_WO + (tA >> 1) * 4096 + ((lane >> 4) * 8 + (lane & 7)) * 64 +
                             (((2 * (tA & 1) + ((lane >> 3) & 1)) ^ ((lane >> 1) & 3)) << 4));
  uint32_t wqt[NQM][4];
  int s = -1;

#define WOFF(ks) (((ks) >> 2) * 28672 + ((ks) & 3) * 1024)
#define ISSUE(G, i) do { const int j_ = (i) >> 1; \
      const uint64_t d_ = ((uint64_t)0x40000040 << 32) | (dlo + (((G) * 20480 + (j_ >> 2) * 4096 + (j_ & 3) * 32) >> 4)); \
      if ((i) & 1) { if (j_ == 0) wgmma_rs32<0>(dv, wv[j_], d_); else wgmma_rs32<1>(dv, wv[j_], d_); } \
      else { if (j_ == 0) wgmma_rs32<0>(dk, wk[j_], d_); else wgmma_rs32<1>(dk, wk[j_], d_); } } while (0)

  auto window = [&](auto G_, auto FIRST_) {
    constexpr int G = decltype(G_)::value;
    constexpr bool FIRST = decltype(FIRST_)::value;
    constexpr int NQ = G ? NQ1 : NQ0;
    const uint32_t t0 = clk32();
    const uint32_t rF = pin(rF_), rP = pin(rP_), rA = pin(rA_);
    const uint32_t tag = (s ^ pin(oA_)) & 1;
    float dk[16], dv[16];
    const uint32_t dlo = pin(((sb + R_XT) >> 4) | 0x10000);
    const uint32_t wqS = rP + R_WQ + G * (20 - NPQ) * 2048;
    const uint32_t xa = rF + R_XT + w * 512;
    if constexpr (G == 1) {
      const bool duty = isred && !FIRST;
      mbar_wait(XBAR, (s + 1) & 1);
      wg_fence();
#pragma unroll
      for (int i = 0; i < WN1; i++) ISSUE(1, i);
      wg_commit();
      const uint32_t ln = (rF - sb) >> 4;
      const unsigned char* rp = g_comm + (cta * 4096 + w * 1024 + ln * 4);
      uint32_t x[8];
#pragma unroll
      for (int j = 0; j < 8; j++) x[j] = 0;
      if (duty) {
        spin_until(t0, PD1);
#pragma unroll
        for (int j = 0; j < 8; j++) x[j] = ldg_rlx32(rp + j * 128);
      }
      TR(9);
      wg_fence();
#pragma unroll
      for (int i = WN1; i < 40; i++) ISSUE(1, i);
      wg_commit();
      if (duty) {
        unsigned char* fp = g_comm + (pubo + (ln & 1) * BC_COPY + (ln >> 1) * 8);
        const uint32_t sa = sb + R_RB + w * 256 + (((ln & 1) * 4 + (ln >> 3)) * 4 + ((ln >> 1) & 3)) * 8;
        int n = 0;
#pragma unroll 1
        while (true) {
          const uint32_t bad = ((((x[0] ^ tag) | (x[1] ^ tag)) | ((x[2] ^ tag) | (x[3] ^ tag))) | (((x[4] ^ tag) | (x[5] ^ tag)) | ((x[6] ^ tag) | (x[7] ^ tag)))) & 1;
          const float lo = ((bf_lo(x[0]) + bf_lo(x[1])) + (bf_lo(x[2]) + bf_lo(x[3]))) + ((bf_lo(x[4]) + bf_lo(x[5])) + (bf_lo(x[6]) + bf_lo(x[7])));
          const float hi = ((bf_hi(x[0]) + bf_hi(x[1])) + (bf_hi(x[2]) + bf_hi(x[3]))) + ((bf_hi(x[4]) + bf_hi(x[5])) + (bf_hi(x[6]) + bf_hi(x[7])));
          sts64f(sa, lo, hi);
          if (!__any_sync(~0u, bad)) break;
#pragma unroll
          for (int j = 0; j < 8; j++) x[j] = ldg_rlx32(rp + j * 128);
          if (++n > SPIN_MAX) { g_err = 4; break; }
        }
        TR(10);
        if (w == 0) {
          bar_sync(2, 128);
          const uint32_t a = sb + R_RB + (ln >> 1) * 16;
          const float4 p0 = lds128f(a), p1 = lds128f(a + 256), p2 = lds128f(a + 512), p3 = lds128f(a + 768);
          const uint32_t w0 = pack2((p0.x + p1.x) + (p2.x + p3.x), (p0.y + p1.y) + (p2.y + p3.y));
          const uint32_t w1 = pack2((p0.z + p1.z) + (p2.z + p3.z), (p0.w + p1.w) + (p2.w + p3.w));
          stg_rlx64(fp, (w0 & ~1u) | tag, w1);
        } else {
          bar_arrive(2, 128);
        }
        TR(11);
      }
      wg_wait0();
#pragma unroll
      for (int q = 0; q < 4; q++) sts128f(xa + 20480 + q * 2048, dv[4 * q], dv[4 * q + 1], dv[4 * q + 2], dv[4 * q + 3]);
#pragma unroll
      for (int f = 0; f < NQ - 4; f++) if (!FIRST) ldsm4t(wqt[f], wqS + f * 2048);
    } else {
      if (!FIRST) {
        fence_async_smem();
        if (w == 3) {
          const uint32_t a = rF + (rF - sb);
          const uint4 a0 = lds128(a + R_KT), a1 = lds128(a + R_KT + 16), c0 = lds128(a + R_KB), c1 = lds128(a + R_KB + 16);
          sts128(a + R_KT, hadd2(a0.x, c0.x), hadd2(a0.y, c0.y), hadd2(a0.z, c0.z), hadd2(a0.w, c0.w));
          sts128(a + R_KT + 16, hadd2(a1.x, c1.x), hadd2(a1.y, c1.y), hadd2(a1.z, c1.z), hadd2(a1.w, c1.w));
          fence_async_smem();
          bar_sync(4, 128);
          if (rF == sb) {
            if (s > 0) {
              bulk_wait0();
              asm volatile("red.relaxed.gpu.global.add.u32 [%0], 1;" ::"l"(&g_segcnt[s - 1]) : "memory");
            }
            tma_store2(&tmK, sb + R_KT, D0, s * LK);
            tma_store2(&tmV, sb + R_VT, D0, s * LK);
            bulk_commit();
          }
          __syncwarp();
        } else {
          bar_arrive(4, 128);
        }
      }
#pragma unroll
      for (int f = 0; f < NQ_WIN; f++) if (!FIRST) ldsm4t(wqt[f], wqS + f * 2048);
      mbar_wait(XBAR, (s + 1) & 1);
      if (!FIRST) spin_until(t0, PW0);
      wg_fence();
#pragma unroll
      for (int i = 0; i < 40; i++) ISSUE(0, i);
      wg_commit();
      if (!FIRST && w == 3) { if (rF == sb) bulk_wait_read0(); __syncwarp(); }
    }
    const unsigned char* yp = g_comm + (BC_BASE + (cta & 1) * BC_COPY + G * 4096 + (rF - sb) + w * 512);
    const unsigned char* yp2 = yp + (8192 - G * 3072);
    uint4 y0, y1, y2;
    if (!FIRST) {
      spin_until(t0, PD0);
      y0 = ldg_rlx128(yp);
      y1 = ldg_rlx128(yp + 2048);
      y2 = make_uint4(tag, 0, tag, 0);
      if (w < 2) y2 = ldg_rlx128(yp2);
    }
    TR(13);
    if constexpr (G == 0) {
      wg_wait0();
#pragma unroll
      for (int q = 0; q < 4; q++) sts128f(xa + q * 2048, dk[4 * q], dk[4 * q + 1], dk[4 * q + 2], dk[4 * q + 3]);
    }
    TR(12);
    __syncthreads();
    {
      const float* d = G ? dk : dv;
      uint32_t pk[8];
#pragma unroll
      for (int q = 0; q < 4; q++) {
        const float4 o = lds128f(xa + (G ^ 1) * 20480 + q * 2048);
        pk[2 * q] = pack2(d[4 * q] + o.x, d[4 * q + 1] + o.y); pk[2 * q + 1] = pack2(d[4 * q + 2] + o.z, d[4 * q + 3] + o.w);
      }
      stsm4t(rP + (G == 0 ? R_VT : R_KT) + 1024, pk[0], pk[1], pk[2], pk[3]);
      stsm4t(rP + (G == 0 ? R_VT : R_KT) + 3072, pk[4], pk[5], pk[6], pk[7]);
    }
#pragma unroll
    for (int f = (G ? NQ - 4 : NQ_WIN); f < NQ; f++) if (!FIRST) ldsm4t(wqt[f], wqS + f * 2048);
    if (FIRST) {
      asm volatile("barrier.cluster.wait.acquire.aligned;" ::: "memory");
      mbar_wait(WBAR + 16, 0);
#pragma unroll
      for (int f = 0; f < NQ; f++) ldsm4t(wqt[f], wqS + f * 2048);
    }
    TR(14);
    if (!FIRST) {
      int n = 0;
#pragma unroll 1
      while (true) {
        sts128(rA, y0.x, y0.y, y0.z, y0.w);
        sts128(rA + 2048, y1.x, y1.y, y1.z, y1.w);
        if (w < 2) sts128(rA + 4096, y2.x, y2.y, y2.z, y2.w);
        const uint32_t b0 = (y0.x ^ tag) | (y0.z ^ tag), b1 = (y1.x ^ tag) | (y1.z ^ tag), b2 = (y2.x ^ tag) | (y2.z ^ tag);
        if (!__any_sync(~0u, (b0 | b1 | b2) & 1)) break;
        if (b0 & 1) y0 = ldg_rlx128(yp);
        if (b1 & 1) y1 = ldg_rlx128(yp + 2048);
        if (b2 & 1) y2 = ldg_rlx128(yp2);
        if (++n > SPIN_MAX) { g_err = 5; break; }
      }
    }
    TR(0);
    bar_sync(5 + G, 128);
  };

  auto oproj = [&](auto TWO_, uint32_t (&wot)[12][4], const uint32_t rF, const uint32_t woA, const uint32_t woB, auto&& between) {
    constexpr bool TWO = decltype(TWO_)::value;
    const uint32_t oA = pin(oA_), tag = (s ^ oA) & 1;
    float c[4][4];
#pragma unroll
    for (int q = 0; q < 4; q++) c[q][0] = c[q][1] = c[q][2] = c[q][3] = 0.f;
    unsigned char* spA = g_comm + (oA & ~1u);
    unsigned char* spB = spA + 8192;
    bar_sync(3, 256);
    uint4 ob[6];
    ob[0] = lds128(rF + R_QB); ob[1] = lds128(rF + R_QB + 512);
    between();
#pragma unroll
    for (int p = 0; p < 6; p++) {
      if (p == 2) {
        mbar_wait(OBAR, s & 1);
        TR(8);
        ob[2] = lds128(rF + R_QA); ob[3] = lds128(rF + R_QA + 512); ob[4] = lds128(rF + R_O2); ob[5] = lds128(rF + R_O2 + 512);
      }
#pragma unroll
      for (int e = 0; e < 2; e++) {
        const int ks = 2 * p + e;
        const uint32_t b0 = e ? ob[p].z : ob[p].x, b1 = e ? ob[p].w : ob[p].y;
        if (TWO) {
          const int iA = (2 * ks) % 12, iB = iA + 1;
          mma16816(c[e], wot[iA], b0, b1);
          if (ks < 6) ldsm4t(wot[iA], woA + WOFF(ks + 6));
          mma16816(c[2 + e], wot[iB], b0, b1);
          if (ks < 6) ldsm4t(wot[iB], woB + WOFF(ks + 6));
        } else {
          mma16816(c[ks & 3], wot[ks], b0, b1);
        }
      }
    }
    if (TWO) {
      stg_rlx64(spA, (pack2(c[0][0] + c[1][0], c[0][1] + c[1][1]) & ~1u) | tag, (pack2(c[0][2] + c[1][2], c[0][3] + c[1][3]) & ~1u) | tag);
      stg_rlx64(spB, (pack2(c[2][0] + c[3][0], c[2][1] + c[3][1]) & ~1u) | tag, (pack2(c[2][2] + c[3][2], c[2][3] + c[3][3]) & ~1u) | tag);
    } else {
      stg_rlx64(spA, (pack2((c[0][0] + c[1][0]) + (c[2][0] + c[3][0]), (c[0][1] + c[1][1]) + (c[2][1] + c[3][1])) & ~1u) | tag,
                (pack2((c[0][2] + c[1][2]) + (c[2][2] + c[3][2]), (c[0][3] + c[1][3]) + (c[2][3] + c[3][3])) & ~1u) | tag);
    }
    TR(15);
  };

  auto step0 = [&](auto LAST_) {
    constexpr bool LAST = decltype(LAST_)::value;
    const uint32_t rF = pin(rF_), rP = pin(rP_), rM = pin(rM_);
    TR(1);
    uint32_t bb[10][4];
    {
      const uint32_t wqS = rP + R_WQ;
      float aq[4] = {0.f, 0.f, 0.f, 0.f}, ak[4] = {0.f, 0.f, 0.f, 0.f}, aq2[4] = {0.f, 0.f, 0.f, 0.f}, ak2[4] = {0.f, 0.f, 0.f, 0.f};
      ldsm4t(bb[0], rM);
      ldsm4t(bb[1], rM + 512);
#pragma unroll
      for (int i = 0; i < 10; i++) {
        if (i + 2 < 10) ldsm4t(bb[i + 2], rM + (i + 2) * 512);
#pragma unroll
        for (int e = 0; e < 2; e++) {
          const int f = 2 * i + e;
          const uint32_t b0 = bb[i][2 * e], b1 = bb[i][2 * e + 1];
          mma16816(e ? ak2 : ak, wk[f], b0, b1);
          if (!LAST) {
            if (f < NPQ) mma16816(e ? aq2 : aq, wqp[f], b0, b1);
            else {
              const int slot = (f - NPQ) % NQ0;
              mma16816(e ? aq2 : aq, wqt[slot], b0, b1);
              if (f + NQ0 < 20) ldsm4t(wqt[slot], wqS + (f - NPQ + NQ0) * 2048);
            }
          }
        }
      }
      TR(2);
      stsm4t(rP + R_QA, pack2(aq[0] + aq2[0], aq[1] + aq2[1]), pack2(aq[2] + aq2[2], aq[3] + aq2[3]),
             pack2(ak[0] + ak2[0], ak[1] + ak2[1]), pack2(ak[2] + ak2[2], ak[3] + ak2[3]));
    }
    __syncthreads();
    TR(3);
    uint32_t vm0, vm1;
    {
      const float4 vb = lds128f(rF + R_RB + w * 512);
      float av[4] = {vb.x, vb.y, vb.z, vb.w}, av1[4] = {0.f, 0.f, 0.f, 0.f}, av2[4] = {0.f, 0.f, 0.f, 0.f};
#pragma unroll
      for (int f = 0; f < 20; f++) mma16816(f % 3 == 2 ? av : (f % 3 == 1 ? av1 : av2), wv[f], bb[f >> 1][2 * (f & 1)], bb[f >> 1][2 * (f & 1) + 1]);
      vm0 = pack2(av[0] + av1[0] + av2[0], av[1] + av1[1] + av2[1]);
      vm1 = pack2(av[2] + av1[2] + av2[2], av[3] + av1[3] + av2[3]);
    }
    stsm2t(rP + R_VT, vm0, vm1);
    TR(5);
    if (LAST) return;
    const uint32_t woA = pin(rW_), woB = woA ^ 32;
    uint32_t wot[12][4], va[8];
    ldsm4t(va, rP + R_VT + 1024); ldsm4t(va + 4, rP + R_VT + 3072);
    if (two) {
#pragma unroll
      for (int i = 0; i < NO_EARLY; i++) ldsm4t(wot[i], ((i & 1) ? woB : woA) + WOFF(i >> 1));
    } else {
#pragma unroll
      for (int i = 0; i < NO_EARLY; i++) ldsm4t(wot[i], woA + WOFF(i));
    }
    const uint32_t l8 = sb + ((rF - sb) >> 1);
    const uint32_t dst = rF + (w >> 1) * 512 + (w & 1) * 8;
    const uint32_t d1 = mapa(dst + R_O2, r1), d2 = mapa(dst + R_QA, r2);
    mbar_wait(SBAR, s & 1);
    TR(6);
    float sc[10];
    {
      const float4 a0 = lds128f(rF + R_SX), b0 = lds128f(rF + R_SX + 1280), c0 = lds128f(rF + R_SX + 2560);
      const float4 a1 = lds128f(rF + R_SX + 512), b1 = lds128f(rF + R_SX + 1792), c1 = lds128f(rF + R_SX + 3072);
      const float2 a2 = lds64f(l8 + R_SX + 1024), b2 = lds64f(l8 + R_SX + 2304), c2 = lds64f(l8 + R_SX + 3584);
      sc[0] = a0.x + b0.x + c0.x; sc[1] = a0.y + b0.y + c0.y; sc[2] = a0.z + b0.z + c0.z; sc[3] = a0.w + b0.w + c0.w;
      sc[4] = a1.x + b1.x + c1.x; sc[5] = a1.y + b1.y + c1.y; sc[6] = a1.z + b1.z + c1.z; sc[7] = a1.w + b1.w + c1.w;
      sc[8] = a2.x + b2.x + c2.x; sc[9] = a2.y + b2.y + c2.y;
    }
    float mx = fmaxf(fmaxf(fmaxf(sc[0], sc[1]), fmaxf(sc[2], sc[3])), fmaxf(fmaxf(sc[4], sc[5]), fmaxf(sc[6], sc[7])));
    mx = fmaxf(mx, fmaxf(sc[8], sc[9]));
    mx = fmaxf(mx, __shfl_xor_sync(~0u, mx, 1));
    mx = fmaxf(mx, __shfl_xor_sync(~0u, mx, 2));
    constexpr float SCL = 0.07216878364870322f * 1.4426950408889634f;
    const float mo = mx * SCL;
    uint32_t pb[5];
    pb[4] = pack2(ex2(fmaf(sc[8], SCL, -mo)), ex2(fmaf(sc[9], SCL, -mo)));
#pragma unroll
    for (int j = 0; j < 4; j++) pb[j] = pack2(ex2(fmaf(sc[2 * j], SCL, -mo)), ex2(fmaf(sc[2 * j + 1], SCL, -mo)));
    const uint32_t ones[4] = {0x3F803F80u, 0x3F803F80u, 0x3F803F80u, 0x3F803F80u};
    float o[4] = {0.f, 0.f, 0.f, 0.f}, sm[4] = {0.f, 0.f, 0.f, 0.f};
    mma1688(sm, ones[0], ones[1], pb[4]);
    mma1688(o, vm0, vm1, pb[4]);
    mma16816(sm, ones, pb[0], pb[1]);
    mma16816(o, va, pb[0], pb[1]);
    mma16816(sm, ones, pb[2], pb[3]);
    mma16816(o, va + 4, pb[2], pb[3]);
    const float i0 = rcp(sm[0]), i1 = rcp(sm[1]);
    const uint32_t b0 = movmat(pack2(o[0] * i0, o[1] * i1)), b1 = movmat(pack2(o[2] * i0, o[3] * i1));
    st_async2(d1, b0, b1, mapa(OBAR, r1));
    st_async2(d2, b0, b1, mapa(OBAR, r2));
    sts64(dst + R_QB, b0, b1);
    TR(7);
    if (two) oproj(std::true_type{}, wot, rF, woA, woB, [&]() {
#pragma unroll
      for (int i = NO_EARLY; i < 12; i++) ldsm4t(wot[i], ((i & 1) ? woB : woA) + WOFF(i >> 1));
    });
    else oproj(std::false_type{}, wot, rF, woA, woB, [&]() {
#pragma unroll
      for (int i = NO_EARLY; i < 12; i++) ldsm4t(wot[i], woA + WOFF(i));
    });
  };

  auto step1 = [&](auto LAST_) {
    constexpr bool LAST = decltype(LAST_)::value;
    const uint32_t rF = pin(rF_), rP = pin(rP_), rM = pin(rM_);
    TR(1);
    {
      const uint32_t wqS = rP + R_WQ + (20 - NPQ) * 2048;
      float aq[4] = {0.f, 0.f, 0.f, 0.f}, ak[4] = {0.f, 0.f, 0.f, 0.f}, av[4] = {0.f, 0.f, 0.f, 0.f};
      uint32_t bb[3][4];
      ldsm4t(bb[0], rM);
      ldsm4t(bb[1], rM + 512);
#pragma unroll
      for (int i = 0; i < 10; i++) {
        if (i + 2 < 10) ldsm4t(bb[(i + 2) % 3], rM + (i + 2) * 512);
#pragma unroll
        for (int e = 0; e < 2; e++) {
          const int f = 2 * i + e;
          const uint32_t b0 = bb[i % 3][2 * e], b1 = bb[i % 3][2 * e + 1];
          mma16816(ak, wk[f], b0, b1);
          if (!LAST) {
            if (f < NPQ) mma16816(aq, wqp[f], b0, b1);
            else {
              const int slot = (f - NPQ) % NQ1;
              mma16816(aq, wqt[slot], b0, b1);
              if (f + NQ1 < 20) ldsm4t(wqt[slot], wqS + (f - NPQ + NQ1) * 2048);
            }
          }
          mma16816(av, wv[f], b0, b1);
        }
      }
      TR(2);
      stsm4t(rP + R_QB, pack2(aq[0], aq[1]), pack2(aq[2], aq[3]), pack2(ak[0], ak[1]), pack2(ak[2], ak[3]));
      sts128f(rF + R_RB + w * 512, av[0], av[1], av[2], av[3]);
    }
    if (LAST) { __syncthreads(); return; }
    if (w < 3) {
      const uint32_t rD1 = pin(rD1_), rD2 = pin(rD2_);
      const uint32_t ry = rD2 + (w == 0 ? 2048 : 1024);
      const uint32_t a1 = rD1 ^ 32, a2 = rD1 ^ 64, a3 = rD1 ^ 96, rx2 = rD2 ^ 64, ry2 = ry ^ 64;
      const uint32_t dst = w == 0 ? sb + R_SX + rank * 1280 + 1024 + ((rF - sb) >> 1) : rF + R_SX + rank * 1280 + (w - 1) * 512;
      const uint32_t e0 = mapa(dst, 0), e1 = mapa(dst, 1), e2 = mapa(dst, 2);
      __syncthreads();
      TR(3);
      uint32_t qa[4][4], kx[8], ky[8];
      ldsm4(qa[0], rD1); ldsm4(kx, rD2); ldsm4(ky, ry);
      ldsm4(qa[1], a1); ldsm4(qa[2], a2); ldsm4(kx + 4, rx2); ldsm4(ky + 4, ry2);
      ldsm4(qa[3], a3);
      float x0[4] = {0.f, 0.f, 0.f, 0.f}, x1[4] = {0.f, 0.f, 0.f, 0.f}, z0[4] = {0.f, 0.f, 0.f, 0.f}, z1[4] = {0.f, 0.f, 0.f, 0.f};
      mma16816(x0, qa[0], kx[0], kx[1]); mma16816(z0, qa[0], ky[0], ky[1]);
      mma16816(x1, qa[1], kx[2], kx[3]); mma16816(z1, qa[1], ky[2], ky[3]);
      mma16816(x0, qa[2], kx[4], kx[5]); mma16816(z0, qa[2], ky[4], ky[5]);
      mma16816(x1, qa[3], kx[6], kx[7]); mma16816(z1, qa[3], ky[6], ky[7]);
      const float u0 = (x0[0] + x0[2]) + (x1[0] + x1[2]), u1 = (x0[1] + x0[3]) + (x1[1] + x1[3]);
      const float u2 = (z0[0] + z0[2]) + (z1[0] + z1[2]), u3 = (z0[1] + z0[3]) + (z1[1] + z1[3]);
      if (w == 0) {
        st_async2(e0, __float_as_uint(u0 + u2), __float_as_uint(u1 + u3), mapa(SBAR, 0));
        st_async2(e1, __float_as_uint(u0 + u2), __float_as_uint(u1 + u3), mapa(SBAR, 1));
        st_async2(e2, __float_as_uint(u0 + u2), __float_as_uint(u1 + u3), mapa(SBAR, 2));
      } else {
        st_async4(e0, __float_as_uint(u0), __float_as_uint(u1), __float_as_uint(u2), __float_as_uint(u3), mapa(SBAR, 0));
        st_async4(e1, __float_as_uint(u0), __float_as_uint(u1), __float_as_uint(u2), __float_as_uint(u3), mapa(SBAR, 1));
        st_async4(e2, __float_as_uint(u0), __float_as_uint(u1), __float_as_uint(u2), __float_as_uint(u3), mapa(SBAR, 2));
      }
    } else {
      __syncthreads();
      TR(3);
      if (rF == sb) {
        mbar_expect(SBAR, 3840); mbar_expect(OBAR, 2048);
        mbar_expect(XBAR, 40960); tma_load3(sb + R_XT, &tmX, 0, (s + 1) * SEG, 0, XBAR);
      }
      __syncwarp();
    }
    TR(4);
    const uint32_t woA = pin(rW_), woB = woA ^ 32;
    uint32_t wot[12][4];
#pragma unroll
    for (int i = 0; i < 12; i++) ldsm4t(wot[i], ((i & 1) ? woB : woA) + WOFF(i >> 1));
    fence_async_smem();
    TR(5);
    oproj(std::true_type{}, wot, rF, woA, woB, []() {});
  };

  GTR(5); GTR(6);
  if (g == 0) {
    window(std::integral_constant<int, 0>{}, std::true_type{});
    GTR(7);
#pragma unroll 1
    for (s = 0; s < NSEG - 1; s++) {
      step0(std::false_type{});
      window(std::integral_constant<int, 0>{}, std::false_type{});
    }
    step0(std::true_type{});
  } else {
    window(std::integral_constant<int, 1>{}, std::true_type{});
#pragma unroll 1
    for (s = 0; s < NSEG - 1; s++) {
      step1(std::false_type{});
      window(std::integral_constant<int, 1>{}, std::false_type{});
    }
    step1(std::true_type{});
  }
  __syncthreads();
  if (wid == 3) {
    const uint32_t a = rF_ + (rF_ - sb);
    const uint4 a0 = lds128(a + R_KT), a1 = lds128(a + R_KT + 16), c0 = lds128(a + R_KB), c1 = lds128(a + R_KB + 16);
    sts128(a + R_KT, hadd2(a0.x, c0.x), hadd2(a0.y, c0.y), hadd2(a0.z, c0.z), hadd2(a0.w, c0.w));
    sts128(a + R_KT + 16, hadd2(a1.x, c1.x), hadd2(a1.y, c1.y), hadd2(a1.z, c1.z), hadd2(a1.w, c1.w));
  }
  fence_async_smem();
  __syncthreads();
  if (tid == 96) {
    tma_store2(&tmK, sb + R_KT, D0, (NSEG - 1) * LK);
    tma_store2(&tmV, sb + R_VT, D0, (NSEG - 1) * LK);
    bulk_commit();
    bulk_wait0();
    asm volatile("red.relaxed.gpu.global.add.u32 [%0], 1;" ::"l"(&g_segcnt[NSEG - 2]) : "memory");
    asm volatile("red.relaxed.gpu.global.add.u32 [%0], 1;" ::"l"(&g_segcnt[NSEG - 1]) : "memory");
  }
  GTR(8);
  cluster_sync();
}

enum { IT_GATE = 0, IT_QKV = 1, IT_XATT = 2, IT_OUT = 3, IT_BATT = 4, IT_CVT = 5, IT_INIT = 6, IT_END = 7 };
constexpr int C_GATE = 0, C_QKV = 16, C_OB = 32, C_INIT = 48, C_ACC = 80, C_O = 112;
#define NS_LIST 4, 4, 4, 4, 4, 4, 4, 4, 4, 4, 4, 4, 8, 8, 16, 16
#define XEARLY 14
constexpr int k_nsplit[16] = {NS_LIST};
constexpr uint32_t mk_item(int ty, int t, int a, int b = 0, int c = 0) { return ty | (t << 3) | (a << 8) | (b << 16) | (c << 24); }
struct ItemTab { uint32_t v[1024]; int n; };
constexpr ItemTab make_items() {
  ItemTab T{};
  int n = 0;
  for (int t = 0; t < 16; t++) T.v[n++] = mk_item(IT_GATE, t, 0);
  for (int t = 0; t < 16; t++) for (int a = 0; a < 5; a++) T.v[n++] = mk_item(IT_QKV, t, a);
  for (int t = 0; t < 32; t++) for (int a = 0; a < 4; a++) T.v[n++] = mk_item(IT_BATT, t, a);
  for (int t = 0; t < 16; t++) for (int a = 0; a < 2; a++) T.v[n++] = mk_item(IT_INIT, t, a);
  auto xatt = [&](int t) { for (int a = 0; a < 16; a++) T.v[n++] = mk_item(IT_XATT, t, a); };
  auto outp = [&](int u) {
    const int ns = k_nsplit[u];
    for (int q = 0; q < ns; q++) for (int a = 0; a < 2; a++) T.v[n++] = mk_item(IT_OUT, u, a | (ns == 1 ? 2 : 0), q * 32 / ns, (q + 1) * 32 / ns);
  };
  auto cvt = [&](int v) {
    if (k_nsplit[v] > 1) for (int a = 0; a < 8; a++) T.v[n++] = mk_item(IT_CVT, v, a);
  };
  for (int t = 0; t < XEARLY; t++) {
    xatt(t);
    if (t >= 1) outp(t - 1);
    if (t >= 4) cvt(t - 4);
  }
  for (int t = XEARLY; t < 16; t++) xatt(t);
  for (int t = XEARLY - 1; t < 16; t++) outp(t);
  for (int t = XEARLY - 4; t < 16; t++) cvt(t);
  T.n = n;
  return T;
}
constexpr ItemTab k_items_host = make_items();
constexpr int NITEMS = k_items_host.n;
__constant__ ItemTab c_items = make_items();

constexpr int AUX_GRID = 132, NST = 7, STG = 32768;
constexpr int A_FULL = NST * STG, A_EMPTY = A_FULL + 64, A_ITEM = A_EMPTY + 64, A_QBAR = A_ITEM + 32, A_QENT = A_QBAR + 128, A_MISC = A_QENT + 256,
              A_SMEM = A_MISC + 64;
static_assert(A_SMEM <= 232448, "smem");
enum { OP_END = 0, OP_O = 1, OP_QKV = 2, OP_OB = 3, OP_ACC = 4, OP_RED = 5, OP_OUT = 6 };

struct AuxMaps { CUtensorMap xA, wq, wqkv, wo, wob, k, v, oA, oS, obA, obS, qkvS, qkvQ, qkvK, acc, outS; };

__device__ __forceinline__ void wait_cnt(const uint32_t* p, uint32_t target) {
  int n = 0;
#pragma unroll 1
  while ((int)(ldg_acq32(p) - target) < 0) { if (++n > SPIN_MAX) { g_err = 7; break; } __nanosleep(20); }
}
__device__ __forceinline__ void mbar_wait_long(uint32_t b, uint32_t par) {
  int n = 0;
#pragma unroll 1
  while (!mbar_try(b, par)) { if (++n > (SPIN_MAX << 4)) { g_err = 8; break; } }
}
__device__ __forceinline__ uint64_t mk_desc(uint32_t addr, uint32_t lbo, uint32_t sbo, uint32_t mode) {
  return (uint64_t)((addr & 0x3FFFF) >> 4) | ((uint64_t)(lbo >> 4) << 16) | ((uint64_t)(sbo >> 4) << 32) | ((uint64_t)mode << 62);
}

__global__ void __launch_bounds__(384, 1)
aux_kernel(const __grid_constant__ AuxMaps tm, const bf16* __restrict__ x, const bf16* __restrict__ gate_w, bf16* __restrict__ out) {
  extern __shared__ __align__(1024) unsigned char smem[];
  const uint32_t sb = smem_u32(smem);
  const int tid = threadIdx.x, lane = tid & 31, wid = __shfl_sync(~0u, tid >> 5, 0);
  if (tid == 0) {
    for (int i = 0; i < NST; i++) { mbar_init(sb + A_FULL + i * 8, 1); mbar_init(sb + A_EMPTY + i * 8, 8); }
    for (int i = 0; i < 16; i++) mbar_init(sb + A_QBAR + i * 8, 4);
    asm volatile("fence.mbarrier_init.release.cluster;" ::: "memory");
    sts32(sb + A_MISC, *(volatile uint32_t*)&g_epoch + 1);
  }
  __syncthreads();
  const uint32_t epoch = lds32(sb + A_MISC);
  uint32_t st = 0, ph = 0;
  auto advance = [&]() { if (++st == NST) { st = 0; ph ^= 1; } };

  if (wid >= 8) {
    asm volatile("setmaxnreg.dec.sync.aligned.u32 40;");
    if (wid == 8 && lane == 0) {
      const uint32_t qbase = (epoch - 1) * (uint32_t)(NITEMS + AUX_GRID);
      while (true) {
        const uint32_t idx = atomicAdd(&g_queue, 1u) - qbase;
        const uint32_t item = idx < (uint32_t)NITEMS ? c_items.v[idx] : (uint32_t)IT_END;
        const int ty = item & 7, t = (item >> 3) & 31, a = (item >> 8) & 255, b = (item >> 16) & 255, c = item >> 24;
        auto slot = [&](uint32_t bytes) -> uint32_t {
          mbar_wait_long(sb + A_EMPTY + st * 8, ph ^ 1);
          sts32(sb + A_ITEM + st * 4, item);
          if (bytes) mbar_expect(sb + A_FULL + st * 8, bytes); else mbar_arrive(sb + A_FULL + st * 8);
          return sb + st * STG;
        };
        if (ty == IT_QKV || ty == IT_XATT) {
          const CUtensorMap* w = ty == IT_QKV ? &tm.wqkv : &tm.wq;
          for (int k = 0; k < 20; k++) {
            const uint32_t d = slot(32768), fb = sb + A_FULL + st * 8;
            tma_load2(d, &tm.xA, k * 32, t * 128, fb);
            tma_load3(d + 8192, w, 0, k * 32, a * 6, fb);
            advance();
          }
          if (ty == IT_QKV) {
            for (int k = 0; k < 4; k++) { slot(0); advance(); }
          } else {
            wait_cnt(&g_cnt[(C_GATE + t) * 8], epoch);
            for (int k = 0; k < 4; k++) wait_cnt(&g_segcnt[4 * t + k], epoch * 96);
            asm volatile("fence.proxy.async;" ::: "memory");
            for (int k = 0; k < 8; k++) {
              const uint32_t d = slot(30720);
              tma_load3(d, k < 4 ? &tm.k : &tm.v, 0, (4 * t + (k & 2)) * LK, (2 * a + (k & 1)) * 3, sb + A_FULL + st * 8);
              advance();
            }
          }
        } else if (ty == IT_OUT || ty == IT_INIT) {
          const CUtensorMap *ma = ty == IT_OUT ? &tm.oA : &tm.obA, *mb = ty == IT_OUT ? &tm.wo : &tm.wob;
          const int k0 = ty == IT_OUT ? b * 6 : 0, k1 = ty == IT_OUT ? c * 6 : 20, jh = a & 1, ns = a >> 1;
          for (int k = k0; k < k1; k++) {
            if (k == k0 || (ty == IT_OUT && k % 12 == 0)) {
              if (ty == IT_OUT) wait_cnt(&g_cnt[(C_O + t * 16 + k / 12) * 8], epoch * 2);
              else wait_cnt(&g_cnt[(C_OB + t) * 8], epoch * 8);
              asm volatile("fence.proxy.async;" ::: "memory");
            }
            const uint32_t d = slot(28672), fb = sb + A_FULL + st * 8;
            tma_load2(d, ma, k * 32, t * 128, fb);
            tma_load3(d + 8192, mb, 0, k * 32, jh * 5, fb);
            advance();
          }
          if (ty == IT_OUT) wait_cnt(&g_cnt[(C_INIT + 2 * t + jh) * 8], epoch * 2);
          if (ns) {
            asm volatile("fence.proxy.async;" ::: "memory");
            for (int k = 0; k < 6; k++) {
              const uint32_t d = slot(k < 4 ? 32768 : 16384), fb = sb + A_FULL + st * 8;
              tma_load3(d, &tm.acc, 0, t * 128 + (k & 1) * 64, jh * 10 + (k >> 1) * 4, fb);
              if (k < 4) tma_load3(d + 16384, &tm.acc, 0, t * 128 + (k & 1) * 64, jh * 10 + (k >> 1) * 4 + 2, fb);
              advance();
            }
          } else {
            for (int k = 0; k < 6; k++) { slot(0); advance(); }
          }
        } else if (ty == IT_BATT) {
          wait_cnt(&g_cnt[(C_GATE + (t >> 1)) * 8], epoch);
          wait_cnt(&g_cnt[(C_QKV + (t >> 1)) * 8], epoch * 10);
          if (t > 0) wait_cnt(&g_cnt[(C_QKV + ((t - 1) >> 1)) * 8], epoch * 10);
          asm volatile("fence.proxy.async;" ::: "memory");
          { const uint32_t d = slot(20480); tma_load2(d, &tm.qkvQ, a * 160, t * 64, sb + A_FULL + st * 8); advance(); }
          { const uint32_t d = slot(25600); tma_load2(d, &tm.qkvK, 640 + a * 160, t * 64 - 16, sb + A_FULL + st * 8); advance(); }
          { const uint32_t d = slot(25600); tma_load2(d, &tm.qkvK, 1280 + a * 160, t * 64 - 16, sb + A_FULL + st * 8); advance(); }
        } else {
          if (ty == IT_CVT) wait_cnt(&g_cnt[(C_ACC + 2 * t + (a & 1)) * 8], epoch * 64);
          slot(0); advance();
          if (ty == IT_END) {
            if (idx == (uint32_t)(NITEMS + AUX_GRID - 1)) g_epoch = epoch;
            break;
          }
        }
      }
      asm volatile("griddepcontrol.wait;" ::: "memory");
    } else if ((wid == 9 || wid == 10) && lane == 0) {
      const uint32_t qb = sb + A_QBAR + (wid - 9) * 64, qe = sb + A_QENT + (wid - 9) * 128;
      for (uint32_t e = 0;; e++) {
        mbar_wait_long(qb + (e & 7) * 8, (e >> 3) & 1);
        const uint4 en = lds128(qe + (e & 7) * 16);
        const int op = en.x & 15, sg = (en.x >> 4) & 15, rel = (en.x >> 8) & 15, nb = (en.x >> 12) & 15;
        if (op == OP_END) break;
        const uint32_t src = sb + sg * STG;
        if (op == OP_O) tma_store3(&tm.oS, src, 0, en.y, en.z);
        else if (op == OP_QKV) tma_store3(&tm.qkvS, src, 0, en.y, en.z);
        else if (op == OP_OB) tma_store2(&tm.obS, src, en.z, en.y);
        else if (op == OP_OUT) { for (int i = 0; i < nb; i++) tma_store3(&tm.outS, src + i * 8192, 0, en.y, en.z + i); }
        else if (op == OP_ACC) { for (int i = 0; i < nb; i++) tma_store3(&tm.acc, src + i * 16384, 0, en.y, en.z + 2 * i); }
        else { for (int i = 0; i < nb; i++) tma_red3(&tm.acc, src + i * 16384, 0, en.y, en.z + 2 * i); }
        bulk_commit();
        bulk_wait_read0();
        asm volatile("mbarrier.arrive.shared::cta.b64 _, [%0], %1;" ::"r"(sb + A_EMPTY + sg * 8), "r"(rel) : "memory");
        if (en.w) {
          bulk_wait0();
          asm volatile("red.relaxed.gpu.global.add.u32 [%0], %1;" ::"l"(&g_cnt[((en.w & 0xFFFF) - 1) * 8]), "r"((en.w >> 16) + 1) : "memory");
        }
      }
      bulk_wait0();
    }
  } else {
    asm volatile("setmaxnreg.inc.sync.aligned.u32 232;");
    const int g = wid >> 2, w = wid & 3;
    uint32_t qn = 0;
    auto wait_full = [&]() { mbar_wait_long(sb + A_FULL + st * 8, ph); };
    auto release = [&](uint32_t s_) { if (lane == 0) mbar_arrive(sb + A_EMPTY + s_ * 8); };
    auto take_pair = [&]() -> uint32_t {
      wait_full();
      const uint32_t s0 = st; advance();
      wait_full();
      const uint32_t s1 = st; advance();
      release(g ? s0 : s1);
      return g ? s1 : s0;
    };
    auto push = [&](uint32_t w0, uint32_t w1, uint32_t w2, uint32_t w3) {
      fence_async_smem();
      if (w == 0 && lane == 0) sts128(sb + A_QENT + g * 128 + (qn & 7) * 16, w0, w1, w2, w3);
      __syncwarp();
      if (lane == 0) mbar_arrive(sb + A_QBAR + g * 64 + (qn & 7) * 8);
      qn++;
    };
    const uint32_t stm = (16 * w + (lane & 7) + (lane & 8)) * 128, stx = lane & 7, sth = lane >> 4;
    auto stage_bf16 = [&](uint32_t dst, const float* d, float s0, float s1) {
#pragma unroll
      for (int ks = 0; ks < 12; ks++)
        stsm4(dst + (ks >> 2) * 8192 + stm + (((2 * (ks & 3) + sth) ^ stx) << 4), pack2(d[8 * ks] * s0, d[8 * ks + 1] * s0), pack2(d[8 * ks + 2] * s1, d[8 * ks + 3] * s1),
              pack2(d[8 * ks + 4] * s0, d[8 * ks + 5] * s0), pack2(d[8 * ks + 6] * s1, d[8 * ks + 7] * s1));
    };
#pragma unroll 1
    while (true) {
      wait_full();
      const uint32_t item = lds32(sb + A_ITEM + st * 4);
      const int ty = item & 7, t = (item >> 3) & 31, a = (item >> 8) & 255;
      if (ty == IT_QKV || ty == IT_XATT) {
        float acc[192] = {};
        uint32_t prev = 0;
#pragma unroll 1
        for (int k = 0; k < 20; k++) {
          if (k) wait_full();
          const uint32_t s_ = sb + st * STG;
          const uint64_t da = mk_desc(s_, 16, 512, 2), db = mk_desc(s_ + 8192 + g * 12288, 4096, 1024, 1);
          wg_fence();
          wgmma_ss192t(acc, da, db, k);
          wgmma_ss192t(acc + 96, da + 256, db, k);
          wgmma_ss192t(acc, da + 2, db + 128, 1);
          wgmma_ss192t(acc + 96, da + 258, db + 128, 1);
          wg_commit();
          if (k) { wg_wait1(); release(prev); }
          prev = st; advance();
        }
        wg_wait0();
        fence_regs<192>(acc);
        release(prev);
        if (ty == IT_QKV) {
#pragma unroll
          for (int q = 0; q < 2; q++) {
            const uint32_t m = take_pair();
            stage_bf16(sb + m * STG, acc + q * 96, 1.f, 1.f);
            push(OP_QKV | (m << 4) | (4 << 8), t * 128 + q * 64, a * 6 + g * 3, q ? C_QKV + t + 1 : 0);
          }
        } else {
          uint32_t qf[24][4];
#pragma unroll
          for (int ks = 23; ks >= 0; ks--)
#pragma unroll
            for (int j = 0; j < 4; j++)
              asm volatile("cvt.rn.bf16x2.f32 %0, %1, %2;" : "=r"(qf[ks][j]) : "f"(acc[8 * ks + 2 * j + 1]), "f"(acc[8 * ks + 2 * j]));
          float sc[2][40] = {};
          uint32_t kst[2];
#pragma unroll
          for (int q = 0; q < 2; q++) {
            kst[q] = take_pair();
            const uint64_t db = mk_desc(sb + kst[q] * STG, 16, 1024, 1);
            wg_fence();
#pragma unroll
            for (int ks = 0; ks < 12; ks++) wgmma_rs80(sc[q], qf[q * 12 + ks], db + (((ks >> 2) * 10240 + (ks & 3) * 32) >> 4), ks);
            wg_commit();
          }
          const int tt = 16 * (w & 1) + (lane >> 2) - 2 * (lane & 3);
          const float* gp = g_gate + t * 128 + 16 * w + (lane >> 2);
          const float gt[4] = {__ldcg(gp), __ldcg(gp + 8), __ldcg(gp + 64), __ldcg(gp + 72)};
          uint32_t pf[2][5][4];
          float rs[2][2];
          auto softmax = [&](const float* s_, uint32_t (&p)[5][4], float* r) {
            constexpr float SCL = 0.07216878364870322f * 1.4426950408889634f;
            float v[20];
#pragma unroll
            for (int i = 0; i < 20; i++) {
              v[i] = w >= 2 ? s_[20 + i] : s_[i];
              if (i >= 4 && 8 * ((i >> 2) - 1) + (i & 1) > tt + ((i & 2) ? 8 : 0)) v[i] = -INFINITY;
            }
            uint32_t pt[5][2];
#pragma unroll
            for (int h = 0; h < 2; h++) {
              float mx = fmaxf(v[2 * h], v[2 * h + 1]);
#pragma unroll
              for (int j = 1; j < 5; j++) mx = fmaxf(mx, fmaxf(v[4 * j + 2 * h], v[4 * j + 2 * h + 1]));
              mx = fmaxf(mx, __shfl_xor_sync(~0u, mx, 1));
              mx = fmaxf(mx, __shfl_xor_sync(~0u, mx, 2));
              const float mo = mx * SCL;
              float sum = 0.f;
#pragma unroll
              for (int j = 0; j < 5; j++) {
                const float e0 = ex2(fmaf(v[4 * j + 2 * h], SCL, -mo)), e1 = ex2(fmaf(v[4 * j + 2 * h + 1], SCL, -mo));
                pt[j][h] = pack2(e0, e1);
                sum += bf_lo(pt[j][h]) + bf_hi(pt[j][h]);
              }
              sum += __shfl_xor_sync(~0u, sum, 1);
              sum += __shfl_xor_sync(~0u, sum, 2);
              r[h] = rcp(sum);
            }
#pragma unroll
            for (int J = 0; J < 10; J++)
#pragma unroll
              for (int h = 0; h < 2; h++) p[J >> 1][(J & 1) * 2 + h] = (J >= 5) == (w >= 2) ? pt[J % 5][h] : 0u;
          };
          wg_wait1();
          fence_regs<40>(sc[0]);
          release(kst[0]);
          softmax(sc[0], pf[0], rs[0]);
#pragma unroll
          for (int q = 0; q < 2; q++) {
            const uint32_t m = take_pair();
            const uint64_t db = mk_desc(sb + m * STG, 10240, 1024, 1);
            float o[96] = {};
            wg_fence();
#pragma unroll
            for (int ks = 0; ks < 5; ks++) wgmma_rs192t(o, pf[q][ks], db + ks * 128, ks);
            wg_commit();
            if (q == 0) {
              wg_wait1();
              fence_regs<40>(sc[1]);
              release(kst[1]);
              softmax(sc[1], pf[1], rs[1]);
            }
            wg_wait0();
            fence_regs<96>(o);
            bar_sync(1 + g, 128);
            stage_bf16(sb + m * STG, o, rs[q][0] * gt[2 * q], rs[q][1] * gt[2 * q + 1]);
            push(OP_O | (m << 4) | (4 << 8), t * 128 + q * 64, a * 6 + g * 3, q ? C_O + t * 16 + a + 1 : 0);
          }
        }
      } else if (ty == IT_OUT || ty == IT_INIT) {
        float acc[160] = {};
        const int nk = ty == IT_OUT ? ((item >> 24) - ((item >> 16) & 255)) * 6 : 20, jh = a & 1;
        uint32_t prev = 0;
#pragma unroll 1
        for (int k = 0; k < nk; k++) {
          if (k) wait_full();
          const uint32_t s_ = sb + st * STG;
          const uint64_t da = mk_desc(s_ + g * 4096, 16, 512, 2), db = mk_desc(s_ + 8192, 4096, 1024, 1);
          wg_fence();
          wgmma_ss192t(acc, da, db, k);
          wgmma_ss128t(acc + 96, da, db + 768, k);
          wgmma_ss192t(acc, da + 2, db + 128, 1);
          wgmma_ss128t(acc + 96, da + 2, db + 896, 1);
          wg_commit();
          if (k) { wg_wait1(); release(prev); }
          prev = st; advance();
        }
        wg_wait0();
        fence_regs<160>(acc);
        release(prev);
        const uint32_t ro = (16 * w + (lane >> 2)) * 128 + (lane & 1) * 8, xr = lane >> 2, ch = (lane >> 1) & 1;
        if (a >> 1) {
          uint32_t m[3];
#pragma unroll
          for (int q = 0; q < 3; q++) {
            m[q] = take_pair();
            const uint32_t dst = sb + m[q] * STG + ro;
#pragma unroll
            for (int j = 0; j < 16; j++) {
              const int nt = q * 16 + j;
              if (nt < 40) {
                const uint32_t ad = dst + (j >> 2) * 8192 + (((2 * (j & 3) + ch) ^ xr) << 4);
                const float2 u = lds64f(ad), v = lds64f(ad + 1024);
                acc[4 * nt] += u.x; acc[4 * nt + 1] += u.y; acc[4 * nt + 2] += v.x; acc[4 * nt + 3] += v.y;
              }
            }
          }
          bar_sync(1 + g, 128);
#pragma unroll
          for (int q = 0; q < 3; q++) {
#pragma unroll
            for (int ks = 0; ks < (q < 2 ? 8 : 4); ks++) {
              const float* d = acc + q * 64 + ks * 8;
              stsm4(sb + m[q] * STG + (ks >> 2) * 8192 + stm + (((2 * (ks & 3) + sth) ^ stx) << 4), pack2(d[0], d[1]), pack2(d[2], d[3]), pack2(d[4], d[5]), pack2(d[6], d[7]));
            }
            push(OP_OUT | (m[q] << 4) | (4 << 8) | ((q < 2 ? 2 : 1) << 12), t * 128 + g * 64, jh * 5 + q * 2, 0);
          }
        } else {
#pragma unroll
          for (int q = 0; q < 3; q++) {
            const uint32_t m = take_pair();
            const uint32_t dst = sb + m * STG + ro;
#pragma unroll
            for (int j = 0; j < 16; j++) {
              const int nt = q * 16 + j;
              if (nt < 40) {
                const uint32_t ad = dst + (j >> 2) * 8192 + (((2 * (j & 3) + ch) ^ xr) << 4);
                sts64f(ad, acc[4 * nt], acc[4 * nt + 1]);
                sts64f(ad + 1024, acc[4 * nt + 2], acc[4 * nt + 3]);
              }
            }
            const uint32_t fl = q < 2 ? 0 : (ty == IT_OUT ? (C_ACC + 2 * t + jh + 1) | ((nk / 6 - 1) << 16) : C_INIT + 2 * t + jh + 1);
            push((ty == IT_OUT ? OP_RED : OP_ACC) | (m << 4) | (4 << 8) | ((q < 2 ? 2 : 1) << 12), t * 128 + g * 64,
                 jh * 10 + q * 4, fl);
          }
        }
      } else if (ty == IT_BATT) {
        const uint32_t sq = st; advance();
        wait_full();
        const uint32_t sk = st; advance();
        wait_full();
        const uint32_t sv = st; advance();
        const int h = tid & 7;
#pragma unroll 1
        for (int p = 0; p < 2; p++) {
          const int tok = (tid >> 3) + 32 * p, pos = t * 64 + tok;
          const uint32_t qa = sb + sq * STG + tok * 320 + h * 40, ka = sb + sk * STG + (tok + 16) * 320 + h * 40, va = sb + sv * STG + (tok + 16) * 320 + h * 40;
          const float gt = __ldcg(g_gate + 2048 + pos);
          float q[20], l[8];
#pragma unroll
          for (int i = 0; i < 5; i++) { const uint2 u = lds64(qa + i * 8); q[4 * i] = bf_lo(u.x); q[4 * i + 1] = bf_hi(u.x); q[4 * i + 2] = bf_lo(u.y); q[4 * i + 3] = bf_hi(u.y); }
          float mx = -INFINITY;
#pragma unroll
          for (int j = 0; j < 8; j++) {
            float s0 = 0.f, s1 = 0.f;
#pragma unroll
            for (int i = 0; i < 5; i++) {
              const uint2 u = lds64(ka - j * 640 + i * 8);
              s0 = fmaf(q[4 * i], bf_lo(u.x), s0); s1 = fmaf(q[4 * i + 1], bf_hi(u.x), s1);
              s0 = fmaf(q[4 * i + 2], bf_lo(u.y), s0); s1 = fmaf(q[4 * i + 3], bf_hi(u.y), s1);
            }
            l[j] = pos - 2 * j >= 0 ? s0 + s1 : -INFINITY;
            mx = fmaxf(mx, l[j]);
          }
          constexpr float SCL = 0.22360679774997896f * 1.4426950408889634f;
          const float mo = mx * SCL;
          float sum = 0.f;
#pragma unroll
          for (int j = 0; j < 8; j++) { l[j] = ex2(fmaf(l[j], SCL, -mo)); sum += l[j]; }
          const float r = gt * rcp(sum);
#pragma unroll
          for (int i = 0; i < 20; i++) q[i] = 0.f;
#pragma unroll
          for (int j = 0; j < 8; j++) {
#pragma unroll
            for (int i = 0; i < 5; i++) {
              const uint2 u = lds64(va - j * 640 + i * 8);
              q[4 * i] = fmaf(l[j], bf_lo(u.x), q[4 * i]); q[4 * i + 1] = fmaf(l[j], bf_hi(u.x), q[4 * i + 1]);
              q[4 * i + 2] = fmaf(l[j], bf_lo(u.y), q[4 * i + 2]); q[4 * i + 3] = fmaf(l[j], bf_hi(u.y), q[4 * i + 3]);
            }
          }
#pragma unroll
          for (int i = 0; i < 5; i++) sts64(qa + i * 8, pack2(q[4 * i] * r, q[4 * i + 1] * r), pack2(q[4 * i + 2] * r, q[4 * i + 3] * r));
        }
        __syncwarp();
        release(sk); release(sv);
        fence_async_smem();
        bar_sync(3, 256);
        if (g == 0) push(OP_OB | (sq << 4) | (8 << 8), t * 64, a * 160, C_OB + (t >> 1) + 1);
      } else if (ty == IT_GATE) {
        release(st); advance();
        uint4 gw[3];
#pragma unroll
        for (int i = 0; i < 3; i++) gw[i] = (i < 2 || lane < 16) ? __ldg((const uint4*)gate_w + lane + 32 * i) : make_uint4(0, 0, 0, 0);
#pragma unroll 4
        for (int r = 0; r < 16; r++) {
          const int row = t * 128 + wid * 16 + r;
          float s_ = 0.f;
#pragma unroll
          for (int i = 0; i < 3; i++) {
            const uint4 v = (i < 2 || lane < 16) ? __ldg((const uint4*)(x + (size_t)row * DM) + lane + 32 * i) : make_uint4(0, 0, 0, 0);
            const uint32_t p0 = hmul2(v.x, gw[i].x), p1 = hmul2(v.y, gw[i].y), p2 = hmul2(v.z, gw[i].z), p3 = hmul2(v.w, gw[i].w);
            s_ += ((bf_lo(p0) + bf_hi(p0)) + (bf_lo(p1) + bf_hi(p1))) + ((bf_lo(p2) + bf_hi(p2)) + (bf_lo(p3) + bf_hi(p3)));
          }
#pragma unroll
          for (int o = 16; o; o >>= 1) s_ += __shfl_xor_sync(~0u, s_, o);
          const float z = bf_lo(pack2(s_, 0.f));
          const float gv = bf_lo(pack2(1.f / (1.f + __expf(-z)), 0.f));
          if (lane == 0) { g_gate[row] = gv; g_gate[2048 + row] = bf_lo(pack2(1.f - gv, 0.f)); }
        }
        __threadfence();
        bar_sync(3, 256);
        if (tid == 0) asm volatile("red.release.gpu.global.add.u32 [%0], 1;" ::"l"(&g_cnt[(C_GATE + t) * 8]) : "memory");
      } else if (ty == IT_CVT) {
        release(st); advance();
        const int o = (t * 128 + (a >> 1) * 32) * DM + (a & 1) * 320;
        float4 v[10];
#pragma unroll
        for (int i = 0; i < 10; i++) { const int e = tid + i * 256; v[i] = __ldcg((const float4*)(g_acc + o + (e / 80) * DM + (e % 80) * 4)); }
#pragma unroll
        for (int i = 0; i < 10; i++) {
          const int e = tid + i * 256;
          *(uint2*)(out + o + (e / 80) * DM + (e % 80) * 4) = make_uint2(pack2(v[i].x, v[i].y), pack2(v[i].z, v[i].w));
        }
      } else {
        push(OP_END, 0, 0, 0);
        break;
      }
    }
  }
}

typedef CUresult (*EncFn)(CUtensorMap*, CUtensorMapDataType, cuuint32_t, void*, const cuuint64_t*, const cuuint64_t*, const cuuint32_t*,
                          const cuuint32_t*, CUtensorMapInterleave, CUtensorMapSwizzle, CUtensorMapL2promotion, CUtensorMapFloatOOBfill);

#define PROMO CU_TENSOR_MAP_L2_PROMOTION_L2_128B
void make_map(EncFn enc, CUtensorMap* tm, const void* base, int rank, const cuuint64_t* dims, const cuuint64_t* strides, const cuuint32_t* box,
              CUtensorMapSwizzle sw = CU_TENSOR_MAP_SWIZZLE_128B, CUtensorMapDataType dt = CU_TENSOR_MAP_DATA_TYPE_BFLOAT16) {
  const cuuint32_t es[5] = {1, 1, 1, 1, 1};
  enc(tm, dt, rank, const_cast<void*>(base), dims, strides, box, es, CU_TENSOR_MAP_INTERLEAVE_NONE, sw, PROMO,
      CU_TENSOR_MAP_FLOAT_OOB_FILL_NONE);
}
void map_blk(EncFn enc, CUtensorMap* tm, const void* base, int rows, int cols, int brows, int bblk) {
  const cuuint64_t d[3] = {64, (cuuint64_t)rows, (cuuint64_t)cols / 64}, st[2] = {(cuuint64_t)cols * 2, 128};
  const cuuint32_t b[3] = {64, (cuuint32_t)brows, (cuuint32_t)bblk};
  make_map(enc, tm, base, 3, d, st, b);
}
void map_2d(EncFn enc, CUtensorMap* tm, const void* base, int rows, int cols, int brows, int bcols, CUtensorMapSwizzle sw) {
  const cuuint64_t d[2] = {(cuuint64_t)cols, (cuuint64_t)rows}, st[1] = {(cuuint64_t)cols * 2};
  const cuuint32_t b[2] = {(cuuint32_t)bcols, (cuuint32_t)brows};
  make_map(enc, tm, base, 2, d, st, b, sw);
}

}

extern "C" void kernel_launch(void* const* d_in, const int* in_sizes, int n_in, void* d_out, int out_size) {
  const bf16* x = (const bf16*)d_in[0];
  const bf16* mem0 = (const bf16*)d_in[1];
  const bf16* Wq = (const bf16*)d_in[2];
  const bf16* Wk = (const bf16*)d_in[3];
  const bf16* Wv = (const bf16*)d_in[4];
  const bf16* Wo = (const bf16*)d_in[5];
  const bf16* wqkv = (const bf16*)d_in[8];
  const bf16* wob = (const bf16*)d_in[9];
  const bf16* gate_w = (const bf16*)d_in[10];
  static EncFn enc = nullptr;
  static void *pK = nullptr, *pV = nullptr, *pO = nullptr, *pQ = nullptr, *pB = nullptr, *pA = nullptr;
  if (!enc) {
    void* fn = nullptr;
    cudaDriverEntryPointQueryResult qr;
    cudaGetDriverEntryPoint("cuTensorMapEncodeTiled", &fn, cudaEnableDefault, &qr);
    enc = (EncFn)fn;
    cudaGetSymbolAddress(&pK, g_K);
    cudaGetSymbolAddress(&pV, g_V);
    cudaGetSymbolAddress(&pO, g_O);
    cudaGetSymbolAddress(&pQ, g_qkv);
    cudaGetSymbolAddress(&pB, g_Ob);
    cudaGetSymbolAddress(&pA, g_acc);
    cudaFuncSetAttribute(rec_kernel, cudaFuncAttributeMaxDynamicSharedMemorySize, R_SMEM_ALLOC);
    cudaFuncSetAttribute(aux_kernel, cudaFuncAttributeMaxDynamicSharedMemorySize, A_SMEM);
  }
  CUtensorMap tmX, tmK, tmV, tmWq, tmWq2, tmWk, tmWv, tmWo;
  map_2d(enc, &tmWq, Wq, DM, HD, 144, 64, CU_TENSOR_MAP_SWIZZLE_128B);
  map_2d(enc, &tmWq2, Wq, DM, HD, 32, 64, CU_TENSOR_MAP_SWIZZLE_128B);
  map_2d(enc, &tmWk, Wk, DM, HD, 128, 64, CU_TENSOR_MAP_SWIZZLE_128B);
  map_2d(enc, &tmWv, Wv, DM, HD, 128, 64, CU_TENSOR_MAP_SWIZZLE_128B);
  {
    const cuuint64_t d[3] = {32, HD, 20}, st[2] = {DM * 2, 64};
    const cuuint32_t b[3] = {32, 64, 7};
    make_map(enc, &tmWo, Wo, 3, d, st, b, CU_TENSOR_MAP_SWIZZLE_64B);
  }
  map_blk(enc, &tmX, x, S_TOK, DM, 32, 10);
  map_2d(enc, &tmK, pK, NSEG * LK, HD, LK, 64, CU_TENSOR_MAP_SWIZZLE_128B);
  map_2d(enc, &tmV, pV, NSEG * LK, HD, LK, 64, CU_TENSOR_MAP_SWIZZLE_128B);
  AuxMaps am;
  map_2d(enc, &am.xA, x, S_TOK, DM, 128, 32, CU_TENSOR_MAP_SWIZZLE_64B);
  map_blk(enc, &am.wq, Wq, DM, HD, 32, 6);
  map_blk(enc, &am.wqkv, wqkv, DM, 3 * DM, 32, 6);
  map_blk(enc, &am.wo, Wo, HD, DM, 32, 5);
  map_blk(enc, &am.wob, wob, DM, DM, 32, 5);
  map_blk(enc, &am.k, pK, NSEG * LK, HD, 80, 3);
  map_blk(enc, &am.v, pV, NSEG * LK, HD, 80, 3);
  map_2d(enc, &am.oA, pO, S_TOK, HD, 128, 32, CU_TENSOR_MAP_SWIZZLE_64B);
  map_blk(enc, &am.oS, pO, S_TOK, HD, 64, 3);
  map_2d(enc, &am.obA, pB, S_TOK, DM, 128, 32, CU_TENSOR_MAP_SWIZZLE_64B);
  map_2d(enc, &am.obS, pB, S_TOK, DM, 64, 160, CU_TENSOR_MAP_SWIZZLE_NONE);
  map_blk(enc, &am.qkvS, pQ, S_TOK, 3 * DM, 64, 3);
  map_2d(enc, &am.qkvQ, pQ, S_TOK, 3 * DM, 64, 160, CU_TENSOR_MAP_SWIZZLE_NONE);
  map_2d(enc, &am.qkvK, pQ, S_TOK, 3 * DM, 80, 160, CU_TENSOR_MAP_SWIZZLE_NONE);
  map_blk(enc, &am.outS, d_out, S_TOK, DM, 64, 1);
  {
    const cuuint64_t d[3] = {32, S_TOK, 20}, st[2] = {DM * 4, 128};
    const cuuint32_t b[3] = {32, 64, 2};
    make_map(enc, &am.acc, pA, 3, d, st, b, CU_TENSOR_MAP_SWIZZLE_128B, CU_TENSOR_MAP_DATA_TYPE_FLOAT32);
  }
  rec_kernel<<<96, 256, R_SMEM_ALLOC, cudaStreamPerThread>>>(tmX, tmK, tmV, tmWq, tmWq2, tmWk, tmWv, tmWo, mem0, Wq, Wo);
  cudaLaunchConfig_t cfg = {};
  cfg.gridDim = dim3(AUX_GRID); cfg.blockDim = dim3(384); cfg.dynamicSmemBytes = A_SMEM; cfg.stream = cudaStreamPerThread;
  cudaLaunchAttribute at[1];
  at[0].id = cudaLaunchAttributeProgrammaticStreamSerialization;
  at[0].val.programmaticStreamSerializationAllowed = 1;
  cfg.attrs = at;
  cfg.numAttrs = 1;
  cudaLaunchKernelEx(&cfg, aux_kernel, am, x, gate_w, (bf16*)d_out);
}
```

```cpp
#include <cuda_runtime.h>
#include <cuda_bf16.h>
#include <cuda.h>
#include <stdint.h>
#include <type_traits>

typedef __nv_bfloat16 bf16;

namespace {

constexpr int S_TOK = 2048, DM = 640, NH = 32, DH = 192, HD = NH * DH, SEG = 32, NSEG = 64, MT = 8, LK = 40;
constexpr int SPIN_MAX = 1 << 20;

#define RB_LINE 384
constexpr int RB_SIZE = 160 * RB_LINE;
__device__ __align__(4096) unsigned char g_red[4 * RB_SIZE];
__device__ unsigned long long g_rec[96];
__device__ uint32_t g_epoch;
__device__ uint32_t g_err;
__device__ __align__(16) uint32_t g_segcnt[NSEG];
__device__ __align__(1024) bf16 g_K[NSEG * LK * HD];
__device__ __align__(1024) bf16 g_V[NSEG * LK * HD];
__device__ __align__(1024) bf16 g_O[S_TOK * HD];
__device__ __align__(1024) bf16 g_qkv[S_TOK * 3 * DM];
__device__ __align__(1024) bf16 g_Ob[S_TOK * DM];
__device__ float g_gate[2 * S_TOK];
__device__ uint32_t g_cnt[512 * 8];
__device__ uint32_t g_queue;
#define GTR(i) do {} while (0)

__device__ __forceinline__ uint32_t smem_u32(const void* p) { return (uint32_t)__cvta_generic_to_shared(p); }
__device__ __forceinline__ uint32_t clk32() { uint32_t t; asm volatile("mov.u32 %0, %%clock;" : "=r"(t)::"memory"); return t; }
__device__ __forceinline__ uint32_t mapa(uint32_t a, uint32_t r) { uint32_t o; asm("mapa.shared::cluster.u32 %0, %1, %2;" : "=r"(o) : "r"(a), "r"(r)); return o; }
__device__ __forceinline__ void mbar_init(uint32_t b, uint32_t c) { asm volatile("mbarrier.init.shared::cta.b64 [%0], %1;" ::"r"(b), "r"(c) : "memory"); }
__device__ __forceinline__ void mbar_expect(uint32_t b, uint32_t bytes) { asm volatile("mbarrier.arrive.expect_tx.shared::cta.b64 _, [%0], %1;" ::"r"(b), "r"(bytes) : "memory"); }
__device__ __forceinline__ void mbar_arrive(uint32_t b) { asm volatile("mbarrier.arrive.shared::cta.b64 _, [%0];" ::"r"(b) : "memory"); }
__device__ __forceinline__ bool mbar_try(uint32_t b, uint32_t par) {
  uint32_t p;
  asm volatile("{.reg .pred p; mbarrier.try_wait.parity.shared::cta.b64 p, [%1], %2; selp.u32 %0,1,0,p;}" : "=r"(p) : "r"(b), "r"(par) : "memory");
  return p;
}
__device__ __forceinline__ bool mbar_test(uint32_t b, uint32_t par) {
  uint32_t p;
  asm volatile("{.reg .pred p; mbarrier.test_wait.parity.shared::cta.b64 p, [%1], %2; selp.u32 %0,1,0,p;}" : "=r"(p) : "r"(b), "r"(par) : "memory");
  return p;
}
__device__ __forceinline__ bool mbar_try_cl(uint32_t b, uint32_t par) {
  uint32_t p;
  asm volatile("{.reg .pred p; mbarrier.try_wait.parity.acquire.cluster.shared::cta.b64 p, [%1], %2; selp.u32 %0,1,0,p;}" : "=r"(p) : "r"(b), "r"(par) : "memory");
  return p;
}
__device__ __forceinline__ void mbar_wait(uint32_t b, uint32_t par) {
  int n = 0;
#pragma unroll 1
  while (!mbar_try(b, par)) { if (++n > SPIN_MAX) { g_err = 1; break; } }
}
__device__ __forceinline__ void mbar_wait_cl(uint32_t b, uint32_t par) {
  int n = 0;
#pragma unroll 1
  while (!mbar_try_cl(b, par)) { if (++n > SPIN_MAX) { g_err = 2; break; } }
}
__device__ __forceinline__ void cluster_sync() { asm volatile("barrier.cluster.arrive.release.aligned; barrier.cluster.wait.acquire.aligned;" ::: "memory"); }
__device__ __forceinline__ void bar_sync(int id, int n) { asm volatile("bar.sync %0, %1;" ::"r"(id), "r"(n) : "memory"); }
__device__ __forceinline__ void bar_arrive(int id, int n) { asm volatile("bar.arrive %0, %1;" ::"r"(id), "r"(n) : "memory"); }
__device__ __forceinline__ void fence_async_smem() { asm volatile("fence.proxy.async.shared::cta;" ::: "memory"); }
__device__ __forceinline__ void ldsm4(uint32_t* r, uint32_t a) {
  asm volatile("ldmatrix.sync.aligned.m8n8.x4.shared.b16 {%0,%1,%2,%3}, [%4];" : "=r"(r[0]), "=r"(r[1]), "=r"(r[2]), "=r"(r[3]) : "r"(a) : "memory");
}
__device__ __forceinline__ void ldsm4t(uint32_t* r, uint32_t a) {
  asm volatile("ldmatrix.sync.aligned.m8n8.x4.trans.shared.b16 {%0,%1,%2,%3}, [%4];" : "=r"(r[0]), "=r"(r[1]), "=r"(r[2]), "=r"(r[3]) : "r"(a) : "memory");
}
__device__ __forceinline__ void ldsm2t(uint32_t* r, uint32_t a) {
  asm volatile("ldmatrix.sync.aligned.m8n8.x2.trans.shared.b16 {%0,%1}, [%2];" : "=r"(r[0]), "=r"(r[1]) : "r"(a) : "memory");
}
__device__ __forceinline__ void stsm4t(uint32_t a, uint32_t r0, uint32_t r1, uint32_t r2, uint32_t r3) {
  asm volatile("stmatrix.sync.aligned.m8n8.x4.trans.shared.b16 [%0], {%1,%2,%3,%4};" ::"r"(a), "r"(r0), "r"(r1), "r"(r2), "r"(r3) : "memory");
}
__device__ __forceinline__ void stsm2t(uint32_t a, uint32_t r0, uint32_t r1) {
  asm volatile("stmatrix.sync.aligned.m8n8.x2.trans.shared.b16 [%0], {%1,%2};" ::"r"(a), "r"(r0), "r"(r1) : "memory");
}
__device__ __forceinline__ uint32_t movmat(uint32_t a) { uint32_t d; asm volatile("movmatrix.sync.aligned.m8n8.trans.b16 %0, %1;" : "=r"(d) : "r"(a)); return d; }
__device__ __forceinline__ void mma16816(float* d, const uint32_t* a, uint32_t b0, uint32_t b1) {
  asm volatile("mma.sync.aligned.m16n8k16.row.col.f32.bf16.bf16.f32 {%0,%1,%2,%3}, {%4,%5,%6,%7}, {%8,%9}, {%0,%1,%2,%3};"
               : "+f"(d[0]), "+f"(d[1]), "+f"(d[2]), "+f"(d[3]) : "r"(a[0]), "r"(a[1]), "r"(a[2]), "r"(a[3]), "r"(b0), "r"(b1));
}
__device__ __forceinline__ void mma1688(float* d, uint32_t a0, uint32_t a1, uint32_t b0) {
  asm volatile("mma.sync.aligned.m16n8k8.row.col.f32.bf16.bf16.f32 {%0,%1,%2,%3}, {%4,%5}, {%6}, {%0,%1,%2,%3};"
               : "+f"(d[0]), "+f"(d[1]), "+f"(d[2]), "+f"(d[3]) : "r"(a0), "r"(a1), "r"(b0));
}
__device__ __forceinline__ uint32_t pack2(float lo, float hi) { uint32_t r; asm("cvt.rn.bf16x2.f32 %0, %1, %2;" : "=r"(r) : "f"(hi), "f"(lo)); return r; }
__device__ __forceinline__ float bf_lo(uint32_t w) { return __uint_as_float(w << 16); }
__device__ __forceinline__ float bf_hi(uint32_t w) { return __uint_as_float(w & 0xffff0000u); }
__device__ __forceinline__ float ex2(float x) { float y; asm("ex2.approx.ftz.f32 %0, %1;" : "=f"(y) : "f"(x)); return y; }
__device__ __forceinline__ void sts128(uint32_t a, uint32_t x, uint32_t y, uint32_t z, uint32_t w) { asm volatile("st.shared.v4.b32 [%0], {%1,%2,%3,%4};" ::"r"(a), "r"(x), "r"(y), "r"(z), "r"(w) : "memory"); }
__device__ __forceinline__ void sts128f(uint32_t a, float x, float y, float z, float w) { asm volatile("st.shared.v4.f32 [%0], {%1,%2,%3,%4};" ::"r"(a), "f"(x), "f"(y), "f"(z), "f"(w) : "memory"); }
__device__ __forceinline__ void sts64f(uint32_t a, float x, float y) { asm volatile("st.shared.v2.f32 [%0], {%1,%2};" ::"r"(a), "f"(x), "f"(y) : "memory"); }
__device__ __forceinline__ void sts32(uint32_t a, uint32_t x) { asm volatile("st.shared.b32 [%0], %1;" ::"r"(a), "r"(x) : "memory"); }
__device__ __forceinline__ void smax32(uint32_t a, uint32_t x) { asm volatile("red.shared.max.u32 [%0], %1;" ::"r"(a), "r"(x) : "memory"); }
__device__ __forceinline__ uint32_t lds32(uint32_t a) { uint32_t v; asm volatile("ld.shared.b32 %0, [%1];" : "=r"(v) : "r"(a) : "memory"); return v; }
__device__ __forceinline__ float4 lds128f(uint32_t a) { float4 v; asm volatile("ld.shared.v4.f32 {%0,%1,%2,%3}, [%4];" : "=f"(v.x), "=f"(v.y), "=f"(v.z), "=f"(v.w) : "r"(a) : "memory"); return v; }
__device__ __forceinline__ uint4 lds128(uint32_t a) { uint4 v; asm volatile("ld.shared.v4.b32 {%0,%1,%2,%3}, [%4];" : "=r"(v.x), "=r"(v.y), "=r"(v.z), "=r"(v.w) : "r"(a) : "memory"); return v; }
__device__ __forceinline__ float2 lds64f(uint32_t a) { float2 v; asm volatile("ld.shared.v2.f32 {%0,%1}, [%2];" : "=f"(v.x), "=f"(v.y) : "r"(a) : "memory"); return v; }
__device__ __forceinline__ void st_async2(uint32_t a, uint32_t x, uint32_t y, uint32_t bar) {
  asm volatile("st.async.weak.shared::cluster.mbarrier::complete_tx::bytes.v2.b32 [%0], {%1,%2}, [%3];" ::"r"(a), "r"(x), "r"(y), "r"(bar) : "memory");
}
__device__ __forceinline__ void st_async4(uint32_t a, uint32_t x, uint32_t y, uint32_t z, uint32_t w, uint32_t bar) {
  asm volatile("st.async.weak.shared::cluster.mbarrier::complete_tx::bytes.v4.b32 [%0], {%1,%2,%3,%4}, [%5];" ::"r"(a), "r"(x), "r"(y), "r"(z), "r"(w), "r"(bar) : "memory");
}
__device__ __forceinline__ void sts64(uint32_t a, uint32_t x, uint32_t y) { asm volatile("st.shared.v2.b32 [%0], {%1,%2};" ::"r"(a), "r"(x), "r"(y) : "memory"); }
__device__ __forceinline__ bool bar_red_or(int id, int n, bool q) {
  uint32_t r;
  asm volatile("{.reg .pred p, q; setp.ne.u32 q, %3, 0; barrier.cta.red.or.aligned.pred p, %1, %2, q; selp.u32 %0,1,0,p;}" : "=r"(r) : "r"(id), "r"(n), "r"((uint32_t)q) : "memory");
  return r;
}
__device__ __forceinline__ float rcp(float x) { float y; asm("rcp.approx.ftz.f32 %0, %1;" : "=f"(y) : "f"(x)); return y; }
__device__ __forceinline__ uint32_t hadd2(uint32_t a, uint32_t b) { uint32_t r; asm("add.rn.bf16x2 %0, %1, %2;" : "=r"(r) : "r"(a), "r"(b)); return r; }
__device__ __forceinline__ uint32_t pin(uint32_t v) { asm volatile("" : "+r"(v)); return v; }
template <int ID> __device__ __forceinline__ void sched_fence_(uint32_t a) {
  asm volatile("{.reg .pred p;\nsetp.eq.u32 p, %0, %1;\nSF: @p pmevent 0;\n@p bra.uni SF;}" ::"r"(a), "n"(0x40000000 + ID) : "memory");
}
#define sched_fence(a) sched_fence_<__LINE__>(a)
__device__ __forceinline__ bool elect() {
  uint32_t p;
  asm volatile("{.reg .pred p; elect.sync _|p, 0xffffffff; selp.u32 %0,1,0,p;}" : "=r"(p));
  return p;
}
__device__ __forceinline__ uint32_t opaque(uint32_t v) { return __shfl_sync(~0u, v, threadIdx.x & 31); }
__device__ __forceinline__ uint4 ldg_rlx128(const void* p) {
  uint4 v; asm volatile("ld.relaxed.gpu.global.v4.b32 {%0,%1,%2,%3}, [%4];" : "=r"(v.x), "=r"(v.y), "=r"(v.z), "=r"(v.w) : "l"(p) : "memory"); return v;
}
__device__ __forceinline__ uint2 ldg_rlx64(const void* p) {
  uint2 v; asm volatile("{.reg .b64 t; ld.relaxed.gpu.global.b64 t, [%2]; mov.b64 {%0,%1}, t;}" : "=r"(v.x), "=r"(v.y) : "l"(p) : "memory"); return v;
}
__device__ __forceinline__ uint32_t hmaxabs2(uint32_t a, uint32_t b) { uint32_t r; asm("max.xorsign.abs.bf16x2 %0, %1, %2;" : "=r"(r) : "r"(a), "r"(b)); return r; }
__device__ __forceinline__ uint32_t ldg_rlx32(const void* p) {
  uint32_t v; asm volatile("ld.relaxed.gpu.global.b32 %0, [%1];" : "=r"(v) : "l"(p) : "memory"); return v;
}
__device__ __forceinline__ void spin_until(uint32_t t0, uint32_t d) {
#pragma unroll 1
  while (clk32() - t0 < d) {}
}
__device__ __forceinline__ void stg_rlx64(void* p, uint32_t a, uint32_t b) {
  asm volatile("{.reg .b64 t; mov.b64 t, {%1,%2}; st.relaxed.gpu.global.b64 [%0], t;}" ::"l"(p), "r"(a), "r"(b) : "memory");
}
__device__ __forceinline__ uint32_t ldg_acq32(const void* p) { uint32_t v; asm volatile("ld.acquire.gpu.global.b32 %0, [%1];" : "=r"(v) : "l"(p) : "memory"); return v; }
__device__ __forceinline__ void stg_rel32(void* p, uint32_t v) { asm volatile("st.release.gpu.global.b32 [%0], %1;" ::"l"(p), "r"(v) : "memory"); }
__device__ __forceinline__ void cp_async16(uint32_t dst, const void* src) { asm volatile("cp.async.cg.shared.global [%0], [%1], 16;" ::"r"(dst), "l"(src) : "memory"); }
__device__ __forceinline__ void cp_async_wait_all() { asm volatile("cp.async.wait_all;" ::: "memory"); }
__device__ __forceinline__ void prefetch_l2(const void* p) { asm volatile("prefetch.global.L2 [%0];" ::"l"(p)); }
__device__ __forceinline__ void tma_load3(uint32_t dst, const CUtensorMap* tm, int c0, int c1, int c2, uint32_t bar) {
  asm volatile("cp.async.bulk.tensor.3d.shared::cluster.global.mbarrier::complete_tx::bytes [%0], [%1, {%3,%4,%5}], [%2];"
               ::"r"(dst), "l"(tm), "r"(bar), "r"(c0), "r"(c1), "r"(c2) : "memory");
}
__device__ __forceinline__ void tma_load2(uint32_t dst, const CUtensorMap* tm, int c0, int c1, uint32_t bar) {
  asm volatile("cp.async.bulk.tensor.2d.shared::cluster.global.mbarrier::complete_tx::bytes [%0], [%1, {%3,%4}], [%2];"
               ::"r"(dst), "l"(tm), "r"(bar), "r"(c0), "r"(c1) : "memory");
}
__device__ __forceinline__ void prefetch_map(const CUtensorMap* tm) { asm volatile("prefetch.tensormap [%0];" ::"l"(tm) : "memory"); }
__device__ __forceinline__ void tma_store2(const CUtensorMap* tm, uint32_t src, int c0, int c1) {
  asm volatile("cp.async.bulk.tensor.2d.global.shared::cta.bulk_group [%0, {%2,%3}], [%1];" ::"l"(tm), "r"(src), "r"(c0), "r"(c1) : "memory");
}
__device__ __forceinline__ void bulk_commit() { asm volatile("cp.async.bulk.commit_group;" ::: "memory"); }
__device__ __forceinline__ void bulk_wait0() { asm volatile("cp.async.bulk.wait_group 0;" ::: "memory"); }
__device__ __forceinline__ void bulk_wait_read0() { asm volatile("cp.async.bulk.wait_group.read 0;" ::: "memory"); }
__device__ __forceinline__ void wg_fence() { asm volatile("wgmma.fence.sync.aligned;" ::: "memory"); }
__device__ __forceinline__ void wg_commit() { asm volatile("wgmma.commit_group.sync.aligned;" ::: "memory"); }
__device__ __forceinline__ void wg_wait0() { asm volatile("wgmma.wait_group.sync.aligned 0;" ::: "memory"); }
__device__ __forceinline__ uint64_t desc_sw128(uint32_t addr) {
  return (uint64_t)((addr & 0x3FFFF) >> 4) | ((uint64_t)1 << 16) | ((uint64_t)64 << 32) | ((uint64_t)1 << 62);
}
template <int ACC>
__device__ __forceinline__ void wgmma_rs32(float* d, const uint32_t* a, uint64_t db) {
  asm volatile("{.reg .pred p; setp.ne.b32 p, %21, 0;\n"
               "wgmma.mma_async.sync.aligned.m64n32k16.f32.bf16.bf16 {%0,%1,%2,%3,%4,%5,%6,%7,%8,%9,%10,%11,%12,%13,%14,%15}, {%16,%17,%18,%19}, %20, p, 1, 1, 0;}"
               : "+f"(d[0]), "+f"(d[1]), "+f"(d[2]), "+f"(d[3]), "+f"(d[4]), "+f"(d[5]), "+f"(d[6]), "+f"(d[7]), "+f"(d[8]), "+f"(d[9]),
                 "+f"(d[10]), "+f"(d[11]), "+f"(d[12]), "+f"(d[13]), "+f"(d[14]), "+f"(d[15])
               : "r"(a[0]), "r"(a[1]), "r"(a[2]), "r"(a[3]), "l"(db), "n"(ACC));
}

template <int N> __device__ __forceinline__ void fence_regs(float* d) {
#pragma unroll
  for (int i = 0; i < N; i++) asm volatile("" : "+f"(d[i])::"memory");
}
__device__ __forceinline__ void wg_wait1() { asm volatile("wgmma.wait_group.sync.aligned 1;" ::: "memory"); }
__device__ __forceinline__ void tma_store3(const CUtensorMap* tm, uint32_t src, int c0, int c1, int c2) {
  asm volatile("cp.async.bulk.tensor.3d.global.shared::cta.bulk_group [%0, {%2,%3,%4}], [%1];" ::"l"(tm), "r"(src), "r"(c0), "r"(c1), "r"(c2) : "memory");
}
__device__ __forceinline__ void tma_red3(const CUtensorMap* tm, uint32_t src, int c0, int c1, int c2) {
  asm volatile("cp.reduce.async.bulk.tensor.3d.global.shared::cta.add.bulk_group [%0, {%2,%3,%4}], [%1];" ::"l"(tm), "r"(src), "r"(c0), "r"(c1), "r"(c2) : "memory");
}
__device__ __forceinline__ void stsm4(uint32_t a, uint32_t r0, uint32_t r1, uint32_t r2, uint32_t r3) {
  asm volatile("stmatrix.sync.aligned.m8n8.x4.shared.b16 [%0], {%1,%2,%3,%4};" ::"r"(a), "r"(r0), "r"(r1), "r"(r2), "r"(r3) : "memory");
}
__device__ __forceinline__ uint2 lds64(uint32_t a) { uint2 v; asm volatile("ld.shared.v2.b32 {%0,%1}, [%2];" : "=r"(v.x), "=r"(v.y) : "r"(a) : "memory"); return v; }
__device__ __forceinline__ uint32_t hmul2(uint32_t a, uint32_t b) { uint32_t r; asm("mul.rn.bf16x2 %0, %1, %2;" : "=r"(r) : "r"(a), "r"(b)); return r; }
__device__ __forceinline__ void wgmma_ss192t(float* d, uint64_t da, uint64_t db, int acc) {
  asm volatile("{.reg .pred p; setp.ne.b32 p, %98, 0;\n"
    "wgmma.mma_async.sync.aligned.m64n192k16.f32.bf16.bf16 "
    "{%0,%1,%2,%3,%4,%5,%6,%7,%8,%9,%10,%11,%12,%13,%14,%15,%16,%17,%18,%19,%20,%21,%22,%23,%24,%25,%26,%27,%28,%29,%30,%31,%32,%33,%34,%35,%36,%37,%38,%39,%40,%41,%42,%43,%44,%45,%46,%47,%48,%49,%50,%51,%52,%53,%54,%55,%56,%57,%58,%59,%60,%61,%62,%63,%64,%65,%66,%67,%68,%69,%70,%71,%72,%73,%74,%75,%76,%77,%78,%79,%80,%81,%82,%83,%84,%85,%86,%87,%88,%89,%90,%91,%92,%93,%94,%95}, %96, %97, p, 1, 1, 0, 1;}"
    : "+f"(d[0]), "+f"(d[1]), "+f"(d[2]), "+f"(d[3]), "+f"(d[4]), "+f"(d[5]), "+f"(d[6]), "+f"(d[7]), "+f"(d[8]), "+f"(d[9]), "+f"(d[10]), "+f"(d[11]),
      "+f"(d[12]), "+f"(d[13]), "+f"(d[14]), "+f"(d[15]), "+f"(d[16]), "+f"(d[17]), "+f"(d[18]), "+f"(d[19]), "+f"(d[20]), "+f"(d[21]), "+f"(d[22]),
      "+f"(d[23]), "+f"(d[24]), "+f"(d[25]), "+f"(d[26]), "+f"(d[27]), "+f"(d[28]), "+f"(d[29]), "+f"(d[30]), "+f"(d[31]), "+f"(d[32]), "+f"(d[33]),
      "+f"(d[34]), "+f"(d[35]), "+f"(d[36]), "+f"(d[37]), "+f"(d[38]), "+f"(d[39]), "+f"(d[40]), "+f"(d[41]), "+f"(d[42]), "+f"(d[43]), "+f"(d[44]),
      "+f"(d[45]), "+f"(d[46]), "+f"(d[47]), "+f"(d[48]), "+f"(d[49]), "+f"(d[50]), "+f"(d[51]), "+f"(d[52]), "+f"(d[53]), "+f"(d[54]), "+f"(d[55]),
      "+f"(d[56]), "+f"(d[57]), "+f"(d[58]), "+f"(d[59]), "+f"(d[60]), "+f"(d[61]), "+f"(d[62]), "+f"(d[63]), "+f"(d[64]), "+f"(d[65]), "+f"(d[66]),
      "+f"(d[67]), "+f"(d[68]), "+f"(d[69]), "+f"(d[70]), "+f"(d[71]), "+f"(d[72]), "+f"(d[73]), "+f"(d[74]), "+f"(d[75]), "+f"(d[76]), "+f"(d[77]),
      "+f"(d[78]), "+f"(d[79]), "+f"(d[80]), "+f"(d[81]), "+f"(d[82]), "+f"(d[83]), "+f"(d[84]), "+f"(d[85]), "+f"(d[86]), "+f"(d[87]), "+f"(d[88]),
      "+f"(d[89]), "+f"(d[90]), "+f"(d[91]), "+f"(d[92]), "+f"(d[93]), "+f"(d[94]), "+f"(d[95])
    : "l"(da), "l"(db), "r"(acc));
}
__device__ __forceinline__ void wgmma_rs128t(float* d, const uint32_t* a, uint64_t db, int acc) {
  asm volatile("{.reg .pred p; setp.ne.b32 p, %69, 0;\n"
    "wgmma.mma_async.sync.aligned.m64n128k16.f32.bf16.bf16 "
    "{%0,%1,%2,%3,%4,%5,%6,%7,%8,%9,%10,%11,%12,%13,%14,%15,%16,%17,%18,%19,%20,%21,%22,%23,%24,%25,%26,%27,%28,%29,%30,%31,%32,%33,%34,%35,%36,%37,%38,%39,%40,%41,%42,%43,%44,%45,%46,%47,%48,%49,%50,%51,%52,%53,%54,%55,%56,%57,%58,%59,%60,%61,%62,%63}, {%64,%65,%66,%67}, %68, p, 1, 1, 1;}"
    : "+f"(d[0]), "+f"(d[1]), "+f"(d[2]), "+f"(d[3]), "+f"(d[4]), "+f"(d[5]), "+f"(d[6]), "+f"(d[7]), "+f"(d[8]), "+f"(d[9]), "+f"(d[10]), "+f"(d[11]),
      "+f"(d[12]), "+f"(d[13]), "+f"(d[14]), "+f"(d[15]), "+f"(d[16]), "+f"(d[17]), "+f"(d[18]), "+f"(d[19]), "+f"(d[20]), "+f"(d[21]), "+f"(d[22]),
      "+f"(d[23]), "+f"(d[24]), "+f"(d[25]), "+f"(d[26]), "+f"(d[27]), "+f"(d[28]), "+f"(d[29]), "+f"(d[30]), "+f"(d[31]), "+f"(d[32]), "+f"(d[33]),
      "+f"(d[34]), "+f"(d[35]), "+f"(d[36]), "+f"(d[37]), "+f"(d[38]), "+f"(d[39]), "+f"(d[40]), "+f"(d[41]), "+f"(d[42]), "+f"(d[43]), "+f"(d[44]),
      "+f"(d[45]), "+f"(d[46]), "+f"(d[47]), "+f"(d[48]), "+f"(d[49]), "+f"(d[50]), "+f"(d[51]), "+f"(d[52]), "+f"(d[53]), "+f"(d[54]), "+f"(d[55]),
      "+f"(d[56]), "+f"(d[57]), "+f"(d[58]), "+f"(d[59]), "+f"(d[60]), "+f"(d[61]), "+f"(d[62]), "+f"(d[63])
    : "r"(a[0]), "r"(a[1]), "r"(a[2]), "r"(a[3]), "l"(db), "r"(acc));
}
__device__ __forceinline__ void wgmma_rs80(float* d, const uint32_t* a, uint64_t db, int acc) {
  asm volatile("{.reg .pred p; setp.ne.b32 p, %45, 0;\n"
    "wgmma.mma_async.sync.aligned.m64n80k16.f32.bf16.bf16 "
    "{%0,%1,%2,%3,%4,%5,%6,%7,%8,%9,%10,%11,%12,%13,%14,%15,%16,%17,%18,%19,%20,%21,%22,%23,%24,%25,%26,%27,%28,%29,%30,%31,%32,%33,%34,%35,%36,%37,%38,%39}, {%40,%41,%42,%43}, %44, p, 1, 1, 0;}"
    : "+f"(d[0]), "+f"(d[1]), "+f"(d[2]), "+f"(d[3]), "+f"(d[4]), "+f"(d[5]), "+f"(d[6]), "+f"(d[7]), "+f"(d[8]), "+f"(d[9]), "+f"(d[10]), "+f"(d[11]),
      "+f"(d[12]), "+f"(d[13]), "+f"(d[14]), "+f"(d[15]), "+f"(d[16]), "+f"(d[17]), "+f"(d[18]), "+f"(d[19]), "+f"(d[20]), "+f"(d[21]), "+f"(d[22]),
      "+f"(d[23]), "+f"(d[24]), "+f"(d[25]), "+f"(d[26]), "+f"(d[27]), "+f"(d[28]), "+f"(d[29]), "+f"(d[30]), "+f"(d[31]), "+f"(d[32]), "+f"(d[33]),
      "+f"(d[34]), "+f"(d[35]), "+f"(d[36]), "+f"(d[37]), "+f"(d[38]), "+f"(d[39])
    : "r"(a[0]), "r"(a[1]), "r"(a[2]), "r"(a[3]), "l"(db), "r"(acc));
}
__device__ __forceinline__ void wgmma_rs192t(float* d, const uint32_t* a, uint64_t db, int acc) {
  asm volatile("{.reg .pred p; setp.ne.b32 p, %101, 0;\n"
    "wgmma.mma_async.sync.aligned.m64n192k16.f32.bf16.bf16 "
    "{%0,%1,%2,%3,%4,%5,%6,%7,%8,%9,%10,%11,%12,%13,%14,%15,%16,%17,%18,%19,%20,%21,%22,%23,%24,%25,%26,%27,%28,%29,%30,%31,%32,%33,%34,%35,%36,%37,%38,%39,%40,%41,%42,%43,%44,%45,%46,%47,%48,%49,%50,%51,%52,%53,%54,%55,%56,%57,%58,%59,%60,%61,%62,%63,%64,%65,%66,%67,%68,%69,%70,%71,%72,%73,%74,%75,%76,%77,%78,%79,%80,%81,%82,%83,%84,%85,%86,%87,%88,%89,%90,%91,%92,%93,%94,%95}, {%96,%97,%98,%99}, %100, p, 1, 1, 1;}"
    : "+f"(d[0]), "+f"(d[1]), "+f"(d[2]), "+f"(d[3]), "+f"(d[4]), "+f"(d[5]), "+f"(d[6]), "+f"(d[7]), "+f"(d[8]), "+f"(d[9]), "+f"(d[10]), "+f"(d[11]),
      "+f"(d[12]), "+f"(d[13]), "+f"(d[14]), "+f"(d[15]), "+f"(d[16]), "+f"(d[17]), "+f"(d[18]), "+f"(d[19]), "+f"(d[20]), "+f"(d[21]), "+f"(d[22]),
      "+f"(d[23]), "+f"(d[24]), "+f"(d[25]), "+f"(d[26]), "+f"(d[27]), "+f"(d[28]), "+f"(d[29]), "+f"(d[30]), "+f"(d[31]), "+f"(d[32]), "+f"(d[33]),
      "+f"(d[34]), "+f"(d[35]), "+f"(d[36]), "+f"(d[37]), "+f"(d[38]), "+f"(d[39]), "+f"(d[40]), "+f"(d[41]), "+f"(d[42]), "+f"(d[43]), "+f"(d[44]),
      "+f"(d[45]), "+f"(d[46]), "+f"(d[47]), "+f"(d[48]), "+f"(d[49]), "+f"(d[50]), "+f"(d[51]), "+f"(d[52]), "+f"(d[53]), "+f"(d[54]), "+f"(d[55]),
      "+f"(d[56]), "+f"(d[57]), "+f"(d[58]), "+f"(d[59]), "+f"(d[60]), "+f"(d[61]), "+f"(d[62]), "+f"(d[63]), "+f"(d[64]), "+f"(d[65]), "+f"(d[66]),
      "+f"(d[67]), "+f"(d[68]), "+f"(d[69]), "+f"(d[70]), "+f"(d[71]), "+f"(d[72]), "+f"(d[73]), "+f"(d[74]), "+f"(d[75]), "+f"(d[76]), "+f"(d[77]),
      "+f"(d[78]), "+f"(d[79]), "+f"(d[80]), "+f"(d[81]), "+f"(d[82]), "+f"(d[83]), "+f"(d[84]), "+f"(d[85]), "+f"(d[86]), "+f"(d[87]), "+f"(d[88]),
      "+f"(d[89]), "+f"(d[90]), "+f"(d[91]), "+f"(d[92]), "+f"(d[93]), "+f"(d[94]), "+f"(d[95])
    : "r"(a[0]), "r"(a[1]), "r"(a[2]), "r"(a[3]), "l"(db), "r"(acc));
}

constexpr int NPQ = 2;
#define NQ 12
#define NQ_WIN 8
#define NO_EARLY 6
#define NO_MID 9
#define NW1 16
#define NW1A 10
#define VLD 10
#define XPF 3
#define WSPLIT 32
#define PFENCE 0
#define DFENCE 0
#define VSW 2
#define PD 1200
constexpr int R_WQ = 0;
constexpr int R_WO = R_WQ + 8 * (20 - NPQ) * 512;
constexpr int R_XT = R_WO + 14 * 12 * 512;
constexpr int R_MEM = R_XT;
constexpr int R_QB = R_XT + 40960;
constexpr int R_QA = R_QB + 1024;
constexpr int R_O2 = R_QA + 1024;
constexpr int R_VS = R_O2 + 1024;
constexpr int R_KT = R_VS + 1024;
constexpr int R_VT = R_KT + 5120;
constexpr int R_V1 = R_VT + 5120;
constexpr int R_SX = R_V1 + 8192;
constexpr int R_VM = R_SX + 4608;
constexpr int R_BAR = R_VM + 2048;
constexpr int R_MI = R_BAR + 64;
constexpr int R_SMEM = R_MI + 64;
static_assert(NPQ == 2 && R_XT % 1024 == 0 && R_KT % 1024 == 0 && R_VT % 1024 == 0 && R_V1 % 1024 == 0 && R_WO % 1024 == 0, "align");
constexpr int R_SMEM_ALLOC = R_SMEM;
static_assert(R_SMEM_ALLOC <= 232448, "smem");

#define TR(i) do {} while (0)

__device__ __forceinline__ void red_pair(unsigned char* p, float lo, float hi) {
  const int b = __float2int_rn(lo), a = __float2int_rn(hi);
  asm volatile("{.reg .b64 t; mov.b64 t, {%1,%2}; red.relaxed.gpu.global.add.u64 [%0], t;}" ::"l"(p), "r"(b + ((1 << 29) + (1 << 23))), "r"(a * 8) : "memory");
}
__device__ __forceinline__ unsigned long long swap0(unsigned char* p) {
  unsigned long long r;
  asm volatile("atom.relaxed.gpu.global.exch.b64 %0, [%1], 0;" : "=l"(r) : "l"(p) : "memory");
  return r;
}
__device__ __forceinline__ void bulk_to_peer(uint32_t dst, uint32_t src, uint32_t bytes, uint32_t bar) {
  asm volatile("cp.async.bulk.shared::cluster.shared::cta.mbarrier::complete_tx::bytes [%0], [%1], %2, [%3];" ::"r"(dst), "r"(src), "r"(bytes), "r"(bar) : "memory");
}
__device__ __forceinline__ uint32_t dec_pair(uint32_t lo, uint32_t hi, uint32_t bias) { return pack2((float)(int)(lo * 8u + bias), (float)(int)hi); }

__global__ void __cluster_dims__(3, 1, 1) __launch_bounds__(256, 1)
rec_kernel(const __grid_constant__ CUtensorMap tmX, const __grid_constant__ CUtensorMap tmK, const __grid_constant__ CUtensorMap tmV,
           const __grid_constant__ CUtensorMap tmWq, const __grid_constant__ CUtensorMap tmWq2, const __grid_constant__ CUtensorMap tmWk,
           const __grid_constant__ CUtensorMap tmWv, const __grid_constant__ CUtensorMap tmWo, const bf16* __restrict__ mem0,
           const bf16* __restrict__ Wq, const bf16* __restrict__ Wo, const bf16* __restrict__ x) {
  extern __shared__ __align__(1024) unsigned char smem[];
  const uint32_t sb = smem_u32(smem);
  const int tid = threadIdx.x, lane = tid & 31, wid = __shfl_sync(~0u, tid >> 5, 0), g = wid >> 2, w = wid & 3;
  const int cta = blockIdx.x, head = cta / 3, rank = cta % 3;
  const int D0 = head * DH + rank * 64;
  const int tile0 = rank == 0 ? 0 : (rank == 1 ? 14 : 26);
  const uint32_t XBAR = sb + R_BAR, SBAR = XBAR + 8, OBAR = XBAR + 16, VBAR = XBAR + 24, WBAR = XBAR + 40;
  constexpr uint32_t ONES = 0x3F803F80u;
  asm volatile("griddepcontrol.launch_dependents;" ::: "memory");
  GTR(0);
  if (wid == 0) {
    if (lane == 0) {
      mbar_init(XBAR, 1); mbar_init(SBAR, 4); mbar_init(OBAR, 5); mbar_init(VBAR, 1);
      mbar_init(WBAR, 1); mbar_init(WBAR + 8, 1); mbar_init(WBAR + 16, 1);
      asm volatile("fence.mbarrier_init.release.cluster;" ::: "memory");
      mbar_expect(WBAR, 81920); mbar_expect(WBAR + 8, 81920 + 2 * NPQ * 2048); mbar_expect(XBAR, 40960);
      mbar_expect(SBAR, 3072); mbar_expect(OBAR, 2048); mbar_expect(VBAR, 8192);
      sts128(sb + R_MI + 48, 0, 0, 0, 0);
    }
    __syncwarp();
    if (lane < 5) tma_load2(sb + lane * 16384, &tmWk, D0, lane * 128, WBAR);
    if (lane == 5) tma_load3(sb + R_XT, &tmX, 0, 0, 0, XBAR);
    if (lane < 5) tma_load2(lane < 4 ? sb + 81920 + lane * 16384 : sb + R_QB, &tmWv, D0, lane * 128, WBAR + 8);
    if (lane < 2) tma_load2(sb + R_QB + 16384 + lane * 4096, &tmWq2, D0, lane * 320, WBAR + 8);
  }
  if (tid == 32) { prefetch_map(&tmWq); prefetch_map(&tmWo); prefetch_map(&tmK); prefetch_map(&tmV); }
  if (tid >= 64 && tid < 144) prefetch_l2(mem0 + (tid - 64) * 64);
  __syncthreads();
  GTR(1);
#pragma unroll
  for (int i = 0; i < 5; i++) { const int l = tid + i * 256; prefetch_l2((l < 640 ? Wq : Wo - 40960) + (size_t)cta * 40960 + l * 64); }
  uint32_t ww[40][4], wqp[NPQ][4];
  {
    uint32_t xm = 0;
#pragma unroll
    for (int i = 0; i < 7; i++) {
      const int v = tid + i * 256, gv = cta * 1707 + v;
      if (v < 1707 && gv < S_TOK * DM / 8) {
        const uint4 q = __ldg((const uint4*)x + gv);
        xm = hmaxabs2(hmaxabs2(xm, hmaxabs2(q.x, q.y)), hmaxabs2(q.z, q.w));
      }
    }
    xm = __reduce_max_sync(~0u, max((xm << 16) & 0x7fffffffu, xm & 0x7fff0000u));
    const uint32_t p = sb + (lane >> 4) * 1024 + (lane & 7) * 128 + (((2 * w + ((lane >> 3) & 1)) ^ (lane & 7)) << 4);
    mbar_wait(WBAR + 8 * g, 0);
    GTR(2);
#pragma unroll
    for (int f = 0; f < 40; f++) ldsm4t(ww[f], (f >= 32 && g == 1) ? p + R_QB + (f - 32) * 2048 : p + g * 81920 + f * 2048);
    mbar_wait(WBAR + 8, 0);
    GTR(3);
#pragma unroll
    for (int f = 0; f < NPQ; f++) ldsm4t(wqp[f], p + R_QB + 16384 + g * 4096 + f * 2048);
    __syncthreads();
    asm volatile("barrier.cluster.arrive.relaxed.aligned;" ::: "memory");
    if (wid == 0) {
      if (lane == 0) mbar_expect(WBAR + 16, 18 * 4096 + 21 * 4096);
      __syncwarp();
      if (lane < 4) tma_load2(sb + R_WQ + lane * 18432, &tmWq, D0, (lane >> 1) * 320 + 32 + (lane & 1) * 144, WBAR + 16);
      else if (lane < 7) tma_load3(sb + R_WO + ((lane - 1 - rank) % 3) * 28672, &tmWo, 0, head * DH + (lane - 4) * 64, tile0 >> 1, WBAR + 16);
      __syncwarp();
    }
    float nv[4] = {0.f, 0.f, 0.f, 0.f};
#pragma unroll
    for (int f = 0; f < 40; f++) {
      const uint32_t a[4] = {ww[f][0] & 0x7fff7fffu, ww[f][1] & 0x7fff7fffu, ww[f][2] & 0x7fff7fffu, ww[f][3] & 0x7fff7fffu};
      mma16816(nv, a, ONES, ONES);
    }
    const uint32_t mv = __reduce_max_sync(~0u, __float_as_uint(fmaxf(nv[0], nv[2])));
    if (lane == 0) { if (g == 1) smax32(sb + R_MI + 48, mv); smax32(sb + R_MI + 52, xm); }
  }
  GTR(4);

  const uint32_t rF_ = opaque(sb + lane * 16);
  const uint32_t rP_ = opaque(sb + (lane >> 4) * 1024 + (lane & 7) * 128 + (((2 * w + ((lane >> 3) & 1)) ^ (lane & 7)) << 4));
  const int tA = g == 1 ? 2 * w : (rank != 1 ? (w < 2 ? 8 + 2 * w : 10 + w) : 8 + w);
  const bool two = g == 1 || (w < 2 && rank != 1);
  const uint32_t r1 = rank == 2 ? 0 : rank + 1, r2 = rank == 0 ? 2 : rank - 1;
  const uint32_t rW_ = opaque(sb + R_WO + (tA >> 1) * 4096 + ((lane >> 4) * 8 + (lane & 7)) * 64 +
                             (((2 * (tA & 1) + ((lane >> 3) & 1)) ^ ((lane >> 1) & 3)) << 4));
  uint32_t wqt[NQ][4];
  float u = 1.f;
  uint32_t t0 = 0;
  int s = -1;

#define WOFF(ks) (((ks) >> 2) * 28672 + ((ks) & 3) * 1024)
#define XDESC(j) (((uint64_t)0x40000040 << 32) | (dlo + ((((j) >> 2) * 4096 + ((j) & 3) * 32) >> 4)))

  auto window = [&](auto G_, auto FIRST_) {
    constexpr int G = decltype(G_)::value;
    constexpr bool FIRST = decltype(FIRST_)::value;
    const uint32_t rF = pin(rF_), rP = pin(rP_);
    float d[16];
    const uint32_t dlo = pin(((sb + R_XT) >> 4) | 0x10000);
    const uint32_t wqS = rP + R_WQ + G * (20 - NPQ) * 2048;
    uint4 y[5];
    unsigned long long zr = 0;
    const uint32_t t = w * 32 + ((rF - sb) >> 4);
    if (G == 0) zr = swap0(g_red + (((s + 2) & 3) * RB_SIZE + ((cta % 20) * 8 + (t >> 4)) * RB_LINE + (t & 15) * 8));
    if (G == 0) {
      if (!FIRST && w == 3) {
        if (elect()) {
          mbar_expect(SBAR, 3072); mbar_expect(OBAR, 2048); mbar_expect(VBAR, 8192);
          asm volatile("mbarrier.arrive.relaxed.cluster.shared::cluster.b64 _, [%0];" ::"r"(mapa(WBAR, r1)) : "memory");
          asm volatile("mbarrier.arrive.relaxed.cluster.shared::cluster.b64 _, [%0];" ::"r"(mapa(WBAR + 8, r2)) : "memory");
        }
        __syncwarp();
      }
    }
    mbar_wait(XBAR, (s + 1) & 1);
    TR(11);
    wg_fence();
    wgmma_rs32<0>(d, ww[0], XDESC(0));
#pragma unroll
    for (int j = 1; j < WSPLIT; j++) wgmma_rs32<1>(d, ww[j], XDESC(j));
    const unsigned char* yp = g_red + ((s & 3) * RB_SIZE + (G * 80 + (t >> 3)) * RB_LINE + (t & 7) * 16);
    asm volatile("" : "+l"(yp));
    if (!FIRST && G == 1 && w == 1) {
      if (elect()) bulk_wait_read0();
      __syncwarp();
    }
    TR(10);
    if (!FIRST) spin_until(t0, PD);
    if (FIRST) {
      const unsigned short* m = (const unsigned short*)mem0 + (t & 1) * 4 * DM + G * 320 + (t >> 1);
#pragma unroll
      for (int q = 0; q < 5; q++) y[q] = make_uint4(m[q * 64], m[q * 64 + DM], m[q * 64 + 2 * DM], m[q * 64 + 3 * DM]);
    } else {
#pragma unroll
      for (int q = 0; q < 5; q++) y[q] = ldg_rlx128(yp + q * 16 * RB_LINE);
      if (PFENCE) sched_fence(sb);
    }
    TR(9);
#pragma unroll
    for (int j = WSPLIT; j < 40; j++) wgmma_rs32<1>(d, ww[j], XDESC(j));
    wg_commit();
    if (!FIRST) {
#pragma unroll
      for (int f = 0; f < NQ_WIN; f++) ldsm4t(wqt[f], wqS + f * 2048);
    }
    if (FIRST) asm volatile("barrier.cluster.wait.acquire.aligned;" ::: "memory");
    wg_wait0();
    fence_regs<16>(d);
    TR(13);
    __syncthreads();
    {
      uint32_t pk[8];
#pragma unroll
      for (int q = 0; q < 8; q++) pk[q] = pack2(d[2 * q], d[2 * q + 1]);
      stsm4t(rP + (G == 1 ? R_VT : R_KT) + 1024, pk[0], pk[1], pk[2], pk[3]);
      stsm4t(rP + (G == 1 ? R_VT : R_KT) + 3072, pk[4], pk[5], pk[6], pk[7]);
    }
    if (FIRST) {
      mbar_wait(WBAR + 16, 0);
      const uint32_t woA = rW_;
      float na[4] = {0.f, 0.f, 0.f, 0.f}, nb[4] = {0.f, 0.f, 0.f, 0.f};
#pragma unroll
      for (int ks = 0; ks < 12; ks++) {
        uint32_t a[4], b[4];
        ldsm4t(a, woA + WOFF(ks));
        ldsm4t(b, (two ? woA ^ 32 : woA) + WOFF(ks));
#pragma unroll
        for (int q = 0; q < 4; q++) { a[q] &= 0x7fff7fffu; b[q] &= 0x7fff7fffu; }
        mma16816(na, a, ONES, ONES);
        mma16816(nb, b, ONES, ONES);
      }
      const uint32_t mo = __reduce_max_sync(~0u, __float_as_uint(fmaxf(fmaxf(na[0], na[2]), fmaxf(nb[0], nb[2]))));
      if (rF == sb) smax32(sb + R_MI + 56, mo);
      __syncthreads();
      if (G == 1 && w == 2) {
        const uint4 r = lds128(sb + R_MI + 48);
        const uint32_t epoch = *(volatile uint32_t*)&g_epoch + 1;
        if (rF == sb) stg_rlx64(&g_rec[cta], (r.y & 0xffff0000u) | (epoch & 0xffffu), ((r.x + 0xffffu) & 0xffff0000u) | ((r.z + 0xffffu) >> 16));
      }
    }
#pragma unroll
    for (int f = FIRST ? 0 : NQ_WIN; f < NQ; f++) ldsm4t(wqt[f], wqS + f * 2048);
    if (FIRST || DFENCE) sched_fence(sb);
    TR(14);
    const uint32_t ma = sb + R_MEM + G * 5120 + t * 8;
    if (FIRST) {
#pragma unroll
      for (int j = 0; j < 5; j++) sts64(ma + j * 1024, y[j].x | (y[j].y << 16), y[j].z | (y[j].w << 16));
    } else {
      int n = 0;
#pragma unroll 1
      while (!__all_sync(~0u, (y[0].y & y[0].w & y[1].y) & (y[1].w & y[2].y & y[2].w) & (y[3].y & y[3].w & y[4].y) & (y[4].w & 4))) {
#pragma unroll
        for (int j = 0; j < 5; j++) if (!(y[j].y & y[j].w & 4)) y[j] = ldg_rlx128(yp + j * 16 * RB_LINE);
        if (++n > SPIN_MAX) { g_err = 5; break; }
      }
      const uint32_t bias = 0x80000000u + (sb >> 31);
#pragma unroll
      for (int j = 0; j < 5; j++) sts64(ma + j * 1024, dec_pair(y[j].x, y[j].y, bias), dec_pair(y[j].z, y[j].w, bias));
    }
    if (G == 0 && zr == ~0ull) g_err = 9;
    TR(0);
  };

  auto oproj = [&](auto TWO_, auto NPRE_, auto& wot, const uint32_t rF, const uint32_t woA, const uint32_t woB,
                   float sm0, float sm1, bool have_sums) {
    constexpr bool TWO = decltype(TWO_)::value;
    constexpr int NPRE = decltype(NPRE_)::value;
    float c[4][4];
#pragma unroll
    for (int q = 0; q < 4; q++) c[q][0] = c[q][1] = c[q][2] = c[q][3] = 0.f;
    unsigned char* sp = g_red + ((s & 3) * RB_SIZE + (4 * (tile0 + tA) + ((rF - sb) >> 8)) * RB_LINE + (((rF - sb) >> 1) & 120));
    bar_sync(3, 256);
    TR(8);
    uint4 ob[6];
    ob[0] = lds128(rF + R_QB); ob[1] = lds128(rF + R_QB + 512);
    const float2 su = lds64f(sb + R_MI + 48);
    if (!have_sums) { const float2 t = lds64f(sb + R_MI + 16 + (((rF - sb) >> 1) & 24)); sm0 = t.x; sm1 = t.y; }
#pragma unroll
    for (int p = 0; p < 6; p++) {
      if (p + 2 < 6) ob[p + 2] = lds128(rF + (p < 2 ? R_QA : R_O2) + (p & 1) * 512);
#pragma unroll
      for (int e = 0; e < 2; e++) {
        const int ks = 2 * p + e;
        const uint32_t b0 = e ? ob[p].z : ob[p].x, b1 = e ? ob[p].w : ob[p].y;
        if (TWO) {
          const int iA = 2 * ks, iB = iA + 1;
          mma16816(c[e], wot[iA % NPRE], b0, b1);
          if (iA + NPRE < 24) ldsm4t(wot[iA % NPRE], woA + WOFF((iA + NPRE) >> 1));
          mma16816(c[2 + e], wot[iB % NPRE], b0, b1);
          if (iB + NPRE < 24) ldsm4t(wot[iB % NPRE], woB + WOFF((iB + NPRE) >> 1));
        } else {
          mma16816(c[ks & 3], wot[ks], b0, b1);
        }
      }
    }
    const float f0 = su.x * rcp(sm0), f1 = su.x * rcp(sm1);
    t0 = clk32();
    u = su.y;
    if (TWO) {
      red_pair(sp, (c[0][0] + c[1][0]) * f0, (c[0][1] + c[1][1]) * f1);
      red_pair(sp + 2 * RB_LINE, (c[0][2] + c[1][2]) * f0, (c[0][3] + c[1][3]) * f1);
      red_pair(sp + 4 * RB_LINE, (c[2][0] + c[3][0]) * f0, (c[2][1] + c[3][1]) * f1);
      red_pair(sp + 6 * RB_LINE, (c[2][2] + c[3][2]) * f0, (c[2][3] + c[3][3]) * f1);
    } else {
      red_pair(sp, ((c[0][0] + c[1][0]) + (c[2][0] + c[3][0])) * f0, ((c[0][1] + c[1][1]) + (c[2][1] + c[3][1])) * f1);
      red_pair(sp + 2 * RB_LINE, ((c[0][2] + c[1][2]) + (c[2][2] + c[3][2])) * f0, ((c[0][3] + c[1][3]) + (c[2][3] + c[3][3])) * f1);
    }
    TR(15);
  };

  auto step = [&](auto G_, auto LAST_) {
    constexpr int G = decltype(G_)::value;
    constexpr bool LAST = decltype(LAST_)::value;
    __syncthreads();
    const uint32_t rF = pin(rF_), rP = pin(rP_);
    TR(1);
    const uint32_t wqS = rP + R_WQ + G * (20 - NPQ) * 2048, rM = rF + R_MEM;
    const uint32_t l8 = sb + ((rF - sb) >> 1) + w * 256;
    const uint32_t woA = pin(rW_), woB = woA ^ 32;
    float aq[2][4] = {};
    const uint32_t ln = (rF - sb) >> 4;
    const uint32_t rS = sb + (ln & 7) * 128 + (ln < 16 ? R_QB + (ln & 8) * 128 + (((2 * w + G) ^ (ln & 7)) << 4) : R_KT + (((2 * w + ((ln >> 3) & 1)) ^ (ln & 7)) << 4));
    auto qmma = [&](int f, uint32_t b0, uint32_t b1) {
      if (f < NPQ) mma16816(aq[f & 1], wqp[f], b0, b1);
      else {
        const int slot = (f - NPQ) % NQ;
        mma16816(aq[f & 1], wqt[slot], b0, b1);
        if (f + NQ < 20) ldsm4t(wqt[slot], wqS + (f - NPQ + NQ) * 2048);
      }
    };
    if constexpr (G == 1) {
      uint32_t bb[20][4];
      if (!LAST && w == VSW) {
        if (s > 0) { mbar_wait(WBAR, s & 1); mbar_wait(WBAR + 8, s & 1); }
        if (elect()) {
          fence_async_smem();
          bulk_to_peer(mapa(sb + R_V1 + 4096, r1), sb + R_VT + 1024, 4096, mapa(VBAR, r1));
          bulk_to_peer(mapa(sb + R_V1, r2), sb + R_VT + 1024, 4096, mapa(VBAR, r2));
        }
        __syncwarp();
      }
      if (!LAST) {
        ldsm4t(bb[10], rM + 5120);
        ldsm4t(bb[11], rM + 5632);
#pragma unroll
        for (int i = 10; i < 20; i++) {
          if (i + 2 < 20) ldsm4t(bb[i + 2], rM + (i + 2) * 512);
          qmma(2 * i - 20, bb[i][0], bb[i][1]);
          qmma(2 * i - 19, bb[i][2], bb[i][3]);
        }
        stsm2t(rS, pack2(aq[0][0] + aq[1][0], aq[0][1] + aq[1][1]), pack2(aq[0][2] + aq[1][2], aq[0][3] + aq[1][3]));
        bar_arrive(1, 256);
      }
      TR(2);
      float av[4][4] = {};
      uint32_t m0 = 0, m1 = 0;
      auto vmma = [&](auto MAX_) {
#pragma unroll
        for (int n = 0; n < 20; n++) {
          const int i = (n + 10) % 20;
          if (LAST && n < 8) ldsm4t(bb[(n + 10) % 20], rM + ((n + 10) % 20) * 512);
          if (LAST && n == 0) { ldsm4t(bb[18], rM + 18 * 512); ldsm4t(bb[19], rM + 19 * 512); }
          if (n == VLD) {
            if (!LAST) { bar_sync(5, 256); sched_fence(sb); }
#pragma unroll
            for (int q = 0; q < 10; q++) ldsm4t(bb[q], rM + q * 512);
            if (!LAST) sched_fence(sb);
          }
          mma16816(av[(2 * n) & 3], ww[2 * i], bb[i][0], bb[i][1]);
          mma16816(av[(2 * n + 1) & 3], ww[2 * i + 1], bb[i][2], bb[i][3]);
          if (decltype(MAX_)::value) { m0 = hmaxabs2(m0, hmaxabs2(bb[i][0], bb[i][1])); m1 = hmaxabs2(m1, hmaxabs2(bb[i][2], bb[i][3])); }
        }
      };
      auto vout = [&]() {
        const uint32_t vm0 = pack2(((av[0][0] + av[1][0]) + (av[2][0] + av[3][0])) * u, ((av[0][1] + av[1][1]) + (av[2][1] + av[3][1])) * u);
        const uint32_t vm1 = pack2(((av[0][2] + av[1][2]) + (av[2][2] + av[3][2])) * u, ((av[0][3] + av[1][3]) + (av[2][3] + av[3][3])) * u);
        if (!LAST) {
          st_async2(mapa(l8 + R_VM + 1024, r1), vm0, vm1, mapa(OBAR, r1));
          st_async2(mapa(l8 + R_VM, r2), vm0, vm1, mapa(OBAR, r2));
          sts64(l8 + R_VS, vm0, vm1);
          __syncwarp();
          if (rF == sb) mbar_arrive(OBAR);
        }
        stsm2t(rP + R_VT, vm0, vm1);
      };
      if (LAST) { vmma(std::false_type{}); vout(); return; }
      uint32_t wot[NW1][4];
      auto wpre = [&](int i0, int i1) {
#pragma unroll
        for (int i = i0; i < i1; i++) ldsm4t(wot[i], ((i & 1) ? woB : woA) + WOFF(i >> 1));
      };
      if (w != 1) {
        vmma(std::false_type{});
        bar_arrive(7, 128);
        vout();
        bar_arrive(2, 128);
        TR(5);
        wpre(0, NW1A);
      } else {
        vmma(std::true_type{});
        bar_sync(7, 128);
        if (elect()) { mbar_expect(XBAR, 40960); tma_load3(sb + R_XT, &tmX, 0, (s + 1) * SEG, 0, XBAR); }
        __syncwarp();
        vout();
        if (XPF && s + XPF < NSEG && rF - sb < 64 && cta < 80) prefetch_l2(x + (size_t)(s + XPF) * SEG * DM + cta * 256 + (rF - sb) * 4);
        TR(5);
        m0 = hmaxabs2(m0, m1);
        const uint32_t mx = __reduce_max_sync(~0u, max((m0 << 16) & 0x7fffffffu, m0 & 0x7fff0000u));
        const float2 mi = lds64f(sb + R_MI + 8);
        wpre(0, NW1A);
        bar_sync(2, 128);
        if (elect()) {
          fence_async_smem();
          if (s > 0) {
            bulk_wait0();
            asm volatile("red.relaxed.gpu.global.add.u32 [%0], 1;" ::"l"(&g_segcnt[s - 1]) : "memory");
          }
          tma_store2(&tmK, sb + R_KT, D0, s * LK);
          tma_store2(&tmV, sb + R_VT, D0, s * LK);
          bulk_commit();
        }
        __syncwarp();
        float wb = mi.x, xm = mi.y;
        if (s == 0) {
          const uint32_t epoch = *(volatile uint32_t*)&g_epoch + 1;
          uint32_t av_ = 0, ao = 0, xi = 0;
#pragma unroll 1
          for (int j = 0; j < 3; j++) {
            uint2 r;
            int n = 0;
#pragma unroll 1
            while (true) {
              r = ldg_rlx64(&g_rec[j * 32 + ((rF - sb) >> 4)]);
              if (((r.x ^ epoch) & 0xffffu) == 0) break;
              if (++n > SPIN_MAX) { g_err = 6; break; }
            }
            av_ = max(av_, r.y & 0xffff0000u); ao = max(ao, r.y << 16); xi = max(xi, r.x & 0xffff0000u);
          }
          av_ = __reduce_max_sync(~0u, av_); ao = __reduce_max_sync(~0u, ao); xi = __reduce_max_sync(~0u, xi);
          wb = __uint_as_float(av_) * __uint_as_float(ao) * 33.f; xm = __uint_as_float(xi);
          if (rF == sb) sts64f(sb + R_MI + 8, wb, xm);
          __syncwarp();
        }
        const float hm = fmaxf(__uint_as_float(mx) * u, xm);
        const uint32_t eb = min(max(__float_as_uint(hm * wb) >> 23, 40u), 200u);
        if (rF == sb) sts64(sb + R_MI + 48, (280u - eb) << 23, (eb - 29u) << 23);
      }
      if (NW1A < NW1) {
        bar_sync(4, 256);
        wpre(NW1A, NW1);
      }
      TR(6);
      oproj(std::true_type{}, std::integral_constant<int, NW1>{}, wot, rF, woA, woB, 0.f, 0.f, false);
    } else {
      {
        uint32_t bb[20][4];
        float ak[4][4] = {};
        ldsm4t(bb[0], rM);
        ldsm4t(bb[10], rM + 5120);
#pragma unroll
        for (int i = 0; i < 10; i++) {
          if (i + 1 < 10) { ldsm4t(bb[i + 1], rM + (i + 1) * 512); ldsm4t(bb[i + 11], rM + (i + 11) * 512); }
          mma16816(ak[0], ww[2 * i], bb[i][0], bb[i][1]);
          if (!LAST) qmma(2 * i, bb[i][0], bb[i][1]);
          mma16816(ak[1], ww[2 * i + 1], bb[i][2], bb[i][3]);
          if (!LAST) qmma(2 * i + 1, bb[i][2], bb[i][3]);
          mma16816(ak[2], ww[2 * i + 20], bb[i + 10][0], bb[i + 10][1]);
          mma16816(ak[3], ww[2 * i + 21], bb[i + 10][2], bb[i + 10][3]);
        }
#pragma unroll
        for (int q = 0; q < 4; q++) { ak[0][q] += ak[2][q]; ak[1][q] += ak[3][q]; }
        stsm4t(rS, pack2(aq[0][0] + aq[1][0], aq[0][1] + aq[1][1]), pack2(aq[0][2] + aq[1][2], aq[0][3] + aq[1][3]),
               pack2((ak[0][0] + ak[1][0]) * u, (ak[0][1] + ak[1][1]) * u), pack2((ak[0][2] + ak[1][2]) * u, (ak[0][3] + ak[1][3]) * u));
      }
      if (LAST) return;
      bar_sync(1, 256);
      bar_arrive(5, 256);
      TR(2);
      if (w != 3) {
        uint32_t qa[4][4], kk[4][4];
        float x[4][4] = {};
#pragma unroll
        for (int i = 0; i < 4; i++) { ldsm4(qa[i], (rP ^ (i << 5)) + R_QB); ldsm4(kk[i], ((rP ^ (i << 5)) + w * 2048) + R_KT); }
        const uint32_t dst = rF + R_SX + rank * 1536 + w * 512;
        const uint32_t e1 = mapa(dst, r1), e2 = mapa(dst, r2), s1 = mapa(SBAR, r1), s2 = mapa(SBAR, r2);
#pragma unroll
        for (int i = 0; i < 4; i++) { mma16816(x[i & 1], qa[i], kk[i][0], kk[i][1]); mma16816(x[2 + (i & 1)], qa[i], kk[i][2], kk[i][3]); }
        const uint32_t u0 = __float_as_uint((x[0][0] + x[0][2]) + (x[1][0] + x[1][2])), u1 = __float_as_uint((x[0][1] + x[0][3]) + (x[1][1] + x[1][3]));
        const uint32_t u2 = __float_as_uint((x[2][0] + x[2][2]) + (x[3][0] + x[3][2])), u3 = __float_as_uint((x[2][1] + x[2][3]) + (x[3][1] + x[3][3]));
        st_async4(e1, u0, u1, u2, u3, s1);
        st_async4(e2, u0, u1, u2, u3, s2);
        sts128(dst, u0, u1, u2, u3);
        __syncwarp();
        if (rF == sb) mbar_arrive(SBAR);
      }
      TR(4);
      mbar_wait(VBAR, s & 1);
      uint32_t wot[12][4], va[3][8];
      ldsm4t(va[0], rP + R_VT + 1024); ldsm4t(va[0] + 4, rP + R_VT + 3072);
#pragma unroll
      for (int q = 0; q < 4; q++) ldsm4t(va[1 + (q >> 1)] + (q & 1) * 4, rP + R_V1 + q * 2048);
      auto wpre = [&](int i0, int i1) {
        if (two) {
#pragma unroll
          for (int i = i0; i < i1; i++) ldsm4t(wot[i], ((i & 1) ? woB : woA) + WOFF(i >> 1));
        } else {
#pragma unroll
          for (int i = i0; i < i1; i++) ldsm4t(wot[i], woA + WOFF(i));
        }
      };
      wpre(0, NO_EARLY);
      const uint32_t dst = rF + (w >> 1) * 512 + (w & 1) * 8;
      const float scl = u * (0.07216878364870322f * 1.4426950408889634f);
      mbar_wait(SBAR, s & 1);
      TR(6);
      float sc[10];
      {
        const float4 a0 = lds128f(rF + R_SX), b0 = lds128f(rF + R_SX + 1536), c0 = lds128f(rF + R_SX + 3072);
        const float4 a1 = lds128f(rF + R_SX + 512), b1 = lds128f(rF + R_SX + 2048), c1 = lds128f(rF + R_SX + 3584);
        const float2 a2 = lds64f(rF + R_SX + 1024), b2 = lds64f(rF + R_SX + 2560), c2 = lds64f(rF + R_SX + 4096);
        sc[8] = a0.x + b0.x + c0.x; sc[9] = a0.y + b0.y + c0.y; sc[0] = a0.z + b0.z + c0.z; sc[1] = a0.w + b0.w + c0.w;
        sc[2] = a1.x + b1.x + c1.x; sc[3] = a1.y + b1.y + c1.y; sc[4] = a1.z + b1.z + c1.z; sc[5] = a1.w + b1.w + c1.w;
        sc[6] = a2.x + b2.x + c2.x; sc[7] = a2.y + b2.y + c2.y;
      }
      float mx = fmaxf(fmaxf(fmaxf(sc[0], sc[1]), fmaxf(sc[2], sc[3])), fmaxf(fmaxf(sc[4], sc[5]), fmaxf(sc[6], sc[7])));
      mx = fmaxf(mx, fmaxf(sc[8], sc[9]));
      mx = fmaxf(mx, __shfl_xor_sync(~0u, mx, 1));
      const bool vok = mbar_test(OBAR, s & 1);
      mx = fmaxf(mx, __shfl_xor_sync(~0u, mx, 2));
      if (NW1A < NW1) bar_arrive(4, 256);
      const float mo = mx * scl;
      uint32_t pb[5];
#pragma unroll
      for (int j = 0; j < 5; j++) pb[j] = pack2(ex2(fmaf(sc[2 * j], scl, -mo)), ex2(fmaf(sc[2 * j + 1], scl, -mo)));
      if (!vok) mbar_wait(OBAR, s & 1);
      const uint2 m0 = lds64(l8 + R_VS), m1 = lds64(l8 + R_VM), m2 = lds64(l8 + R_VM + 1024);
      const uint32_t ones[4] = {ONES, ONES, ONES, ONES};
      float o[3][4], o2[3][4], sm[4] = {0.f, 0.f, 0.f, 0.f}, sn[4] = {0.f, 0.f, 0.f, 0.f}, so[4] = {0.f, 0.f, 0.f, 0.f};
#pragma unroll
      for (int b = 0; b < 3; b++) {
        o[b][0] = o[b][1] = o[b][2] = o[b][3] = o2[b][0] = o2[b][1] = o2[b][2] = o2[b][3] = 0.f;
        mma16816(o[b], va[b], pb[0], pb[1]);
      }
#pragma unroll
      for (int b = 0; b < 3; b++) mma16816(o2[b], va[b] + 4, pb[2], pb[3]);
      mma1688(o[0], m0.x, m0.y, pb[4]);
      mma1688(o[1], m1.x, m1.y, pb[4]);
      mma1688(o[2], m2.x, m2.y, pb[4]);
      mma16816(sm, ones, pb[0], pb[1]);
      mma16816(sn, ones, pb[2], pb[3]);
      mma1688(so, ONES, ONES, pb[4]);
      wpre(NO_EARLY, NO_MID);
#pragma unroll
      for (int b = 0; b < 3; b++)
        sts64(dst + (b == 0 ? R_QB : (b == 1 ? R_QA : R_O2)), movmat(pack2(o[b][0] + o2[b][0], o[b][1] + o2[b][1])),
              movmat(pack2(o[b][2] + o2[b][2], o[b][3] + o2[b][3])));
      sm[0] += sn[0] + so[0]; sm[1] += sn[1] + so[1];
      if (rF - sb < 64) sts64f(sb + R_MI + 16 + ((rF - sb) >> 1), sm[0], sm[1]);
      wpre(NO_MID, 12);
      TR(7);
      if (two) oproj(std::true_type{}, std::integral_constant<int, 12>{}, wot, rF, woA, woB, sm[0], sm[1], true);
      else oproj(std::false_type{}, std::integral_constant<int, 12>{}, wot, rF, woA, woB, sm[0], sm[1], true);
    }
  };

  GTR(5); GTR(6);
  if (g == 0) {
    window(std::integral_constant<int, 0>{}, std::true_type{});
    GTR(7);
#pragma unroll 1
    for (s = 0; s < NSEG - 1; s++) {
      step(std::integral_constant<int, 0>{}, std::false_type{});
      window(std::integral_constant<int, 0>{}, std::false_type{});
    }
    step(std::integral_constant<int, 0>{}, std::true_type{});
  } else {
    window(std::integral_constant<int, 1>{}, std::true_type{});
#pragma unroll 1
    for (s = 0; s < NSEG - 1; s++) {
      step(std::integral_constant<int, 1>{}, std::false_type{});
      window(std::integral_constant<int, 1>{}, std::false_type{});
    }
    step(std::integral_constant<int, 1>{}, std::true_type{});
  }
  __syncthreads();
  if (tid == 160) {
    fence_async_smem();
    tma_store2(&tmK, sb + R_KT, D0, (NSEG - 1) * LK);
    tma_store2(&tmV, sb + R_VT, D0, (NSEG - 1) * LK);
    bulk_commit();
    bulk_wait0();
    asm volatile("red.relaxed.gpu.global.add.u32 [%0], 1;" ::"l"(&g_segcnt[NSEG - 2]) : "memory");
    asm volatile("red.relaxed.gpu.global.add.u32 [%0], 1;" ::"l"(&g_segcnt[NSEG - 1]) : "memory");
  }
  GTR(8);
  cluster_sync();
}

enum { IT_GATE = 0, IT_QKV = 1, IT_XATT = 2, IT_OUT = 3, IT_BATT = 4, IT_CVT = 5, IT_INIT = 6, IT_END = 7 };
constexpr int C_GATE = 0, C_QKV = 16, C_OB = 32, C_ACC = 48, C_O = 80;
#define T8 10
#define T16 14
#define T32 16
#define XEARLY 11
constexpr int k_nsplit(int t) { return t >= T32 ? 32 : (t >= T16 ? 16 : (t >= T8 ? 8 : 4)); }
constexpr uint32_t mk_item(int ty, int t, int a, int b = 0, int c = 0) { return ty | (t << 3) | (a << 8) | (b << 16) | (c << 24); }
constexpr int part_base(int t) { return t ? part_base(t - 1) + k_nsplit(t - 1) + 1 : 0; }
struct ItemTab { uint32_t v[1280]; uint32_t pb[17]; int n; };
constexpr ItemTab make_items() {
  ItemTab T{};
  int n = 0;
  for (int t = 0; t < 16; t++) T.v[n++] = mk_item(IT_GATE, t, 0);
  for (int t = 0; t < 16; t++) for (int a = 0; a < 5; a++) T.v[n++] = mk_item(IT_QKV, t, a);
  for (int t = 0; t < 32; t++) for (int a = 0; a < 4; a++) T.v[n++] = mk_item(IT_BATT, t, a);
  for (int t = 0; t < 16; t++) for (int a = 0; a < 2; a++) T.v[n++] = mk_item(IT_INIT, t, a);
  auto xatt = [&](int t) { for (int a = 0; a < 16; a++) T.v[n++] = mk_item(IT_XATT, t, a); };
  auto outp = [&](int u) {
    const int ns = k_nsplit(u);
    for (int q = 0; q < ns; q++) for (int a = 0; a < 2; a++) T.v[n++] = mk_item(IT_OUT, u, a, q * 32 / ns, (q + 1) * 32 / ns);
  };
  auto cvt = [&](int v) {
    const int r = k_nsplit(v) == 4 ? 4 : (k_nsplit(v) == 8 ? 2 : 1);
    for (int q = 0; q < 16; q += r) for (int a = 0; a < 2; a++) T.v[n++] = mk_item(IT_CVT, v, a, q, r);
  };
  for (int t = 0; t <= 16; t++) T.pb[t] = part_base(t);
  for (int t = 0; t < XEARLY; t++) {
    xatt(t);
    if (t >= 1) outp(t - 1);
    if (t >= 4) cvt(t - 4);
  }
  for (int t = XEARLY; t < 16; t++) xatt(t);
  for (int t = XEARLY - 1; t < 16; t++) outp(t);
  for (int t = XEARLY - 4; t < 16; t++) cvt(t);
  T.n = n;
  return T;
}
constexpr ItemTab k_items_host = make_items();
constexpr int NITEMS = k_items_host.n;
__constant__ ItemTab c_items = make_items();
__device__ __align__(1024) bf16 g_part[part_base(16) * 128 * DM];

constexpr int AUX_GRID = 132, NST = 7, STG = 32768;
constexpr int A_FULL = NST * STG, A_EMPTY = A_FULL + 64, A_ITEM = A_EMPTY + 64, A_QBAR = A_ITEM + 32, A_QENT = A_QBAR + 128, A_MISC = A_QENT + 256,
              A_SMEM = A_MISC + 64;
static_assert(A_SMEM <= 232448, "smem");
enum { OP_END = 0, OP_O = 1, OP_QKV = 2, OP_OB = 3, OP_PART = 4 };

struct AuxMaps { CUtensorMap xA, wq, wqkv, wo, wob, k, v, oA, oS, obA, obS, qkvS, qkvQ, qkvK, part; };

__device__ __forceinline__ void mbar_wait_long(uint32_t b, uint32_t par) {
  int n = 0;
#pragma unroll 1
  while (!mbar_try(b, par)) { if (++n > (SPIN_MAX << 4)) { g_err = 8; break; } }
}
__device__ __forceinline__ uint64_t mk_desc(uint32_t addr, uint32_t lbo, uint32_t sbo, uint32_t mode) {
  return (uint64_t)((addr & 0x3FFFF) >> 4) | ((uint64_t)(lbo >> 4) << 16) | ((uint64_t)(sbo >> 4) << 32) | ((uint64_t)mode << 62);
}

__global__ void __launch_bounds__(384, 1)
aux_kernel(const __grid_constant__ AuxMaps tm, const bf16* __restrict__ x, const bf16* __restrict__ gate_w, bf16* __restrict__ out) {
  extern __shared__ __align__(1024) unsigned char smem[];
  const uint32_t sb = smem_u32(smem);
  const int tid = threadIdx.x, lane = tid & 31, wid = __shfl_sync(~0u, tid >> 5, 0);
  if (tid == 0) {
    for (int i = 0; i < NST; i++) { mbar_init(sb + A_FULL + i * 8, 1); mbar_init(sb + A_EMPTY + i * 8, 8); }
    for (int i = 0; i < 16; i++) mbar_init(sb + A_QBAR + i * 8, 4);
    asm volatile("fence.mbarrier_init.release.cluster;" ::: "memory");
    sts32(sb + A_MISC, *(volatile uint32_t*)&g_epoch + 1);
  }
  __syncthreads();
  const uint32_t epoch = lds32(sb + A_MISC);
  uint32_t st = 0, ph = 0;
  auto advance = [&]() { if (++st == NST) { st = 0; ph ^= 1; } };

  if (wid >= 8) {
    asm volatile("setmaxnreg.dec.sync.aligned.u32 40;");
    if (wid == 8 && lane == 0) {
      const uint32_t qbase = (epoch - 1) * (uint32_t)(NITEMS + AUX_GRID);
      auto cnt = [&](int c, uint32_t per) -> bool { return (int)(ldg_rlx32(&g_cnt[c * 8]) - epoch * per) >= 0; };
      auto ready = [&](uint32_t item) -> int {
        const int ty = item & 7, t = (item >> 3) & 31, a = (item >> 8) & 255, b = (item >> 17) & 127, n = (((item >> 24) + 1) >> 1) - b;
        int r;
        if (ty == IT_OUT) {
          const int c = C_O + t * 16 + b;
          const bool r0 = cnt(c, 2), r1 = cnt(c + (n > 1), 2), r2 = cnt(c + (n > 2) * 2, 2), r3 = cnt(c + (n > 3) * 3, 2);
          r = r0 ? (r1 ? (r2 ? (r3 ? 4 : 3) : 2) : 1) : 0;
        } else if (ty == IT_XATT) {
          const uint4 v = ldg_rlx128(&g_segcnt[4 * t]);
          const uint32_t e = epoch * 96;
          r = cnt(C_GATE + t, 1) & ((int)(v.x - e) >= 0) & ((int)(v.y - e) >= 0) & ((int)(v.z - e) >= 0) & ((int)(v.w - e) >= 0);
        } else if (ty == IT_BATT) {
          r = cnt(C_GATE + (t >> 1), 1) & cnt(C_QKV + (t >> 1), 10) & cnt(C_QKV + (max(t - 1, 0) >> 1), 10);
        } else {
          r = cnt(ty == IT_INIT ? C_OB + t : C_ACC + 2 * t + (a & 1), ty == IT_INIT ? 8 : 66);
        }
        asm volatile("fence.acquire.gpu; fence.proxy.async.global;" ::: "memory");
        return r;
      };
      uint32_t item = IT_GATE;
      int trail = 0;
      auto slot = [&](uint32_t bytes) -> uint32_t {
        mbar_wait_long(sb + A_EMPTY + st * 8, ph ^ 1);
        sts32(sb + A_ITEM + st * 4, item);
        if (bytes) mbar_expect(sb + A_FULL + st * 8, bytes); else mbar_arrive(sb + A_FULL + st * 8);
        return sb + st * STG;
      };
#pragma unroll 1
      while (true) {
        const uint32_t nidx = atomicAdd(&g_queue, 1u) - qbase;
        const uint32_t nitem = nidx < (uint32_t)NITEMS ? c_items.v[nidx] : (uint32_t)IT_END;
        int rdy = (0x78 >> (nitem & 7)) & 1 ? ready(nitem) : 0;
#pragma unroll 1
        for (; trail; trail--) { slot(0); advance(); }
        item = nitem;
        int k = (item & 7) == IT_OUT ? ((item >> 16) & 255) * 6 : 0;
        const int k1 = (item & 7) == IT_OUT ? (item >> 24) * 6 : (0x01140103001c1401ull >> ((item & 7) * 8)) & 255;
#pragma unroll 1
        for (; k < k1; k++) {
          item = pin(item);
          const int ty = item & 7, t = (item >> 3) & 31, a = (item >> 8) & 255;
          const bool out_ = ty == IT_OUT, gemm1 = ty == IT_QKV || ty == IT_XATT;
          const int dep = out_ ? k / 12 - ((item >> 17) & 127) : (ty == IT_XATT ? (k >= 20) - 1 : ((0x70 >> ty) & 1) - 1);
          if (rdy <= dep || (k == 12 && ty == IT_XATT)) {
            int n = 0;
#pragma unroll 1
            while ((rdy = ready(pin(item))) <= dep) {
              if (++n > SPIN_MAX) { g_err = 7; break; }
              __nanosleep(20);
            }
          }
          const uint32_t fb = sb + A_FULL + st * 8;
          if (out_ || ty == IT_INIT) {
            const uint32_t d = slot(28672);
            tma_load2(d, out_ ? &tm.oA : &tm.obA, k * 32, t * 128, fb);
            tma_load3(d + 8192, out_ ? &tm.wo : &tm.wob, 0, k * 32, a * 5, fb);
          } else if (gemm1 && k < 20) {
            const uint32_t d = slot(32768);
            tma_load2(d, &tm.xA, k * 32, t * 128, fb);
            tma_load3(d + 8192, ty == IT_QKV ? &tm.wqkv : &tm.wq, 0, k * 32, a * 6, fb);
          } else if (gemm1) {
            const uint32_t d = slot(30720);
            tma_load3(d, k < 24 ? &tm.k : &tm.v, 0, (4 * t + (k & 2)) * LK, (2 * a + (k & 1)) * 3, fb);
          } else if (ty == IT_BATT) {
            const uint32_t d = slot(k ? 25600 : 20480);
            tma_load2(d, k ? &tm.qkvK : &tm.qkvQ, k * 640 + a * 160, t * 64 - (k ? 16 : 0), fb);
          } else {
            slot(0);
            mbar_wait_long(sb + A_EMPTY + st * 8, ph);
          }
          advance();
        }
        if ((item & 7) == IT_END) {
          if (nidx == (uint32_t)(NITEMS + AUX_GRID - 1)) g_epoch = epoch;
          break;
        }
        trail = (0x4a >> (item & 7)) & 1 ? 4 : 0;
      }
      asm volatile("griddepcontrol.wait;" ::: "memory");
    } else if ((wid == 9 || wid == 10) && lane == 0) {
      const uint32_t qb = sb + A_QBAR + (wid - 9) * 64, qe = sb + A_QENT + (wid - 9) * 128;
      for (uint32_t e = 0;; e++) {
        mbar_wait_long(qb + (e & 7) * 8, (e >> 3) & 1);
        const uint4 en = lds128(qe + (e & 7) * 16);
        const int op = en.x & 15, sg = (en.x >> 4) & 15, rel = (en.x >> 8) & 15, nb = (en.x >> 12) & 15;
        if (op == OP_END) break;
        const uint32_t src = sb + sg * STG;
        if (op == OP_O) tma_store3(&tm.oS, src, 0, en.y, en.z);
        else if (op == OP_QKV) tma_store3(&tm.qkvS, src, 0, en.y, en.z);
        else if (op == OP_OB) tma_store2(&tm.obS, src, en.z, en.y);
        else { for (int i = 0; i < nb; i++) tma_store3(&tm.part, src + i * 8192, 0, en.y, en.z + i); }
        bulk_commit();
        bulk_wait_read0();
        asm volatile("mbarrier.arrive.shared::cta.b64 _, [%0], %1;" ::"r"(sb + A_EMPTY + sg * 8), "r"(rel) : "memory");
        if (en.w) {
          bulk_wait0();
          asm volatile("red.relaxed.gpu.global.add.u32 [%0], %1;" ::"l"(&g_cnt[((en.w & 0xFFFF) - 1) * 8]), "r"((en.w >> 16) + 1) : "memory");
        }
      }
      bulk_wait0();
    }
  } else {
    asm volatile("setmaxnreg.inc.sync.aligned.u32 232;");
    const int g = wid >> 2, w = wid & 3;
    uint32_t qn = 0;
    auto wait_full = [&]() { mbar_wait_long(sb + A_FULL + st * 8, ph); };
    auto release = [&](uint32_t s_) { if (lane == 0) mbar_arrive(sb + A_EMPTY + s_ * 8); };
    auto take_pair = [&]() -> uint32_t {
      wait_full();
      const uint32_t s0 = st; advance();
      wait_full();
      const uint32_t s1 = st; advance();
      release(g ? s0 : s1);
      return g ? s1 : s0;
    };
    auto push = [&](uint32_t w0, uint32_t w1, uint32_t w2, uint32_t w3) {
      fence_async_smem();
      if (w == 0 && lane == 0) sts128(sb + A_QENT + g * 128 + (qn & 7) * 16, w0, w1, w2, w3);
      __syncwarp();
      if (lane == 0) mbar_arrive(sb + A_QBAR + g * 64 + (qn & 7) * 8);
      qn++;
    };
    const uint32_t stm = (16 * w + (lane & 7) + (lane & 8)) * 128, stx = lane & 7, sth = lane >> 4;
    auto stage_bf16 = [&](uint32_t dst, const float* d, float s0, float s1, int nks = 12) {
#pragma unroll
      for (int ks = 0; ks < nks; ks++)
        stsm4(dst + (ks >> 2) * 8192 + stm + (((2 * (ks & 3) + sth) ^ stx) << 4), pack2(d[8 * ks] * s0, d[8 * ks + 1] * s0), pack2(d[8 * ks + 2] * s1, d[8 * ks + 3] * s1),
              pack2(d[8 * ks + 4] * s0, d[8 * ks + 5] * s0), pack2(d[8 * ks + 6] * s1, d[8 * ks + 7] * s1));
    };
#pragma unroll 1
    while (true) {
      wait_full();
      const uint32_t item = lds32(sb + A_ITEM + st * 4);
      const int ty = item & 7, t = (item >> 3) & 31, a = (item >> 8) & 255;
      if (ty == IT_QKV || ty == IT_XATT) {
        float acc[192] = {};
        uint32_t prev = 0;
#pragma unroll 1
        for (int k = 0; k < 20; k++) {
          if (k) wait_full();
          const uint32_t s_ = sb + st * STG;
          const uint64_t da = mk_desc(s_, 16, 512, 2), db = mk_desc(s_ + 8192 + g * 12288, 4096, 1024, 1);
          wg_fence();
          wgmma_ss192t(acc, da, db, k);
          wgmma_ss192t(acc + 96, da + 256, db, k);
          wgmma_ss192t(acc, da + 2, db + 128, 1);
          wgmma_ss192t(acc + 96, da + 258, db + 128, 1);
          wg_commit();
          if (k) { wg_wait1(); release(prev); }
          prev = st; advance();
        }
        wg_wait0();
        fence_regs<192>(acc);
        release(prev);
        if (ty == IT_QKV) {
#pragma unroll
          for (int q = 0; q < 2; q++) {
            const uint32_t m = take_pair();
            stage_bf16(sb + m * STG, acc + q * 96, 1.f, 1.f);
            push(OP_QKV | (m << 4) | (4 << 8), t * 128 + q * 64, a * 6 + g * 3, q ? C_QKV + t + 1 : 0);
          }
        } else {
          uint32_t qf[24][4];
#pragma unroll
          for (int ks = 23; ks >= 0; ks--)
#pragma unroll
            for (int j = 0; j < 4; j++)
              asm volatile("cvt.rn.bf16x2.f32 %0, %1, %2;" : "=r"(qf[ks][j]) : "f"(acc[8 * ks + 2 * j + 1]), "f"(acc[8 * ks + 2 * j]));
          float sc[2][40] = {};
          uint32_t kst[2];
#pragma unroll
          for (int q = 0; q < 2; q++) {
            kst[q] = take_pair();
            const uint64_t db = mk_desc(sb + kst[q] * STG, 16, 1024, 1);
            wg_fence();
#pragma unroll
            for (int ks = 0; ks < 12; ks++) wgmma_rs80(sc[q], qf[q * 12 + ks], db + (((ks >> 2) * 10240 + (ks & 3) * 32) >> 4), ks);
            wg_commit();
          }
          const int tt = 16 * (w & 1) + (lane >> 2) - 2 * (lane & 3);
          const float* gp = g_gate + t * 128 + 16 * w + (lane >> 2);
          const float gt[4] = {__ldcg(gp), __ldcg(gp + 8), __ldcg(gp + 64), __ldcg(gp + 72)};
          uint32_t pf[2][5][4];
          float rs[2][2];
          auto softmax = [&](const float* s_, uint32_t (&p)[5][4], float* r) {
            constexpr float SCL = 0.07216878364870322f * 1.4426950408889634f;
            float v[20];
#pragma unroll
            for (int i = 0; i < 20; i++) {
              v[i] = w >= 2 ? s_[20 + i] : s_[i];
              if (i >= 4 && 8 * ((i >> 2) - 1) + (i & 1) > tt + ((i & 2) ? 8 : 0)) v[i] = -INFINITY;
            }
            uint32_t pt[5][2];
#pragma unroll
            for (int h = 0; h < 2; h++) {
              float mx = fmaxf(v[2 * h], v[2 * h + 1]);
#pragma unroll
              for (int j = 1; j < 5; j++) mx = fmaxf(mx, fmaxf(v[4 * j + 2 * h], v[4 * j + 2 * h + 1]));
              mx = fmaxf(mx, __shfl_xor_sync(~0u, mx, 1));
              mx = fmaxf(mx, __shfl_xor_sync(~0u, mx, 2));
              const float mo = mx * SCL;
              float sum = 0.f;
#pragma unroll
              for (int j = 0; j < 5; j++) {
                const float e0 = ex2(fmaf(v[4 * j + 2 * h], SCL, -mo)), e1 = ex2(fmaf(v[4 * j + 2 * h + 1], SCL, -mo));
                pt[j][h] = pack2(e0, e1);
                sum += bf_lo(pt[j][h]) + bf_hi(pt[j][h]);
              }
              sum += __shfl_xor_sync(~0u, sum, 1);
              sum += __shfl_xor_sync(~0u, sum, 2);
              r[h] = rcp(sum);
            }
#pragma unroll
            for (int J = 0; J < 10; J++)
#pragma unroll
              for (int h = 0; h < 2; h++) p[J >> 1][(J & 1) * 2 + h] = (J >= 5) == (w >= 2) ? pt[J % 5][h] : 0u;
          };
          wg_wait1();
          fence_regs<40>(sc[0]);
          release(kst[0]);
          softmax(sc[0], pf[0], rs[0]);
#pragma unroll
          for (int q = 0; q < 2; q++) {
            const uint32_t m = take_pair();
            const uint64_t db = mk_desc(sb + m * STG, 10240, 1024, 1);
            float o[96] = {};
            wg_fence();
#pragma unroll
            for (int ks = 0; ks < 5; ks++) wgmma_rs192t(o, pf[q][ks], db + ks * 128, ks);
            wg_commit();
            if (q == 0) {
              wg_wait1();
              fence_regs<40>(sc[1]);
              release(kst[1]);
              softmax(sc[1], pf[1], rs[1]);
            }
            wg_wait0();
            fence_regs<96>(o);
            bar_sync(1 + g, 128);
            stage_bf16(sb + m * STG, o, rs[q][0] * gt[2 * q], rs[q][1] * gt[2 * q + 1]);
            push(OP_O | (m << 4) | (4 << 8), t * 128 + q * 64, a * 6 + g * 3, q ? C_O + t * 16 + a + 1 : 0);
          }
        }
      } else if (ty == IT_OUT || ty == IT_INIT) {
        float acc[160] = {};
        const int hb = (item >> 16) & 255, nh = (item >> 24) - hb, nk = ty == IT_OUT ? nh * 6 : 20, jh = a & 1;
        const uint32_t ln = pin(lane), ao = (g * 64 + 16 * w + (ln & 15)) * 64 + (((ln >> 4) ^ ((ln >> 1) & 3)) << 4);
#pragma unroll 1
        for (int k = 0; k < nk; k += 2) {
          uint32_t af[4][4], sg[2];
#pragma unroll
          for (int e = 0; e < 2; e++) {
            if (k + e) wait_full();
            sg[e] = st;
            ldsm4(af[2 * e], sb + st * STG + ao);
            ldsm4(af[2 * e + 1], sb + st * STG + (ao ^ 32));
            advance();
          }
          wg_fence();
#pragma unroll
          for (int e = 0; e < 4; e++) {
            const uint64_t db = mk_desc(sb + sg[e >> 1] * STG + 8192 + (e & 1) * 2048, 4096, 1024, 1);
            wgmma_rs192t(acc, af[e], db, 1);
            wgmma_rs128t(acc + 96, af[e], db + 768, 1);
          }
          wg_commit();
          wg_wait0();
          release(sg[0]); release(sg[1]);
        }
        fence_regs<160>(acc);
        const uint32_t row = (ty == IT_OUT ? c_items.pb[t] + hb / nh : c_items.pb[t + 1] - 1) * 128 + g * 64;
#pragma unroll
        for (int q = 0; q < 2; q++) {
          const uint32_t m = take_pair();
          stage_bf16(sb + m * STG, acc + q * 96, 1.f, 1.f, q ? 8 : 12);
          push(OP_PART | (m << 4) | (4 << 8) | ((3 - q) << 12), row, jh * 5 + q * 3, q ? (C_ACC + 2 * t + jh + 1) | ((ty == IT_OUT ? nh - 1 : 0) << 16) : 0);
        }
      } else if (ty == IT_BATT) {
        const uint32_t sq = st; advance();
        wait_full();
        const uint32_t sk = st; advance();
        wait_full();
        const uint32_t sv = st; advance();
        const int h = tid & 7;
#pragma unroll 1
        for (int p = 0; p < 2; p++) {
          const int tok = (tid >> 3) + 32 * p, pos = t * 64 + tok;
          const uint32_t qa = sb + sq * STG + tok * 320 + h * 40, ka = sb + sk * STG + (tok + 16) * 320 + h * 40, va = sb + sv * STG + (tok + 16) * 320 + h * 40;
          const float gt = __ldcg(g_gate + 2048 + pos);
          float q[20], l[8];
#pragma unroll
          for (int i = 0; i < 5; i++) { const uint2 u = lds64(qa + i * 8); q[4 * i] = bf_lo(u.x); q[4 * i + 1] = bf_hi(u.x); q[4 * i + 2] = bf_lo(u.y); q[4 * i + 3] = bf_hi(u.y); }
          float mx = -INFINITY;
#pragma unroll
          for (int j = 0; j < 8; j++) {
            float s0 = 0.f, s1 = 0.f;
#pragma unroll
            for (int i = 0; i < 5; i++) {
              const uint2 u = lds64(ka - j * 640 + i * 8);
              s0 = fmaf(q[4 * i], bf_lo(u.x), s0); s1 = fmaf(q[4 * i + 1], bf_hi(u.x), s1);
              s0 = fmaf(q[4 * i + 2], bf_lo(u.y), s0); s1 = fmaf(q[4 * i + 3], bf_hi(u.y), s1);
            }
            l[j] = pos - 2 * j >= 0 ? s0 + s1 : -INFINITY;
            mx = fmaxf(mx, l[j]);
          }
          constexpr float SCL = 0.22360679774997896f * 1.4426950408889634f;
          const float mo = mx * SCL;
          float sum = 0.f;
#pragma unroll
          for (int j = 0; j < 8; j++) { l[j] = ex2(fmaf(l[j], SCL, -mo)); sum += l[j]; }
          const float r = gt * rcp(sum);
#pragma unroll
          for (int i = 0; i < 20; i++) q[i] = 0.f;
#pragma unroll
          for (int j = 0; j < 8; j++) {
#pragma unroll
            for (int i = 0; i < 5; i++) {
              const uint2 u = lds64(va - j * 640 + i * 8);
              q[4 * i] = fmaf(l[j], bf_lo(u.x), q[4 * i]); q[4 * i + 1] = fmaf(l[j], bf_hi(u.x), q[4 * i + 1]);
              q[4 * i + 2] = fmaf(l[j], bf_lo(u.y), q[4 * i + 2]); q[4 * i + 3] = fmaf(l[j], bf_hi(u.y), q[4 * i + 3]);
            }
          }
#pragma unroll
          for (int i = 0; i < 5; i++) sts64(qa + i * 8, pack2(q[4 * i] * r, q[4 * i + 1] * r), pack2(q[4 * i + 2] * r, q[4 * i + 3] * r));
        }
        __syncwarp();
        release(sk); release(sv);
        fence_async_smem();
        bar_sync(3, 256);
        if (g == 0) push(OP_OB | (sq << 4) | (8 << 8), t * 64, a * 160, C_OB + (t >> 1) + 1);
      } else if (ty == IT_GATE) {
        release(st); advance();
        uint4 gw[3];
#pragma unroll
        for (int i = 0; i < 3; i++) gw[i] = (i < 2 || lane < 16) ? __ldg((const uint4*)gate_w + lane + 32 * i) : make_uint4(0, 0, 0, 0);
#pragma unroll 4
        for (int r = 0; r < 16; r++) {
          const int row = t * 128 + wid * 16 + r;
          float s_ = 0.f;
#pragma unroll
          for (int i = 0; i < 3; i++) {
            const uint4 v = (i < 2 || lane < 16) ? __ldg((const uint4*)(x + (size_t)row * DM) + lane + 32 * i) : make_uint4(0, 0, 0, 0);
            const uint32_t p0 = hmul2(v.x, gw[i].x), p1 = hmul2(v.y, gw[i].y), p2 = hmul2(v.z, gw[i].z), p3 = hmul2(v.w, gw[i].w);
            s_ += ((bf_lo(p0) + bf_hi(p0)) + (bf_lo(p1) + bf_hi(p1))) + ((bf_lo(p2) + bf_hi(p2)) + (bf_lo(p3) + bf_hi(p3)));
          }
#pragma unroll
          for (int o = 16; o; o >>= 1) s_ += __shfl_xor_sync(~0u, s_, o);
          const float z = bf_lo(pack2(s_, 0.f));
          const float gv = bf_lo(pack2(1.f / (1.f + __expf(-z)), 0.f));
          if (lane == 0) { g_gate[row] = gv; g_gate[2048 + row] = bf_lo(pack2(1.f - gv, 0.f)); }
        }
        __threadfence();
        bar_sync(3, 256);
        if (tid == 0) asm volatile("red.release.gpu.global.add.u32 [%0], 1;" ::"l"(&g_cnt[(C_GATE + t) * 8]) : "memory");
      } else if (ty == IT_CVT) {
        release(st); advance();
        const int r0 = ((item >> 16) & 255) * 8, lim = (item >> 24) * 640, np = c_items.pb[t + 1] - c_items.pb[t];
        const int td = pin(tid);
        auto add_parts = [&](auto NI_, auto U0_) {
          constexpr int NI = decltype(NI_)::value, U0 = decltype(U0_)::value;
          uint32_t off[NI];
          float sum[NI][4];
          const char* src = (const char*)(g_part + ((size_t)c_items.pb[t] * 128 + r0) * DM + a * 320);
#pragma unroll
          for (int i = 0; i < NI; i++) { const int e = min(td + i * 256, lim - 1); off[i] = (e / 80) * (DM * 2) + (e % 80) * 8; }
          auto round = [&](auto U_, bool first) {
            constexpr int U = decltype(U_)::value;
            uint2 v[NI][U];
#pragma unroll
            for (int i = 0; i < NI; i++) {
              const char* q0 = src + off[i];
#pragma unroll
              for (int q = 0; q < U; q++) v[i][q] = __ldcg((const uint2*)(q0 + q * (128 * DM * 2)));
            }
            src += U * (128 * DM * 2);
#pragma unroll
            for (int i = 0; i < NI; i++) {
              if (first) sum[i][0] = sum[i][1] = sum[i][2] = sum[i][3] = 0.f;
#pragma unroll
              for (int q = 0; q < U; q++) {
                sum[i][0] += bf_lo(v[i][q].x); sum[i][1] += bf_hi(v[i][q].x); sum[i][2] += bf_lo(v[i][q].y); sum[i][3] += bf_hi(v[i][q].y);
              }
            }
          };
          round(U0_, true);
          if (U0 == 9) {
#pragma unroll 1
            for (int q = U0; q < np; q += 8) round(std::integral_constant<int, 8>{}, false);
          }
          char* dst = (char*)(out + (t * 128 + r0) * DM + a * 320);
#pragma unroll
          for (int i = 0; i < NI; i++)
            if (td + i * 256 < lim) *(uint2*)(dst + off[i]) = make_uint2(pack2(sum[i][0], sum[i][1]), pack2(sum[i][2], sum[i][3]));
        };
        if (np == 5) add_parts(std::integral_constant<int, 10>{}, std::integral_constant<int, 5>{});
        else add_parts(std::integral_constant<int, 5>{}, std::integral_constant<int, 9>{});
      } else {
        release(st);
        push(OP_END, 0, 0, 0);
        break;
      }
    }
  }
}

typedef CUresult (*EncFn)(CUtensorMap*, CUtensorMapDataType, cuuint32_t, void*, const cuuint64_t*, const cuuint64_t*, const cuuint32_t*,
                          const cuuint32_t*, CUtensorMapInterleave, CUtensorMapSwizzle, CUtensorMapL2promotion, CUtensorMapFloatOOBfill);

#define PROMO CU_TENSOR_MAP_L2_PROMOTION_L2_128B
void make_map(EncFn enc, CUtensorMap* tm, const void* base, int rank, const cuuint64_t* dims, const cuuint64_t* strides, const cuuint32_t* box,
              CUtensorMapSwizzle sw = CU_TENSOR_MAP_SWIZZLE_128B, CUtensorMapDataType dt = CU_TENSOR_MAP_DATA_TYPE_BFLOAT16) {
  const cuuint32_t es[5] = {1, 1, 1, 1, 1};
  enc(tm, dt, rank, const_cast<void*>(base), dims, strides, box, es, CU_TENSOR_MAP_INTERLEAVE_NONE, sw, PROMO,
      CU_TENSOR_MAP_FLOAT_OOB_FILL_NONE);
}
void map_blk(EncFn enc, CUtensorMap* tm, const void* base, int rows, int cols, int brows, int bblk) {
  const cuuint64_t d[3] = {64, (cuuint64_t)rows, (cuuint64_t)cols / 64}, st[2] = {(cuuint64_t)cols * 2, 128};
  const cuuint32_t b[3] = {64, (cuuint32_t)brows, (cuuint32_t)bblk};
  make_map(enc, tm, base, 3, d, st, b);
}
void map_2d(EncFn enc, CUtensorMap* tm, const void* base, int rows, int cols, int brows, int bcols, CUtensorMapSwizzle sw) {
  const cuuint64_t d[2] = {(cuuint64_t)cols, (cuuint64_t)rows}, st[1] = {(cuuint64_t)cols * 2};
  const cuuint32_t b[2] = {(cuuint32_t)bcols, (cuuint32_t)brows};
  make_map(enc, tm, base, 2, d, st, b, sw);
}

}

extern "C" void kernel_launch(void* const* d_in, const int* in_sizes, int n_in, void* d_out, int out_size) {
  const bf16* x = (const bf16*)d_in[0];
  const bf16* mem0 = (const bf16*)d_in[1];
  const bf16* Wq = (const bf16*)d_in[2];
  const bf16* Wk = (const bf16*)d_in[3];
  const bf16* Wv = (const bf16*)d_in[4];
  const bf16* Wo = (const bf16*)d_in[5];
  const bf16* wqkv = (const bf16*)d_in[8];
  const bf16* wob = (const bf16*)d_in[9];
  const bf16* gate_w = (const bf16*)d_in[10];
  static EncFn enc = nullptr;
  static void *pK = nullptr, *pV = nullptr, *pO = nullptr, *pQ = nullptr, *pB = nullptr, *pA = nullptr;
  if (!enc) {
    void* fn = nullptr;
    cudaDriverEntryPointQueryResult qr;
    cudaGetDriverEntryPoint("cuTensorMapEncodeTiled", &fn, cudaEnableDefault, &qr);
    enc = (EncFn)fn;
    cudaGetSymbolAddress(&pK, g_K);
    cudaGetSymbolAddress(&pV, g_V);
    cudaGetSymbolAddress(&pO, g_O);
    cudaGetSymbolAddress(&pQ, g_qkv);
    cudaGetSymbolAddress(&pB, g_Ob);
    cudaGetSymbolAddress(&pA, g_part);
    cudaFuncSetAttribute(rec_kernel, cudaFuncAttributeMaxDynamicSharedMemorySize, R_SMEM_ALLOC);
    cudaFuncSetAttribute(aux_kernel, cudaFuncAttributeMaxDynamicSharedMemorySize, A_SMEM);
  }
  CUtensorMap tmX, tmK, tmV, tmWq, tmWq2, tmWk, tmWv, tmWo;
  map_2d(enc, &tmWq, Wq, DM, HD, 144, 64, CU_TENSOR_MAP_SWIZZLE_128B);
  map_2d(enc, &tmWq2, Wq, DM, HD, 32, 64, CU_TENSOR_MAP_SWIZZLE_128B);
  map_2d(enc, &tmWk, Wk, DM, HD, 128, 64, CU_TENSOR_MAP_SWIZZLE_128B);
  map_2d(enc, &tmWv, Wv, DM, HD, 128, 64, CU_TENSOR_MAP_SWIZZLE_128B);
  {
    const cuuint64_t d[3] = {32, HD, 20}, st[2] = {DM * 2, 64};
    const cuuint32_t b[3] = {32, 64, 7};
    make_map(enc, &tmWo, Wo, 3, d, st, b, CU_TENSOR_MAP_SWIZZLE_64B);
  }
  map_blk(enc, &tmX, x, S_TOK, DM, 32, 10);
  map_2d(enc, &tmK, pK, NSEG * LK, HD, LK, 64, CU_TENSOR_MAP_SWIZZLE_128B);
  map_2d(enc, &tmV, pV, NSEG * LK, HD, LK, 64, CU_TENSOR_MAP_SWIZZLE_128B);
  AuxMaps am;
  map_2d(enc, &am.xA, x, S_TOK, DM, 128, 32, CU_TENSOR_MAP_SWIZZLE_64B);
  map_blk(enc, &am.wq, Wq, DM, HD, 32, 6);
  map_blk(enc, &am.wqkv, wqkv, DM, 3 * DM, 32, 6);
  map_blk(enc, &am.wo, Wo, HD, DM, 32, 5);
  map_blk(enc, &am.wob, wob, DM, DM, 32, 5);
  map_blk(enc, &am.k, pK, NSEG * LK, HD, 80, 3);
  map_blk(enc, &am.v, pV, NSEG * LK, HD, 80, 3);
  map_2d(enc, &am.oA, pO, S_TOK, HD, 128, 32, CU_TENSOR_MAP_SWIZZLE_64B);
  map_blk(enc, &am.oS, pO, S_TOK, HD, 64, 3);
  map_2d(enc, &am.obA, pB, S_TOK, DM, 128, 32, CU_TENSOR_MAP_SWIZZLE_64B);
  map_2d(enc, &am.obS, pB, S_TOK, DM, 64, 160, CU_TENSOR_MAP_SWIZZLE_NONE);
  map_blk(enc, &am.qkvS, pQ, S_TOK, 3 * DM, 64, 3);
  map_2d(enc, &am.qkvQ, pQ, S_TOK, 3 * DM, 64, 160, CU_TENSOR_MAP_SWIZZLE_NONE);
  map_2d(enc, &am.qkvK, pQ, S_TOK, 3 * DM, 80, 160, CU_TENSOR_MAP_SWIZZLE_NONE);
  map_blk(enc, &am.part, pA, part_base(16) * 128, DM, 64, 1);
  rec_kernel<<<96, 256, R_SMEM_ALLOC, cudaStreamPerThread>>>(tmX, tmK, tmV, tmWq, tmWq2, tmWk, tmWv, tmWo, mem0, Wq, Wo, x);
  cudaLaunchConfig_t cfg = {};
  cfg.gridDim = dim3(AUX_GRID); cfg.blockDim = dim3(384); cfg.dynamicSmemBytes = A_SMEM; cfg.stream = cudaStreamPerThread;
  cudaLaunchAttribute at[1];
  at[0].id = cudaLaunchAttributeProgrammaticStreamSerialization;
  at[0].val.programmaticStreamSerializationAllowed = 1;
  cfg.attrs = at;
  cfg.numAttrs = 1;
  cudaLaunchKernelEx(&cfg, aux_kernel, am, x, gate_w, (bf16*)d_out);
}
```

```cpp
#include <cuda_runtime.h>
#include <cuda_bf16.h>
#include <cuda.h>
#include <stdint.h>
#include <type_traits>

typedef __nv_bfloat16 bf16;

namespace {

constexpr int S_TOK = 2048, DM = 640, NH = 32, DH = 192, HD = NH * DH, SEG = 32, NSEG = 64, MT = 8, LK = 40;
constexpr int SPIN_MAX = 1 << 20;

#define RB_LINE 384
constexpr int RB_SIZE = 160 * RB_LINE;
__device__ __align__(4096) unsigned char g_red[4 * RB_SIZE];
__device__ unsigned long long g_rec[96];
__device__ uint32_t g_epoch;
__device__ uint32_t g_err;
__device__ __align__(16) uint32_t g_segcnt[NSEG];
__device__ __align__(1024) bf16 g_K[NSEG * LK * HD];
__device__ __align__(1024) bf16 g_V[NSEG * LK * HD];
__device__ __align__(1024) bf16 g_O[S_TOK * HD];
__device__ __align__(1024) bf16 g_qkv[S_TOK * 3 * DM];
__device__ __align__(1024) bf16 g_Ob[S_TOK * DM];
__device__ float g_gate[2 * S_TOK];
__device__ uint32_t g_cnt[512 * 8];
__device__ uint32_t g_queue;
#define GTR(i) do {} while (0)

__device__ __forceinline__ uint32_t smem_u32(const void* p) { return (uint32_t)__cvta_generic_to_shared(p); }
__device__ __forceinline__ uint32_t clk32() { uint32_t t; asm volatile("mov.u32 %0, %%clock;" : "=r"(t)::"memory"); return t; }
__device__ __forceinline__ uint32_t mapa(uint32_t a, uint32_t r) { uint32_t o; asm("mapa.shared::cluster.u32 %0, %1, %2;" : "=r"(o) : "r"(a), "r"(r)); return o; }
__device__ __forceinline__ void mbar_init(uint32_t b, uint32_t c) { asm volatile("mbarrier.init.shared::cta.b64 [%0], %1;" ::"r"(b), "r"(c) : "memory"); }
__device__ __forceinline__ void mbar_expect(uint32_t b, uint32_t bytes) { asm volatile("mbarrier.arrive.expect_tx.shared::cta.b64 _, [%0], %1;" ::"r"(b), "r"(bytes) : "memory"); }
__device__ __forceinline__ void mbar_arrive(uint32_t b) { asm volatile("mbarrier.arrive.shared::cta.b64 _, [%0];" ::"r"(b) : "memory"); }
__device__ __forceinline__ bool mbar_try(uint32_t b, uint32_t par) {
  uint32_t p;
  asm volatile("{.reg .pred p; mbarrier.try_wait.parity.shared::cta.b64 p, [%1], %2; selp.u32 %0,1,0,p;}" : "=r"(p) : "r"(b), "r"(par) : "memory");
  return p;
}
__device__ __forceinline__ bool mbar_test(uint32_t b, uint32_t par) {
  uint32_t p;
  asm volatile("{.reg .pred p; mbarrier.test_wait.parity.shared::cta.b64 p, [%1], %2; selp.u32 %0,1,0,p;}" : "=r"(p) : "r"(b), "r"(par) : "memory");
  return p;
}
__device__ __forceinline__ bool mbar_try_cl(uint32_t b, uint32_t par) {
  uint32_t p;
  asm volatile("{.reg .pred p; mbarrier.try_wait.parity.acquire.cluster.shared::cta.b64 p, [%1], %2; selp.u32 %0,1,0,p;}" : "=r"(p) : "r"(b), "r"(par) : "memory");
  return p;
}
__device__ __forceinline__ void mbar_wait(uint32_t b, uint32_t par) {
  int n = 0;
#pragma unroll 1
  while (!mbar_try(b, par)) { if (++n > SPIN_MAX) { g_err = 1; break; } }
}
__device__ __forceinline__ void mbar_wait_cl(uint32_t b, uint32_t par) {
  int n = 0;
#pragma unroll 1
  while (!mbar_try_cl(b, par)) { if (++n > SPIN_MAX) { g_err = 2; break; } }
}
__device__ __forceinline__ void cluster_sync() { asm volatile("barrier.cluster.arrive.release.aligned; barrier.cluster.wait.acquire.aligned;" ::: "memory"); }
__device__ __forceinline__ void bar_sync(int id, int n) { asm volatile("bar.sync %0, %1;" ::"r"(id), "r"(n) : "memory"); }
__device__ __forceinline__ void bar_arrive(int id, int n) { asm volatile("bar.arrive %0, %1;" ::"r"(id), "r"(n) : "memory"); }
__device__ __forceinline__ void fence_async_smem() { asm volatile("fence.proxy.async.shared::cta;" ::: "memory"); }
__device__ __forceinline__ void ldsm4(uint32_t* r, uint32_t a) {
  asm volatile("ldmatrix.sync.aligned.m8n8.x4.shared.b16 {%0,%1,%2,%3}, [%4];" : "=r"(r[0]), "=r"(r[1]), "=r"(r[2]), "=r"(r[3]) : "r"(a) : "memory");
}
__device__ __forceinline__ void ldsm4t(uint32_t* r, uint32_t a) {
  asm volatile("ldmatrix.sync.aligned.m8n8.x4.trans.shared.b16 {%0,%1,%2,%3}, [%4];" : "=r"(r[0]), "=r"(r[1]), "=r"(r[2]), "=r"(r[3]) : "r"(a) : "memory");
}
__device__ __forceinline__ void ldsm2t(uint32_t* r, uint32_t a) {
  asm volatile("ldmatrix.sync.aligned.m8n8.x2.trans.shared.b16 {%0,%1}, [%2];" : "=r"(r[0]), "=r"(r[1]) : "r"(a) : "memory");
}
__device__ __forceinline__ void stsm4t(uint32_t a, uint32_t r0, uint32_t r1, uint32_t r2, uint32_t r3) {
  asm volatile("stmatrix.sync.aligned.m8n8.x4.trans.shared.b16 [%0], {%1,%2,%3,%4};" ::"r"(a), "r"(r0), "r"(r1), "r"(r2), "r"(r3) : "memory");
}
__device__ __forceinline__ void stsm2t(uint32_t a, uint32_t r0, uint32_t r1) {
  asm volatile("stmatrix.sync.aligned.m8n8.x2.trans.shared.b16 [%0], {%1,%2};" ::"r"(a), "r"(r0), "r"(r1) : "memory");
}
__device__ __forceinline__ uint32_t movmat(uint32_t a) { uint32_t d; asm volatile("movmatrix.sync.aligned.m8n8.trans.b16 %0, %1;" : "=r"(d) : "r"(a)); return d; }
__device__ __forceinline__ void mma16816(float* d, const uint32_t* a, uint32_t b0, uint32_t b1) {
  asm volatile("mma.sync.aligned.m16n8k16.row.col.f32.bf16.bf16.f32 {%0,%1,%2,%3}, {%4,%5,%6,%7}, {%8,%9}, {%0,%1,%2,%3};"
               : "+f"(d[0]), "+f"(d[1]), "+f"(d[2]), "+f"(d[3]) : "r"(a[0]), "r"(a[1]), "r"(a[2]), "r"(a[3]), "r"(b0), "r"(b1));
}
__device__ __forceinline__ void mma1688(float* d, uint32_t a0, uint32_t a1, uint32_t b0) {
  asm volatile("mma.sync.aligned.m16n8k8.row.col.f32.bf16.bf16.f32 {%0,%1,%2,%3}, {%4,%5}, {%6}, {%0,%1,%2,%3};"
               : "+f"(d[0]), "+f"(d[1]), "+f"(d[2]), "+f"(d[3]) : "r"(a0), "r"(a1), "r"(b0));
}
__device__ __forceinline__ uint32_t pack2(float lo, float hi) { uint32_t r; asm("cvt.rn.bf16x2.f32 %0, %1, %2;" : "=r"(r) : "f"(hi), "f"(lo)); return r; }
__device__ __forceinline__ float bf_lo(uint32_t w) { return __uint_as_float(w << 16); }
__device__ __forceinline__ float bf_hi(uint32_t w) { return __uint_as_float(w & 0xffff0000u); }
__device__ __forceinline__ float ex2(float x) { float y; asm("ex2.approx.ftz.f32 %0, %1;" : "=f"(y) : "f"(x)); return y; }
__device__ __forceinline__ void sts128(uint32_t a, uint32_t x, uint32_t y, uint32_t z, uint32_t w) { asm volatile("st.shared.v4.b32 [%0], {%1,%2,%3,%4};" ::"r"(a), "r"(x), "r"(y), "r"(z), "r"(w) : "memory"); }
__device__ __forceinline__ void sts128f(uint32_t a, float x, float y, float z, float w) { asm volatile("st.shared.v4.f32 [%0], {%1,%2,%3,%4};" ::"r"(a), "f"(x), "f"(y), "f"(z), "f"(w) : "memory"); }
__device__ __forceinline__ void sts64f(uint32_t a, float x, float y) { asm volatile("st.shared.v2.f32 [%0], {%1,%2};" ::"r"(a), "f"(x), "f"(y) : "memory"); }
__device__ __forceinline__ void sts32(uint32_t a, uint32_t x) { asm volatile("st.shared.b32 [%0], %1;" ::"r"(a), "r"(x) : "memory"); }
__device__ __forceinline__ void smax32(uint32_t a, uint32_t x) { asm volatile("red.shared.max.u32 [%0], %1;" ::"r"(a), "r"(x) : "memory"); }
__device__ __forceinline__ uint32_t lds32(uint32_t a) { uint32_t v; asm volatile("ld.shared.b32 %0, [%1];" : "=r"(v) : "r"(a) : "memory"); return v; }
__device__ __forceinline__ float4 lds128f(uint32_t a) { float4 v; asm volatile("ld.shared.v4.f32 {%0,%1,%2,%3}, [%4];" : "=f"(v.x), "=f"(v.y), "=f"(v.z), "=f"(v.w) : "r"(a) : "memory"); return v; }
__device__ __forceinline__ uint4 lds128(uint32_t a) { uint4 v; asm volatile("ld.shared.v4.b32 {%0,%1,%2,%3}, [%4];" : "=r"(v.x), "=r"(v.y), "=r"(v.z), "=r"(v.w) : "r"(a) : "memory"); return v; }
__device__ __forceinline__ float2 lds64f(uint32_t a) { float2 v; asm volatile("ld.shared.v2.f32 {%0,%1}, [%2];" : "=f"(v.x), "=f"(v.y) : "r"(a) : "memory"); return v; }
__device__ __forceinline__ void st_async2(uint32_t a, uint32_t x, uint32_t y, uint32_t bar) {
  asm volatile("st.async.weak.shared::cluster.mbarrier::complete_tx::bytes.v2.b32 [%0], {%1,%2}, [%3];" ::"r"(a), "r"(x), "r"(y), "r"(bar) : "memory");
}
__device__ __forceinline__ void st_async4(uint32_t a, uint32_t x, uint32_t y, uint32_t z, uint32_t w, uint32_t bar) {
  asm volatile("st.async.weak.shared::cluster.mbarrier::complete_tx::bytes.v4.b32 [%0], {%1,%2,%3,%4}, [%5];" ::"r"(a), "r"(x), "r"(y), "r"(z), "r"(w), "r"(bar) : "memory");
}
__device__ __forceinline__ void sts64(uint32_t a, uint32_t x, uint32_t y) { asm volatile("st.shared.v2.b32 [%0], {%1,%2};" ::"r"(a), "r"(x), "r"(y) : "memory"); }
__device__ __forceinline__ bool bar_red_or(int id, int n, bool q) {
  uint32_t r;
  asm volatile("{.reg .pred p, q; setp.ne.u32 q, %3, 0; barrier.cta.red.or.aligned.pred p, %1, %2, q; selp.u32 %0,1,0,p;}" : "=r"(r) : "r"(id), "r"(n), "r"((uint32_t)q) : "memory");
  return r;
}
__device__ __forceinline__ float rcp(float x) { float y; asm("rcp.approx.ftz.f32 %0, %1;" : "=f"(y) : "f"(x)); return y; }
__device__ __forceinline__ uint32_t hadd2(uint32_t a, uint32_t b) { uint32_t r; asm("add.rn.bf16x2 %0, %1, %2;" : "=r"(r) : "r"(a), "r"(b)); return r; }
__device__ __forceinline__ uint32_t pin(uint32_t v) { asm volatile("" : "+r"(v)); return v; }
template <int ID> __device__ __forceinline__ void sched_fence_(uint32_t a) {
  asm volatile("{.reg .pred p;\nsetp.eq.u32 p, %0, %1;\nSF: @p pmevent 0;\n@p bra.uni SF;}" ::"r"(a), "n"(0x40000000 + ID) : "memory");
}
#define sched_fence(a) sched_fence_<__LINE__>(a)
__device__ __forceinline__ bool elect() {
  uint32_t p;
  asm volatile("{.reg .pred p; elect.sync _|p, 0xffffffff; selp.u32 %0,1,0,p;}" : "=r"(p));
  return p;
}
__device__ __forceinline__ uint32_t opaque(uint32_t v) { return __shfl_sync(~0u, v, threadIdx.x & 31); }
__device__ __forceinline__ uint4 ldg_rlx128(const void* p) {
  uint4 v; asm volatile("ld.relaxed.gpu.global.v4.b32 {%0,%1,%2,%3}, [%4];" : "=r"(v.x), "=r"(v.y), "=r"(v.z), "=r"(v.w) : "l"(p) : "memory"); return v;
}
__device__ __forceinline__ uint2 ldg_rlx64(const void* p) {
  uint2 v; asm volatile("{.reg .b64 t; ld.relaxed.gpu.global.b64 t, [%2]; mov.b64 {%0,%1}, t;}" : "=r"(v.x), "=r"(v.y) : "l"(p) : "memory"); return v;
}
__device__ __forceinline__ uint32_t hmaxabs2(uint32_t a, uint32_t b) { uint32_t r; asm("max.xorsign.abs.bf16x2 %0, %1, %2;" : "=r"(r) : "r"(a), "r"(b)); return r; }
__device__ __forceinline__ uint32_t ldg_rlx32(const void* p) {
  uint32_t v; asm volatile("ld.relaxed.gpu.global.b32 %0, [%1];" : "=r"(v) : "l"(p) : "memory"); return v;
}
__device__ __forceinline__ void spin_until(uint32_t t0, int d) {
#pragma unroll 1
  while ((int)(clk32() - t0) < d) {}
}
__device__ __forceinline__ void stg_rlx64(void* p, uint32_t a, uint32_t b) {
  asm volatile("{.reg .b64 t; mov.b64 t, {%1,%2}; st.relaxed.gpu.global.b64 [%0], t;}" ::"l"(p), "r"(a), "r"(b) : "memory");
}
__device__ __forceinline__ uint32_t ldg_acq32(const void* p) { uint32_t v; asm volatile("ld.acquire.gpu.global.b32 %0, [%1];" : "=r"(v) : "l"(p) : "memory"); return v; }
__device__ __forceinline__ void stg_rel32(void* p, uint32_t v) { asm volatile("st.release.gpu.global.b32 [%0], %1;" ::"l"(p), "r"(v) : "memory"); }
__device__ __forceinline__ void cp_async16(uint32_t dst, const void* src) { asm volatile("cp.async.cg.shared.global [%0], [%1], 16;" ::"r"(dst), "l"(src) : "memory"); }
__device__ __forceinline__ void cp_async_wait_all() { asm volatile("cp.async.wait_all;" ::: "memory"); }
__device__ __forceinline__ void prefetch_l2(const void* p) { asm volatile("prefetch.global.L2 [%0];" ::"l"(p)); }
__device__ __forceinline__ void tma_load3(uint32_t dst, const CUtensorMap* tm, int c0, int c1, int c2, uint32_t bar) {
  asm volatile("cp.async.bulk.tensor.3d.shared::cluster.global.mbarrier::complete_tx::bytes [%0], [%1, {%3,%4,%5}], [%2];"
               ::"r"(dst), "l"(tm), "r"(bar), "r"(c0), "r"(c1), "r"(c2) : "memory");
}
__device__ __forceinline__ void tma_load2(uint32_t dst, const CUtensorMap* tm, int c0, int c1, uint32_t bar) {
  asm volatile("cp.async.bulk.tensor.2d.shared::cluster.global.mbarrier::complete_tx::bytes [%0], [%1, {%3,%4}], [%2];"
               ::"r"(dst), "l"(tm), "r"(bar), "r"(c0), "r"(c1) : "memory");
}
__device__ __forceinline__ void prefetch_map(const CUtensorMap* tm) { asm volatile("prefetch.tensormap [%0];" ::"l"(tm) : "memory"); }
__device__ __forceinline__ void tma_store2(const CUtensorMap* tm, uint32_t src, int c0, int c1) {
  asm volatile("cp.async.bulk.tensor.2d.global.shared::cta.bulk_group [%0, {%2,%3}], [%1];" ::"l"(tm), "r"(src), "r"(c0), "r"(c1) : "memory");
}
__device__ __forceinline__ void bulk_commit() { asm volatile("cp.async.bulk.commit_group;" ::: "memory"); }
__device__ __forceinline__ void bulk_wait0() { asm volatile("cp.async.bulk.wait_group 0;" ::: "memory"); }
__device__ __forceinline__ void bulk_wait_read0() { asm volatile("cp.async.bulk.wait_group.read 0;" ::: "memory"); }
__device__ __forceinline__ void wg_fence() { asm volatile("wgmma.fence.sync.aligned;" ::: "memory"); }
__device__ __forceinline__ void wg_commit() { asm volatile("wgmma.commit_group.sync.aligned;" ::: "memory"); }
__device__ __forceinline__ void wg_wait0() { asm volatile("wgmma.wait_group.sync.aligned 0;" ::: "memory"); }
__device__ __forceinline__ uint64_t desc_sw128(uint32_t addr) {
  return (uint64_t)((addr & 0x3FFFF) >> 4) | ((uint64_t)1 << 16) | ((uint64_t)64 << 32) | ((uint64_t)1 << 62);
}
template <int ACC>
__device__ __forceinline__ void wgmma_rs32(float* d, const uint32_t* a, uint64_t db) {
  asm volatile("{.reg .pred p; setp.ne.b32 p, %21, 0;\n"
               "wgmma.mma_async.sync.aligned.m64n32k16.f32.bf16.bf16 {%0,%1,%2,%3,%4,%5,%6,%7,%8,%9,%10,%11,%12,%13,%14,%15}, {%16,%17,%18,%19}, %20, p, 1, 1, 0;}"
               : "+f"(d[0]), "+f"(d[1]), "+f"(d[2]), "+f"(d[3]), "+f"(d[4]), "+f"(d[5]), "+f"(d[6]), "+f"(d[7]), "+f"(d[8]), "+f"(d[9]),
                 "+f"(d[10]), "+f"(d[11]), "+f"(d[12]), "+f"(d[13]), "+f"(d[14]), "+f"(d[15])
               : "r"(a[0]), "r"(a[1]), "r"(a[2]), "r"(a[3]), "l"(db), "n"(ACC));
}

template <int N> __device__ __forceinline__ void fence_regs(float* d) {
#pragma unroll
  for (int i = 0; i < N; i++) asm volatile("" : "+f"(d[i])::"memory");
}
__device__ __forceinline__ void wg_wait1() { asm volatile("wgmma.wait_group.sync.aligned 1;" ::: "memory"); }
__device__ __forceinline__ void tma_store3(const CUtensorMap* tm, uint32_t src, int c0, int c1, int c2) {
  asm volatile("cp.async.bulk.tensor.3d.global.shared::cta.bulk_group [%0, {%2,%3,%4}], [%1];" ::"l"(tm), "r"(src), "r"(c0), "r"(c1), "r"(c2) : "memory");
}
__device__ __forceinline__ void tma_red3(const CUtensorMap* tm, uint32_t src, int c0, int c1, int c2) {
  asm volatile("cp.reduce.async.bulk.tensor.3d.global.shared::cta.add.bulk_group [%0, {%2,%3,%4}], [%1];" ::"l"(tm), "r"(src), "r"(c0), "r"(c1), "r"(c2) : "memory");
}
__device__ __forceinline__ void stsm4(uint32_t a, uint32_t r0, uint32_t r1, uint32_t r2, uint32_t r3) {
  asm volatile("stmatrix.sync.aligned.m8n8.x4.shared.b16 [%0], {%1,%2,%3,%4};" ::"r"(a), "r"(r0), "r"(r1), "r"(r2), "r"(r3) : "memory");
}
__device__ __forceinline__ uint2 lds64(uint32_t a) { uint2 v; asm volatile("ld.shared.v2.b32 {%0,%1}, [%2];" : "=r"(v.x), "=r"(v.y) : "r"(a) : "memory"); return v; }
__device__ __forceinline__ uint32_t hmul2(uint32_t a, uint32_t b) { uint32_t r; asm("mul.rn.bf16x2 %0, %1, %2;" : "=r"(r) : "r"(a), "r"(b)); return r; }
__device__ __forceinline__ void wgmma_ss192t(float* d, uint64_t da, uint64_t db, int acc) {
  asm volatile("{.reg .pred p; setp.ne.b32 p, %98, 0;\n"
    "wgmma.mma_async.sync.aligned.m64n192k16.f32.bf16.bf16 "
    "{%0,%1,%2,%3,%4,%5,%6,%7,%8,%9,%10,%11,%12,%13,%14,%15,%16,%17,%18,%19,%20,%21,%22,%23,%24,%25,%26,%27,%28,%29,%30,%31,%32,%33,%34,%35,%36,%37,%38,%39,%40,%41,%42,%43,%44,%45,%46,%47,%48,%49,%50,%51,%52,%53,%54,%55,%56,%57,%58,%59,%60,%61,%62,%63,%64,%65,%66,%67,%68,%69,%70,%71,%72,%73,%74,%75,%76,%77,%78,%79,%80,%81,%82,%83,%84,%85,%86,%87,%88,%89,%90,%91,%92,%93,%94,%95}, %96, %97, p, 1, 1, 0, 1;}"
    : "+f"(d[0]), "+f"(d[1]), "+f"(d[2]), "+f"(d[3]), "+f"(d[4]), "+f"(d[5]), "+f"(d[6]), "+f"(d[7]), "+f"(d[8]), "+f"(d[9]), "+f"(d[10]), "+f"(d[11]),
      "+f"(d[12]), "+f"(d[13]), "+f"(d[14]), "+f"(d[15]), "+f"(d[16]), "+f"(d[17]), "+f"(d[18]), "+f"(d[19]), "+f"(d[20]), "+f"(d[21]), "+f"(d[22]),
      "+f"(d[23]), "+f"(d[24]), "+f"(d[25]), "+f"(d[26]), "+f"(d[27]), "+f"(d[28]), "+f"(d[29]), "+f"(d[30]), "+f"(d[31]), "+f"(d[32]), "+f"(d[33]),
      "+f"(d[34]), "+f"(d[35]), "+f"(d[36]), "+f"(d[37]), "+f"(d[38]), "+f"(d[39]), "+f"(d[40]), "+f"(d[41]), "+f"(d[42]), "+f"(d[43]), "+f"(d[44]),
      "+f"(d[45]), "+f"(d[46]), "+f"(d[47]), "+f"(d[48]), "+f"(d[49]), "+f"(d[50]), "+f"(d[51]), "+f"(d[52]), "+f"(d[53]), "+f"(d[54]), "+f"(d[55]),
      "+f"(d[56]), "+f"(d[57]), "+f"(d[58]), "+f"(d[59]), "+f"(d[60]), "+f"(d[61]), "+f"(d[62]), "+f"(d[63]), "+f"(d[64]), "+f"(d[65]), "+f"(d[66]),
      "+f"(d[67]), "+f"(d[68]), "+f"(d[69]), "+f"(d[70]), "+f"(d[71]), "+f"(d[72]), "+f"(d[73]), "+f"(d[74]), "+f"(d[75]), "+f"(d[76]), "+f"(d[77]),
      "+f"(d[78]), "+f"(d[79]), "+f"(d[80]), "+f"(d[81]), "+f"(d[82]), "+f"(d[83]), "+f"(d[84]), "+f"(d[85]), "+f"(d[86]), "+f"(d[87]), "+f"(d[88]),
      "+f"(d[89]), "+f"(d[90]), "+f"(d[91]), "+f"(d[92]), "+f"(d[93]), "+f"(d[94]), "+f"(d[95])
    : "l"(da), "l"(db), "r"(acc));
}
__device__ __forceinline__ void wgmma_rs128t(float* d, const uint32_t* a, uint64_t db, int acc) {
  asm volatile("{.reg .pred p; setp.ne.b32 p, %69, 0;\n"
    "wgmma.mma_async.sync.aligned.m64n128k16.f32.bf16.bf16 "
    "{%0,%1,%2,%3,%4,%5,%6,%7,%8,%9,%10,%11,%12,%13,%14,%15,%16,%17,%18,%19,%20,%21,%22,%23,%24,%25,%26,%27,%28,%29,%30,%31,%32,%33,%34,%35,%36,%37,%38,%39,%40,%41,%42,%43,%44,%45,%46,%47,%48,%49,%50,%51,%52,%53,%54,%55,%56,%57,%58,%59,%60,%61,%62,%63}, {%64,%65,%66,%67}, %68, p, 1, 1, 1;}"
    : "+f"(d[0]), "+f"(d[1]), "+f"(d[2]), "+f"(d[3]), "+f"(d[4]), "+f"(d[5]), "+f"(d[6]), "+f"(d[7]), "+f"(d[8]), "+f"(d[9]), "+f"(d[10]), "+f"(d[11]),
      "+f"(d[12]), "+f"(d[13]), "+f"(d[14]), "+f"(d[15]), "+f"(d[16]), "+f"(d[17]), "+f"(d[18]), "+f"(d[19]), "+f"(d[20]), "+f"(d[21]), "+f"(d[22]),
      "+f"(d[23]), "+f"(d[24]), "+f"(d[25]), "+f"(d[26]), "+f"(d[27]), "+f"(d[28]), "+f"(d[29]), "+f"(d[30]), "+f"(d[31]), "+f"(d[32]), "+f"(d[33]),
      "+f"(d[34]), "+f"(d[35]), "+f"(d[36]), "+f"(d[37]), "+f"(d[38]), "+f"(d[39]), "+f"(d[40]), "+f"(d[41]), "+f"(d[42]), "+f"(d[43]), "+f"(d[44]),
      "+f"(d[45]), "+f"(d[46]), "+f"(d[47]), "+f"(d[48]), "+f"(d[49]), "+f"(d[50]), "+f"(d[51]), "+f"(d[52]), "+f"(d[53]), "+f"(d[54]), "+f"(d[55]),
      "+f"(d[56]), "+f"(d[57]), "+f"(d[58]), "+f"(d[59]), "+f"(d[60]), "+f"(d[61]), "+f"(d[62]), "+f"(d[63])
    : "r"(a[0]), "r"(a[1]), "r"(a[2]), "r"(a[3]), "l"(db), "r"(acc));
}
__device__ __forceinline__ void wgmma_rs80(float* d, const uint32_t* a, uint64_t db, int acc) {
  asm volatile("{.reg .pred p; setp.ne.b32 p, %45, 0;\n"
    "wgmma.mma_async.sync.aligned.m64n80k16.f32.bf16.bf16 "
    "{%0,%1,%2,%3,%4,%5,%6,%7,%8,%9,%10,%11,%12,%13,%14,%15,%16,%17,%18,%19,%20,%21,%22,%23,%24,%25,%26,%27,%28,%29,%30,%31,%32,%33,%34,%35,%36,%37,%38,%39}, {%40,%41,%42,%43}, %44, p, 1, 1, 0;}"
    : "+f"(d[0]), "+f"(d[1]), "+f"(d[2]), "+f"(d[3]), "+f"(d[4]), "+f"(d[5]), "+f"(d[6]), "+f"(d[7]), "+f"(d[8]), "+f"(d[9]), "+f"(d[10]), "+f"(d[11]),
      "+f"(d[12]), "+f"(d[13]), "+f"(d[14]), "+f"(d[15]), "+f"(d[16]), "+f"(d[17]), "+f"(d[18]), "+f"(d[19]), "+f"(d[20]), "+f"(d[21]), "+f"(d[22]),
      "+f"(d[23]), "+f"(d[24]), "+f"(d[25]), "+f"(d[26]), "+f"(d[27]), "+f"(d[28]), "+f"(d[29]), "+f"(d[30]), "+f"(d[31]), "+f"(d[32]), "+f"(d[33]),
      "+f"(d[34]), "+f"(d[35]), "+f"(d[36]), "+f"(d[37]), "+f"(d[38]), "+f"(d[39])
    : "r"(a[0]), "r"(a[1]), "r"(a[2]), "r"(a[3]), "l"(db), "r"(acc));
}
__device__ __forceinline__ void wgmma_rs192t(float* d, const uint32_t* a, uint64_t db, int acc) {
  asm volatile("{.reg .pred p; setp.ne.b32 p, %101, 0;\n"
    "wgmma.mma_async.sync.aligned.m64n192k16.f32.bf16.bf16 "
    "{%0,%1,%2,%3,%4,%5,%6,%7,%8,%9,%10,%11,%12,%13,%14,%15,%16,%17,%18,%19,%20,%21,%22,%23,%24,%25,%26,%27,%28,%29,%30,%31,%32,%33,%34,%35,%36,%37,%38,%39,%40,%41,%42,%43,%44,%45,%46,%47,%48,%49,%50,%51,%52,%53,%54,%55,%56,%57,%58,%59,%60,%61,%62,%63,%64,%65,%66,%67,%68,%69,%70,%71,%72,%73,%74,%75,%76,%77,%78,%79,%80,%81,%82,%83,%84,%85,%86,%87,%88,%89,%90,%91,%92,%93,%94,%95}, {%96,%97,%98,%99}, %100, p, 1, 1, 1;}"
    : "+f"(d[0]), "+f"(d[1]), "+f"(d[2]), "+f"(d[3]), "+f"(d[4]), "+f"(d[5]), "+f"(d[6]), "+f"(d[7]), "+f"(d[8]), "+f"(d[9]), "+f"(d[10]), "+f"(d[11]),
      "+f"(d[12]), "+f"(d[13]), "+f"(d[14]), "+f"(d[15]), "+f"(d[16]), "+f"(d[17]), "+f"(d[18]), "+f"(d[19]), "+f"(d[20]), "+f"(d[21]), "+f"(d[22]),
      "+f"(d[23]), "+f"(d[24]), "+f"(d[25]), "+f"(d[26]), "+f"(d[27]), "+f"(d[28]), "+f"(d[29]), "+f"(d[30]), "+f"(d[31]), "+f"(d[32]), "+f"(d[33]),
      "+f"(d[34]), "+f"(d[35]), "+f"(d[36]), "+f"(d[37]), "+f"(d[38]), "+f"(d[39]), "+f"(d[40]), "+f"(d[41]), "+f"(d[42]), "+f"(d[43]), "+f"(d[44]),
      "+f"(d[45]), "+f"(d[46]), "+f"(d[47]), "+f"(d[48]), "+f"(d[49]), "+f"(d[50]), "+f"(d[51]), "+f"(d[52]), "+f"(d[53]), "+f"(d[54]), "+f"(d[55]),
      "+f"(d[56]), "+f"(d[57]), "+f"(d[58]), "+f"(d[59]), "+f"(d[60]), "+f"(d[61]), "+f"(d[62]), "+f"(d[63]), "+f"(d[64]), "+f"(d[65]), "+f"(d[66]),
      "+f"(d[67]), "+f"(d[68]), "+f"(d[69]), "+f"(d[70]), "+f"(d[71]), "+f"(d[72]), "+f"(d[73]), "+f"(d[74]), "+f"(d[75]), "+f"(d[76]), "+f"(d[77]),
      "+f"(d[78]), "+f"(d[79]), "+f"(d[80]), "+f"(d[81]), "+f"(d[82]), "+f"(d[83]), "+f"(d[84]), "+f"(d[85]), "+f"(d[86]), "+f"(d[87]), "+f"(d[88]),
      "+f"(d[89]), "+f"(d[90]), "+f"(d[91]), "+f"(d[92]), "+f"(d[93]), "+f"(d[94]), "+f"(d[95])
    : "r"(a[0]), "r"(a[1]), "r"(a[2]), "r"(a[3]), "l"(db), "r"(acc));
}

constexpr int NPQ = 2;
#define NQ 12
#define NQ_WIN 8
#define NO_EARLY 6
#define NO_MID 9
#define NW1 16
#define NW1A 10
#define VLD 6
#define VB 0
#define XPF 3
#define WSPLIT 8
#define PEARLY 0
#define NQ_W1 8
#define B5LATE 0
#define WD 750
#define DFENCE 0
#define PDS 300
#define PDT 50
#define PD 900
constexpr int R_WQ = 0;
constexpr int R_WO = R_WQ + 8 * (20 - NPQ) * 512;
constexpr int R_XT = R_WO + 14 * 12 * 512;
constexpr int R_MEM = R_XT;
constexpr int R_QB = R_XT + 40960;
constexpr int R_QA = R_QB + 1024;
constexpr int R_O2 = R_QA + 1024;
constexpr int R_VS = R_O2 + 1024;
constexpr int R_KT = R_VS + 1024;
constexpr int R_VT = R_KT + 5120;
constexpr int R_V1 = R_VT + 5120;
constexpr int R_SX = R_V1 + 8192;
constexpr int R_VM = R_SX + 4608;
constexpr int R_BAR = R_VM + 2048;
constexpr int R_MI = R_BAR + 64;
constexpr int R_SMEM = R_MI + 64;
static_assert(NPQ == 2 && R_XT % 1024 == 0 && R_KT % 1024 == 0 && R_VT % 1024 == 0 && R_V1 % 1024 == 0 && R_WO % 1024 == 0, "align");
constexpr int R_SMEM_ALLOC = R_SMEM;
static_assert(R_SMEM_ALLOC <= 232448, "smem");

#define TR(i) do {} while (0)

__device__ __forceinline__ void red_pair(unsigned char* p, float lo, float hi) {
  const int b = __float2int_rn(lo), a = __float2int_rn(hi);
  asm volatile("{.reg .b64 t; mov.b64 t, {%1,%2}; red.relaxed.gpu.global.add.u64 [%0], t;}" ::"l"(p), "r"(b + ((1 << 29) + (1 << 23))), "r"(a * 8) : "memory");
}
__device__ __forceinline__ unsigned long long swap0(unsigned char* p) {
  unsigned long long r;
  asm volatile("atom.relaxed.gpu.global.exch.b64 %0, [%1], 0;" : "=l"(r) : "l"(p) : "memory");
  return r;
}
__device__ __forceinline__ uint32_t dec_pair(uint32_t lo, uint32_t hi, uint32_t bias) { return pack2((float)(int)(lo * 8u + bias), (float)(int)hi); }

__global__ void __cluster_dims__(3, 1, 1) __launch_bounds__(256, 1)
rec_kernel(const __grid_constant__ CUtensorMap tmX, const __grid_constant__ CUtensorMap tmK, const __grid_constant__ CUtensorMap tmV,
           const __grid_constant__ CUtensorMap tmWq, const __grid_constant__ CUtensorMap tmWq2, const __grid_constant__ CUtensorMap tmWk,
           const __grid_constant__ CUtensorMap tmWv, const __grid_constant__ CUtensorMap tmWo, const bf16* __restrict__ mem0,
           const bf16* __restrict__ Wq, const bf16* __restrict__ Wo, const bf16* __restrict__ x) {
  extern __shared__ __align__(1024) unsigned char smem[];
  const uint32_t sb = smem_u32(smem);
  const int tid = threadIdx.x, lane = tid & 31, wid = __shfl_sync(~0u, tid >> 5, 0), g = wid >> 2, w = wid & 3;
  const int cta = blockIdx.x, head = cta / 3, rank = cta % 3;
  const int D0 = head * DH + rank * 64;
  const int tile0 = rank == 0 ? 0 : (rank == 1 ? 14 : 26);
  const uint32_t XBAR = sb + R_BAR, SBAR = XBAR + 8, OBAR = XBAR + 16, VBAR = XBAR + 24, FBAR = XBAR + 32, WBAR = XBAR + 40;
  constexpr uint32_t ONES = 0x3F803F80u;
  asm volatile("griddepcontrol.launch_dependents;" ::: "memory");
  GTR(0);
  if (wid == 0) {
    if (lane == 0) {
      mbar_init(XBAR, 1); mbar_init(SBAR, 4); mbar_init(OBAR, 5); mbar_init(VBAR, 1); mbar_init(FBAR, 2);
      mbar_init(WBAR, 1); mbar_init(WBAR + 8, 1); mbar_init(WBAR + 16, 1);
      asm volatile("fence.mbarrier_init.release.cluster;" ::: "memory");
      mbar_expect(WBAR, 81920); mbar_expect(WBAR + 8, 81920 + 2 * NPQ * 2048); mbar_expect(XBAR, 40960);
      mbar_expect(SBAR, 3072); mbar_expect(OBAR, 2048); mbar_expect(VBAR, 8192);
      sts128(sb + R_MI + 48, 0, 0, 0, 0);
    }
    __syncwarp();
    if (lane < 5) tma_load2(sb + lane * 16384, &tmWk, D0, lane * 128, WBAR);
    if (lane == 5) tma_load3(sb + R_XT, &tmX, 0, 0, 0, XBAR);
    if (lane < 5) tma_load2(lane < 4 ? sb + 81920 + lane * 16384 : sb + R_QB, &tmWv, D0, lane * 128, WBAR + 8);
    if (lane < 2) tma_load2(sb + R_QB + 16384 + lane * 4096, &tmWq2, D0, lane * 320, WBAR + 8);
  }
  if (tid == 32) { prefetch_map(&tmWq); prefetch_map(&tmWo); prefetch_map(&tmK); prefetch_map(&tmV); }
  if (tid >= 64 && tid < 144) prefetch_l2(mem0 + (tid - 64) * 64);
  __syncthreads();
  GTR(1);
#pragma unroll
  for (int i = 0; i < 5; i++) { const int l = tid + i * 256; prefetch_l2((l < 640 ? Wq : Wo - 40960) + (size_t)cta * 40960 + l * 64); }
  uint32_t ww[40][4], wqp[NPQ][4];
  {
    uint32_t xm = 0;
#pragma unroll
    for (int i = 0; i < 7; i++) {
      const int v = tid + i * 256, gv = cta * 1707 + v;
      if (v < 1707 && gv < S_TOK * DM / 8) {
        const uint4 q = __ldg((const uint4*)x + gv);
        xm = hmaxabs2(hmaxabs2(xm, hmaxabs2(q.x, q.y)), hmaxabs2(q.z, q.w));
      }
    }
    xm = __reduce_max_sync(~0u, max((xm << 16) & 0x7fffffffu, xm & 0x7fff0000u));
    const uint32_t p = sb + (lane >> 4) * 1024 + (lane & 7) * 128 + (((2 * w + ((lane >> 3) & 1)) ^ (lane & 7)) << 4);
    mbar_wait(WBAR + 8 * g, 0);
    GTR(2);
#pragma unroll
    for (int f = 0; f < 40; f++) ldsm4t(ww[f], (f >= 32 && g == 1) ? p + R_QB + (f - 32) * 2048 : p + g * 81920 + f * 2048);
    mbar_wait(WBAR + 8, 0);
    GTR(3);
#pragma unroll
    for (int f = 0; f < NPQ; f++) ldsm4t(wqp[f], p + R_QB + 16384 + g * 4096 + f * 2048);
    __syncthreads();
    asm volatile("barrier.cluster.arrive.relaxed.aligned;" ::: "memory");
    if (wid == 0) {
      if (lane == 0) mbar_expect(WBAR + 16, 18 * 4096 + 21 * 4096);
      __syncwarp();
      if (lane < 4) tma_load2(sb + R_WQ + lane * 18432, &tmWq, D0, (lane >> 1) * 320 + 32 + (lane & 1) * 144, WBAR + 16);
      else if (lane < 7) tma_load3(sb + R_WO + ((lane - 1 - rank) % 3) * 28672, &tmWo, 0, head * DH + (lane - 4) * 64, tile0 >> 1, WBAR + 16);
      __syncwarp();
    }
    float nv[4] = {0.f, 0.f, 0.f, 0.f};
#pragma unroll
    for (int f = 0; f < 40; f++) {
      const uint32_t a[4] = {ww[f][0] & 0x7fff7fffu, ww[f][1] & 0x7fff7fffu, ww[f][2] & 0x7fff7fffu, ww[f][3] & 0x7fff7fffu};
      mma16816(nv, a, ONES, ONES);
    }
    const uint32_t mv = __reduce_max_sync(~0u, __float_as_uint(fmaxf(nv[0], nv[2])));
    if (lane == 0) { if (g == 1) smax32(sb + R_MI + 48, mv); smax32(sb + R_MI + 52, xm); }
  }
  GTR(4);

  const uint32_t rF_ = opaque(sb + lane * 16);
  const uint32_t rP_ = opaque(sb + (lane >> 4) * 1024 + (lane & 7) * 128 + (((2 * w + ((lane >> 3) & 1)) ^ (lane & 7)) << 4));
  const int tA = g == 1 ? 2 * w : (rank != 1 ? (w < 2 ? 8 + 2 * w : 10 + w) : 8 + w);
  const bool two = g == 1 || (w < 2 && rank != 1);
  const uint32_t r1 = rank == 2 ? 0 : rank + 1, r2 = rank == 0 ? 2 : rank - 1;
  const uint32_t rW_ = opaque(sb + R_WO + (tA >> 1) * 4096 + ((lane >> 4) * 8 + (lane & 7)) * 64 +
                             (((2 * (tA & 1) + ((lane >> 3) & 1)) ^ ((lane >> 1) & 3)) << 4));
  uint32_t wqt[NQ][4];
  float u = 1.f;
  uint32_t t0 = 0;
  int s = -1;

#define WOFF(ks) (((ks) >> 2) * 28672 + ((ks) & 3) * 1024)
#define XDESC(j) (((uint64_t)0x40000040 << 32) | (dlo + ((((j) >> 2) * 4096 + ((j) & 3) * 32) >> 4)))

  auto window = [&](auto G_, auto FIRST_) {
    constexpr int G = decltype(G_)::value;
    constexpr bool FIRST = decltype(FIRST_)::value;
    const uint32_t rF = pin(rF_), rP = pin(rP_);
    float d[16];
    const uint32_t dlo = pin(((sb + R_XT) >> 4) | 0x10000);
    const uint32_t wqS = rP + R_WQ + G * (20 - NPQ) * 2048;
    uint4 y[5];
    unsigned long long zr = 0;
    const uint32_t t = w * 32 + ((rF - sb) >> 4);
    if (G == 0) zr = swap0(g_red + (((s + 2) & 3) * RB_SIZE + ((cta % 20) * 8 + (t >> 4)) * RB_LINE + (t & 15) * 8));
    if (G == 0) {
      if (!FIRST && w == 3) {
        if (elect()) {
          mbar_expect(SBAR, 3072); mbar_expect(OBAR, 2048); mbar_expect(VBAR, 8192);
          asm volatile("mbarrier.arrive.relaxed.cluster.shared::cluster.b64 _, [%0];" ::"r"(mapa(FBAR, r1)) : "memory");
          asm volatile("mbarrier.arrive.relaxed.cluster.shared::cluster.b64 _, [%0];" ::"r"(mapa(FBAR, r2)) : "memory");
        }
        __syncwarp();
      }
    }
    const unsigned char* yp = g_red + ((s & 3) * RB_SIZE + (G * 80 + (t >> 3)) * RB_LINE + (t & 7) * 16);
    auto poll = [&]() {
      TR(10);
      spin_until(t0, PD);
#pragma unroll
      for (int q = 0; q < 5; q++) y[q] = ldg_rlx128(yp + q * 16 * RB_LINE);
      TR(9);
      sched_fence(sb);
    };
    constexpr int WS = FIRST || G == 1 ? 40 : WSPLIT;
    if (!FIRST && G == 0) {
#pragma unroll
      for (int f = 0; f < NQ_WIN; f++) ldsm4t(wqt[f], wqS + f * 2048);
      asm volatile("" : "+l"(yp));
      mbar_wait(XBAR, (s + 1) & 1);
      spin_until(t0, WD);
    } else {
      mbar_wait(XBAR, (s + 1) & 1);
    }
    TR(11);
    wg_fence();
    wgmma_rs32<0>(d, ww[0], XDESC(0));
#pragma unroll
    for (int j = 1; j < WS; j++) wgmma_rs32<1>(d, ww[j], XDESC(j));
    if (FIRST) {
      const unsigned short* m = (const unsigned short*)mem0 + (t & 1) * 4 * DM + G * 320 + (t >> 1);
#pragma unroll
      for (int q = 0; q < 5; q++) y[q] = make_uint4(m[q * 64], m[q * 64 + DM], m[q * 64 + 2 * DM], m[q * 64 + 3 * DM]);
    } else if (G == 0) {
      poll();
    }
#pragma unroll
    for (int j = WS; j < 40; j++) wgmma_rs32<1>(d, ww[j], XDESC(j));
    wg_commit();
    if (!FIRST && G == 1) {
      asm volatile("" : "+l"(yp));
      if (PEARLY) poll();
      mbar_wait(FBAR, s & 1);
#pragma unroll
      for (int f = 0; f < NQ_W1; f++) ldsm4t(wqt[f], wqS + f * 2048);
    }
    if (FIRST) asm volatile("barrier.cluster.wait.acquire.aligned;" ::: "memory");
    wg_wait0();
    fence_regs<16>(d);
    TR(13);
    bar_arrive(8 + G, 256);
    if (!FIRST && G == 1 && !PEARLY) poll();
    {
      uint32_t pk[8];
#pragma unroll
      for (int q = 0; q < 8; q++) pk[q] = pack2(d[2 * q], d[2 * q + 1]);
      stsm4t(rP + (G == 1 ? R_VT : R_KT) + 1024, pk[0], pk[1], pk[2], pk[3]);
      stsm4t(rP + (G == 1 ? R_VT : R_KT) + 3072, pk[4], pk[5], pk[6], pk[7]);
      if (G == 1) {
        const uint32_t e1 = mapa(rF + R_V1 + 4096 + w * 512, r1), e2 = mapa(rF + R_V1 + w * 512, r2), b1 = mapa(VBAR, r1), b2 = mapa(VBAR, r2);
        st_async4(e1, pk[0], pk[1], pk[2], pk[3], b1);
        st_async4(e2, pk[0], pk[1], pk[2], pk[3], b2);
        st_async4(e1 + 2048, pk[4], pk[5], pk[6], pk[7], b1);
        st_async4(e2 + 2048, pk[4], pk[5], pk[6], pk[7], b2);
      }
    }
    if (FIRST) {
      mbar_wait(WBAR + 16, 0);
      const uint32_t woA = rW_;
      float na[4] = {0.f, 0.f, 0.f, 0.f}, nb[4] = {0.f, 0.f, 0.f, 0.f};
#pragma unroll
      for (int ks = 0; ks < 12; ks++) {
        uint32_t a[4], b[4];
        ldsm4t(a, woA + WOFF(ks));
        ldsm4t(b, (two ? woA ^ 32 : woA) + WOFF(ks));
#pragma unroll
        for (int q = 0; q < 4; q++) { a[q] &= 0x7fff7fffu; b[q] &= 0x7fff7fffu; }
        mma16816(na, a, ONES, ONES);
        mma16816(nb, b, ONES, ONES);
      }
      const uint32_t mo = __reduce_max_sync(~0u, __float_as_uint(fmaxf(fmaxf(na[0], na[2]), fmaxf(nb[0], nb[2]))));
      if (rF == sb) smax32(sb + R_MI + 56, mo);
      __syncthreads();
      if (G == 1 && w == 2) {
        const uint4 r = lds128(sb + R_MI + 48);
        const uint32_t epoch = *(volatile uint32_t*)&g_epoch + 1;
        if (rF == sb) stg_rlx64(&g_rec[cta], (r.y & 0xffff0000u) | (epoch & 0xffffu), ((r.x + 0xffffu) & 0xffff0000u) | ((r.z + 0xffffu) >> 16));
      }
    }
#pragma unroll
    for (int f = FIRST ? 0 : (G == 1 ? NQ_W1 : NQ_WIN); f < NQ; f++) ldsm4t(wqt[f], wqS + f * 2048);
    if (FIRST || DFENCE) sched_fence(sb);
    TR(14);
    const uint32_t ma = sb + R_MEM + G * 5120 + t * 8;
    if (FIRST) {
      bar_sync(9 - G, 256);
#pragma unroll
      for (int j = 0; j < 5; j++) sts64(ma + j * 1024, y[j].x | (y[j].y << 16), y[j].z | (y[j].w << 16));
    } else {
      int n = 0;
#pragma unroll 1
      while (!__all_sync(~0u, (y[0].y & y[0].w & y[1].y) & (y[1].w & y[2].y & y[2].w) & (y[3].y & y[3].w & y[4].y) & (y[4].w & 4))) {
#pragma unroll
        for (int j = 0; j < 5; j++) if (!(y[j].y & y[j].w & 4)) y[j] = ldg_rlx128(yp + j * 16 * RB_LINE);
        if (++n > SPIN_MAX) { g_err = 5; break; }
      }
      const uint32_t bias = 0x80000000u + (sb >> 31);
      bar_sync(9 - G, 256);
#pragma unroll
      for (int j = 0; j < 5; j++) sts64(ma + j * 1024, dec_pair(y[j].x, y[j].y, bias), dec_pair(y[j].z, y[j].w, bias));
    }
    if (G == 0 && zr == ~0ull) g_err = 9;
    TR(0);
  };

  auto oproj = [&](auto TWO_, auto NPRE_, auto& wot, const uint32_t rF, const uint32_t woA, const uint32_t woB,
                   float sm0, float sm1, bool have_sums) {
    constexpr bool TWO = decltype(TWO_)::value;
    constexpr int NPRE = decltype(NPRE_)::value;
    float c[4][4];
#pragma unroll
    for (int q = 0; q < 4; q++) c[q][0] = c[q][1] = c[q][2] = c[q][3] = 0.f;
    unsigned char* sp = g_red + ((s & 3) * RB_SIZE + (4 * (tile0 + tA) + ((rF - sb) >> 8)) * RB_LINE + (((rF - sb) >> 1) & 120));
    bar_sync(3, 256);
    TR(8);
    uint4 ob[6];
    ob[0] = lds128(rF + R_QB); ob[1] = lds128(rF + R_QB + 512);
    const float2 su = lds64f(sb + R_MI + 48);
    if (!have_sums) { const float2 t = lds64f(sb + R_MI + 16 + (((rF - sb) >> 1) & 24)); sm0 = t.x; sm1 = t.y; }
#pragma unroll
    for (int p = 0; p < 6; p++) {
      if (p + 2 < 6) ob[p + 2] = lds128(rF + (p < 2 ? R_QA : R_O2) + (p & 1) * 512);
#pragma unroll
      for (int e = 0; e < 2; e++) {
        const int ks = 2 * p + e;
        const uint32_t b0 = e ? ob[p].z : ob[p].x, b1 = e ? ob[p].w : ob[p].y;
        if (TWO) {
          const int iA = 2 * ks, iB = iA + 1;
          mma16816(c[e], wot[iA % NPRE], b0, b1);
          if (iA + NPRE < 24) ldsm4t(wot[iA % NPRE], woA + WOFF((iA + NPRE) >> 1));
          mma16816(c[2 + e], wot[iB % NPRE], b0, b1);
          if (iB + NPRE < 24) ldsm4t(wot[iB % NPRE], woB + WOFF((iB + NPRE) >> 1));
        } else {
          mma16816(c[ks & 3], wot[ks], b0, b1);
        }
      }
    }
    const float f0 = su.x * rcp(sm0), f1 = su.x * rcp(sm1);
    t0 = clk32() + (TWO ? (have_sums ? -PDT : 0) : PDS);
    u = su.y;
    if (TWO) {
      red_pair(sp, (c[0][0] + c[1][0]) * f0, (c[0][1] + c[1][1]) * f1);
      red_pair(sp + 2 * RB_LINE, (c[0][2] + c[1][2]) * f0, (c[0][3] + c[1][3]) * f1);
      red_pair(sp + 4 * RB_LINE, (c[2][0] + c[3][0]) * f0, (c[2][1] + c[3][1]) * f1);
      red_pair(sp + 6 * RB_LINE, (c[2][2] + c[3][2]) * f0, (c[2][3] + c[3][3]) * f1);
    } else {
      red_pair(sp, ((c[0][0] + c[1][0]) + (c[2][0] + c[3][0])) * f0, ((c[0][1] + c[1][1]) + (c[2][1] + c[3][1])) * f1);
      red_pair(sp + 2 * RB_LINE, ((c[0][2] + c[1][2]) + (c[2][2] + c[3][2])) * f0, ((c[0][3] + c[1][3]) + (c[2][3] + c[3][3])) * f1);
    }
    TR(15);
  };

  auto step = [&](auto G_, auto LAST_) {
    constexpr int G = decltype(G_)::value;
    constexpr bool LAST = decltype(LAST_)::value;
    __syncthreads();
    const uint32_t rF = pin(rF_), rP = pin(rP_);
    TR(1);
    const uint32_t wqS = rP + R_WQ + G * (20 - NPQ) * 2048, rM = rF + R_MEM;
    const uint32_t l8 = sb + ((rF - sb) >> 1) + w * 256;
    const uint32_t woA = pin(rW_), woB = woA ^ 32;
    float aq[2][4] = {};
    const uint32_t ln = (rF - sb) >> 4;
    const uint32_t rS = sb + (ln & 7) * 128 + (ln < 16 ? R_QB + (ln & 8) * 128 + (((2 * w + G) ^ (ln & 7)) << 4) : R_KT + (((2 * w + ((ln >> 3) & 1)) ^ (ln & 7)) << 4));
    auto qmma = [&](int f, uint32_t b0, uint32_t b1) {
      if (f < NPQ) mma16816(aq[f & 1], wqp[f], b0, b1);
      else {
        const int slot = (f - NPQ) % NQ;
        mma16816(aq[f & 1], wqt[slot], b0, b1);
        if (f + NQ < 20) ldsm4t(wqt[slot], wqS + (f - NPQ + NQ) * 2048);
      }
    };
    if constexpr (G == 1) {
      uint32_t bb[20][4];
      if (!LAST) {
        ldsm4t(bb[10], rM + 5120);
        ldsm4t(bb[11], rM + 5632);
#pragma unroll
        for (int i = 10; i < 20; i++) {
          if (i + 2 < 20) ldsm4t(bb[i + 2], rM + (i + 2) * 512);
          qmma(2 * i - 20, bb[i][0], bb[i][1]);
          qmma(2 * i - 19, bb[i][2], bb[i][3]);
        }
        stsm2t(rS, pack2(aq[0][0] + aq[1][0], aq[0][1] + aq[1][1]), pack2(aq[0][2] + aq[1][2], aq[0][3] + aq[1][3]));
        bar_arrive(1, 256);
      }
      TR(2);
      float av[4][4] = {};
      uint32_t m0 = 0, m1 = 0;
      auto vmma = [&](auto MAX_) {
#pragma unroll
        for (int n = 0; n < 20; n++) {
          const int i = (n + 10) % 20;
          if (LAST && n < 8) ldsm4t(bb[(n + 10) % 20], rM + ((n + 10) % 20) * 512);
          if (LAST && n == 0) { ldsm4t(bb[18], rM + 18 * 512); ldsm4t(bb[19], rM + 19 * 512); }
          if (n == VB && !LAST) { bar_sync(5, 256); sched_fence(sb); }
          if (n == VLD) {
            if (VB != VLD && !LAST) sched_fence(sb);
#pragma unroll
            for (int q = 0; q < 10; q++) ldsm4t(bb[q], rM + q * 512);
            if (!LAST) sched_fence(sb);
          }
          mma16816(av[(2 * n) & 3], ww[2 * i], bb[i][0], bb[i][1]);
          mma16816(av[(2 * n + 1) & 3], ww[2 * i + 1], bb[i][2], bb[i][3]);
          if (decltype(MAX_)::value) { m0 = hmaxabs2(m0, hmaxabs2(bb[i][0], bb[i][1])); m1 = hmaxabs2(m1, hmaxabs2(bb[i][2], bb[i][3])); }
        }
      };
      auto vout = [&]() {
        const uint32_t vm0 = pack2(((av[0][0] + av[1][0]) + (av[2][0] + av[3][0])) * u, ((av[0][1] + av[1][1]) + (av[2][1] + av[3][1])) * u);
        const uint32_t vm1 = pack2(((av[0][2] + av[1][2]) + (av[2][2] + av[3][2])) * u, ((av[0][3] + av[1][3]) + (av[2][3] + av[3][3])) * u);
        if (!LAST) {
          st_async2(mapa(l8 + R_VM + 1024, r1), vm0, vm1, mapa(OBAR, r1));
          st_async2(mapa(l8 + R_VM, r2), vm0, vm1, mapa(OBAR, r2));
          sts64(l8 + R_VS, vm0, vm1);
          __syncwarp();
          if (rF == sb) mbar_arrive(OBAR);
        }
        stsm2t(rP + R_VT, vm0, vm1);
      };
      if (LAST) { vmma(std::false_type{}); vout(); return; }
      uint32_t wot[NW1][4];
      auto wpre = [&](int i0, int i1) {
#pragma unroll
        for (int i = i0; i < i1; i++) ldsm4t(wot[i], ((i & 1) ? woB : woA) + WOFF(i >> 1));
      };
      if (w != 1) {
        vmma(std::false_type{});
        bar_arrive(7, 128);
        vout();
        bar_arrive(2, 128);
        TR(5);
        wpre(0, NW1A);
      } else {
        vmma(std::true_type{});
        bar_sync(7, 128);
        if (elect()) { mbar_expect(XBAR, 40960); tma_load3(sb + R_XT, &tmX, 0, (s + 1) * SEG, 0, XBAR); }
        __syncwarp();
        vout();
        if (XPF && s + XPF < NSEG && rF - sb < 64 && cta < 80) prefetch_l2(x + (size_t)(s + XPF) * SEG * DM + cta * 256 + (rF - sb) * 4);
        TR(5);
        m0 = hmaxabs2(m0, m1);
        const uint32_t mx = __reduce_max_sync(~0u, max((m0 << 16) & 0x7fffffffu, m0 & 0x7fff0000u));
        const float2 mi = lds64f(sb + R_MI + 8);
        wpre(0, NW1A);
        bar_sync(2, 128);
        if (elect()) {
          fence_async_smem();
          if (s > 0) {
            bulk_wait0();
            asm volatile("red.relaxed.gpu.global.add.u32 [%0], 1;" ::"l"(&g_segcnt[s - 1]) : "memory");
          }
          tma_store2(&tmK, sb + R_KT, D0, s * LK);
          tma_store2(&tmV, sb + R_VT, D0, s * LK);
          bulk_commit();
        }
        __syncwarp();
        float wb = mi.x, xm = mi.y;
        if (s == 0) {
          const uint32_t epoch = *(volatile uint32_t*)&g_epoch + 1;
          uint32_t av_ = 0, ao = 0, xi = 0;
#pragma unroll 1
          for (int j = 0; j < 3; j++) {
            uint2 r;
            int n = 0;
#pragma unroll 1
            while (true) {
              r = ldg_rlx64(&g_rec[j * 32 + ((rF - sb) >> 4)]);
              if (((r.x ^ epoch) & 0xffffu) == 0) break;
              if (++n > SPIN_MAX) { g_err = 6; break; }
            }
            av_ = max(av_, r.y & 0xffff0000u); ao = max(ao, r.y << 16); xi = max(xi, r.x & 0xffff0000u);
          }
          av_ = __reduce_max_sync(~0u, av_); ao = __reduce_max_sync(~0u, ao); xi = __reduce_max_sync(~0u, xi);
          wb = __uint_as_float(av_) * __uint_as_float(ao) * 33.f; xm = __uint_as_float(xi);
          if (rF == sb) sts64f(sb + R_MI + 8, wb, xm);
          __syncwarp();
        }
        const float hm = fmaxf(__uint_as_float(mx) * u, xm);
        const uint32_t eb = min(max(__float_as_uint(hm * wb) >> 23, 40u), 200u);
        if (rF == sb) sts64(sb + R_MI + 48, (280u - eb) << 23, (eb - 29u) << 23);
        if (elect()) bulk_wait_read0();
        __syncwarp();
      }
      if (NW1A < NW1) {
        bar_sync(4, 256);
        wpre(NW1A, NW1);
      }
      TR(6);
      oproj(std::true_type{}, std::integral_constant<int, NW1>{}, wot, rF, woA, woB, 0.f, 0.f, false);
    } else {
      {
        uint32_t bb[20][4];
        float ak[4][4] = {};
        ldsm4t(bb[0], rM);
        ldsm4t(bb[10], rM + 5120);
#pragma unroll
        for (int i = 0; i < 10; i++) {
          if (i + 1 < 10) { ldsm4t(bb[i + 1], rM + (i + 1) * 512); ldsm4t(bb[i + 11], rM + (i + 11) * 512); }
          mma16816(ak[0], ww[2 * i], bb[i][0], bb[i][1]);
          if (!LAST) qmma(2 * i, bb[i][0], bb[i][1]);
          mma16816(ak[1], ww[2 * i + 1], bb[i][2], bb[i][3]);
          if (!LAST) qmma(2 * i + 1, bb[i][2], bb[i][3]);
          mma16816(ak[2], ww[2 * i + 20], bb[i + 10][0], bb[i + 10][1]);
          mma16816(ak[3], ww[2 * i + 21], bb[i + 10][2], bb[i + 10][3]);
        }
#pragma unroll
        for (int q = 0; q < 4; q++) { ak[0][q] += ak[2][q]; ak[1][q] += ak[3][q]; }
        stsm4t(rS, pack2(aq[0][0] + aq[1][0], aq[0][1] + aq[1][1]), pack2(aq[0][2] + aq[1][2], aq[0][3] + aq[1][3]),
               pack2((ak[0][0] + ak[1][0]) * u, (ak[0][1] + ak[1][1]) * u), pack2((ak[0][2] + ak[1][2]) * u, (ak[0][3] + ak[1][3]) * u));
      }
      if (LAST) return;
      bar_sync(1, 256);
      if (!B5LATE) bar_arrive(5, 256);
      TR(2);
      if (w != 3) {
        uint32_t qa[4][4], kk[4][4];
        float x[4][4] = {};
#pragma unroll
        for (int i = 0; i < 4; i++) { ldsm4(qa[i], (rP ^ (i << 5)) + R_QB); ldsm4(kk[i], ((rP ^ (i << 5)) + w * 2048) + R_KT); }
        const uint32_t dst = rF + R_SX + rank * 1536 + w * 512;
        const uint32_t e1 = mapa(dst, r1), e2 = mapa(dst, r2), s1 = mapa(SBAR, r1), s2 = mapa(SBAR, r2);
#pragma unroll
        for (int i = 0; i < 4; i++) { mma16816(x[i & 1], qa[i], kk[i][0], kk[i][1]); mma16816(x[2 + (i & 1)], qa[i], kk[i][2], kk[i][3]); }
        const uint32_t u0 = __float_as_uint((x[0][0] + x[0][2]) + (x[1][0] + x[1][2])), u1 = __float_as_uint((x[0][1] + x[0][3]) + (x[1][1] + x[1][3]));
        const uint32_t u2 = __float_as_uint((x[2][0] + x[2][2]) + (x[3][0] + x[3][2])), u3 = __float_as_uint((x[2][1] + x[2][3]) + (x[3][1] + x[3][3]));
        st_async4(e1, u0, u1, u2, u3, s1);
        st_async4(e2, u0, u1, u2, u3, s2);
        sts128(dst, u0, u1, u2, u3);
        __syncwarp();
        if (rF == sb) mbar_arrive(SBAR);
      }
      if (B5LATE) bar_arrive(5, 256);
      TR(4);
      mbar_wait(VBAR, s & 1);
      uint32_t wot[12][4], va[3][8];
      ldsm4t(va[0], rP + R_VT + 1024); ldsm4t(va[0] + 4, rP + R_VT + 3072);
#pragma unroll
      for (int q = 0; q < 4; q++) {
        const uint4 t = lds128(rF + R_V1 + w * 512 + q * 2048);
        uint32_t* v = va[1 + (q >> 1)] + (q & 1) * 4;
        v[0] = t.x; v[1] = t.y; v[2] = t.z; v[3] = t.w;
      }
      auto wpre = [&](int i0, int i1) {
        if (two) {
#pragma unroll
          for (int i = i0; i < i1; i++) ldsm4t(wot[i], ((i & 1) ? woB : woA) + WOFF(i >> 1));
        } else {
#pragma unroll
          for (int i = i0; i < i1; i++) ldsm4t(wot[i], woA + WOFF(i));
        }
      };
      wpre(0, NO_EARLY);
      const uint32_t dst = rF + (w >> 1) * 512 + (w & 1) * 8;
      const float scl = u * (0.07216878364870322f * 1.4426950408889634f);
      mbar_wait(SBAR, s & 1);
      TR(6);
      float sc[10];
      {
        const float4 a0 = lds128f(rF + R_SX), b0 = lds128f(rF + R_SX + 1536), c0 = lds128f(rF + R_SX + 3072);
        const float4 a1 = lds128f(rF + R_SX + 512), b1 = lds128f(rF + R_SX + 2048), c1 = lds128f(rF + R_SX + 3584);
        const float2 a2 = lds64f(rF + R_SX + 1024), b2 = lds64f(rF + R_SX + 2560), c2 = lds64f(rF + R_SX + 4096);
        sc[8] = a0.x + b0.x + c0.x; sc[9] = a0.y + b0.y + c0.y; sc[0] = a0.z + b0.z + c0.z; sc[1] = a0.w + b0.w + c0.w;
        sc[2] = a1.x + b1.x + c1.x; sc[3] = a1.y + b1.y + c1.y; sc[4] = a1.z + b1.z + c1.z; sc[5] = a1.w + b1.w + c1.w;
        sc[6] = a2.x + b2.x + c2.x; sc[7] = a2.y + b2.y + c2.y;
      }
      float mx = fmaxf(fmaxf(fmaxf(sc[0], sc[1]), fmaxf(sc[2], sc[3])), fmaxf(fmaxf(sc[4], sc[5]), fmaxf(sc[6], sc[7])));
      mx = fmaxf(mx, fmaxf(sc[8], sc[9]));
      mx = fmaxf(mx, __shfl_xor_sync(~0u, mx, 1));
      const bool vok = mbar_test(OBAR, s & 1);
      mx = fmaxf(mx, __shfl_xor_sync(~0u, mx, 2));
      if (NW1A < NW1) bar_arrive(4, 256);
      const float mo = mx * scl;
      uint32_t pb[5];
#pragma unroll
      for (int j = 0; j < 5; j++) pb[j] = pack2(ex2(fmaf(sc[2 * j], scl, -mo)), ex2(fmaf(sc[2 * j + 1], scl, -mo)));
      if (!vok) mbar_wait(OBAR, s & 1);
      const uint2 m0 = lds64(l8 + R_VS), m1 = lds64(l8 + R_VM), m2 = lds64(l8 + R_VM + 1024);
      const uint32_t ones[4] = {ONES, ONES, ONES, ONES};
      float o[3][4], o2[3][4], sm[4] = {0.f, 0.f, 0.f, 0.f}, sn[4] = {0.f, 0.f, 0.f, 0.f}, so[4] = {0.f, 0.f, 0.f, 0.f};
#pragma unroll
      for (int b = 0; b < 3; b++) {
        o[b][0] = o[b][1] = o[b][2] = o[b][3] = o2[b][0] = o2[b][1] = o2[b][2] = o2[b][3] = 0.f;
        mma16816(o[b], va[b], pb[0], pb[1]);
      }
#pragma unroll
      for (int b = 0; b < 3; b++) mma16816(o2[b], va[b] + 4, pb[2], pb[3]);
      mma1688(o[0], m0.x, m0.y, pb[4]);
      mma1688(o[1], m1.x, m1.y, pb[4]);
      mma1688(o[2], m2.x, m2.y, pb[4]);
      mma16816(sm, ones, pb[0], pb[1]);
      mma16816(sn, ones, pb[2], pb[3]);
      mma1688(so, ONES, ONES, pb[4]);
      wpre(NO_EARLY, NO_MID);
#pragma unroll
      for (int b = 0; b < 3; b++)
        sts64(dst + (b == 0 ? R_QB : (b == 1 ? R_QA : R_O2)), movmat(pack2(o[b][0] + o2[b][0], o[b][1] + o2[b][1])),
              movmat(pack2(o[b][2] + o2[b][2], o[b][3] + o2[b][3])));
      sm[0] += sn[0] + so[0]; sm[1] += sn[1] + so[1];
      if (rF - sb < 64) sts64f(sb + R_MI + 16 + ((rF - sb) >> 1), sm[0], sm[1]);
      wpre(NO_MID, 12);
      TR(7);
      if (two) oproj(std::true_type{}, std::integral_constant<int, 12>{}, wot, rF, woA, woB, sm[0], sm[1], true);
      else oproj(std::false_type{}, std::integral_constant<int, 12>{}, wot, rF, woA, woB, sm[0], sm[1], true);
    }
  };

  GTR(5); GTR(6);
  if (g == 0) {
    window(std::integral_constant<int, 0>{}, std::true_type{});
    GTR(7);
#pragma unroll 1
    for (s = 0; s < NSEG - 1; s++) {
      step(std::integral_constant<int, 0>{}, std::false_type{});
      window(std::integral_constant<int, 0>{}, std::false_type{});
    }
    step(std::integral_constant<int, 0>{}, std::true_type{});
  } else {
    window(std::integral_constant<int, 1>{}, std::true_type{});
#pragma unroll 1
    for (s = 0; s < NSEG - 1; s++) {
      step(std::integral_constant<int, 1>{}, std::false_type{});
      window(std::integral_constant<int, 1>{}, std::false_type{});
    }
    step(std::integral_constant<int, 1>{}, std::true_type{});
  }
  __syncthreads();
  if (tid == 160) {
    fence_async_smem();
    tma_store2(&tmK, sb + R_KT, D0, (NSEG - 1) * LK);
    tma_store2(&tmV, sb + R_VT, D0, (NSEG - 1) * LK);
    bulk_commit();
    bulk_wait0();
    asm volatile("red.relaxed.gpu.global.add.u32 [%0], 1;" ::"l"(&g_segcnt[NSEG - 2]) : "memory");
    asm volatile("red.relaxed.gpu.global.add.u32 [%0], 1;" ::"l"(&g_segcnt[NSEG - 1]) : "memory");
  }
  GTR(8);
  cluster_sync();
}

enum { IT_GATE = 0, IT_QKV = 1, IT_XATT = 2, IT_OUT = 3, IT_BATT = 4, IT_CVT = 5, IT_INIT = 6, IT_END = 7 };
constexpr int C_GATE = 0, C_QKV = 16, C_OB = 32, C_ACC = 48, C_O = 80;
#define T8 10
#define T16 14
#define T32 16
#define XEARLY 11
constexpr int k_nsplit(int t) { return t >= T32 ? 32 : (t >= T16 ? 16 : (t >= T8 ? 8 : 4)); }
constexpr uint32_t mk_item(int ty, int t, int a, int b = 0, int c = 0) { return ty | (t << 3) | (a << 8) | (b << 16) | (c << 24); }
constexpr int part_base(int t) { return t ? part_base(t - 1) + k_nsplit(t - 1) + 1 : 0; }
struct ItemTab { uint32_t v[1280]; uint32_t pb[17]; int n; };
constexpr ItemTab make_items() {
  ItemTab T{};
  int n = 0;
  for (int t = 0; t < 16; t++) T.v[n++] = mk_item(IT_GATE, t, 0);
  for (int t = 0; t < 16; t++) for (int a = 0; a < 5; a++) T.v[n++] = mk_item(IT_QKV, t, a);
  for (int t = 0; t < 32; t++) for (int a = 0; a < 4; a++) T.v[n++] = mk_item(IT_BATT, t, a);
  for (int t = 0; t < 16; t++) for (int a = 0; a < 2; a++) T.v[n++] = mk_item(IT_INIT, t, a);
  auto xatt = [&](int t) { for (int a = 0; a < 16; a++) T.v[n++] = mk_item(IT_XATT, t, a); };
  auto outp = [&](int u) {
    const int ns = k_nsplit(u);
    for (int q = 0; q < ns; q++) for (int a = 0; a < 2; a++) T.v[n++] = mk_item(IT_OUT, u, a, q * 32 / ns, (q + 1) * 32 / ns);
  };
  auto cvt = [&](int v) {
    const int r = k_nsplit(v) == 4 ? 4 : (k_nsplit(v) == 8 ? 2 : 1);
    for (int q = 0; q < 16; q += r) for (int a = 0; a < 2; a++) T.v[n++] = mk_item(IT_CVT, v, a, q, r);
  };
  for (int t = 0; t <= 16; t++) T.pb[t] = part_base(t);
  for (int t = 0; t < XEARLY; t++) {
    xatt(t);
    if (t >= 1) outp(t - 1);
    if (t >= 4) cvt(t - 4);
  }
  for (int t = XEARLY; t < 16; t++) xatt(t);
  for (int t = XEARLY - 1; t < 16; t++) outp(t);
  for (int t = XEARLY - 4; t < 16; t++) cvt(t);
  T.n = n;
  return T;
}
constexpr ItemTab k_items_host = make_items();
constexpr int NITEMS = k_items_host.n;
__constant__ ItemTab c_items = make_items();
__device__ __align__(1024) bf16 g_part[part_base(16) * 128 * DM];

constexpr int AUX_GRID = 132, NST = 7, STG = 32768;
constexpr int A_FULL = NST * STG, A_EMPTY = A_FULL + 64, A_ITEM = A_EMPTY + 64, A_QBAR = A_ITEM + 32, A_QENT = A_QBAR + 128, A_MISC = A_QENT + 256,
              A_SMEM = A_MISC + 64;
static_assert(A_SMEM <= 232448, "smem");
enum { OP_END = 0, OP_O = 1, OP_QKV = 2, OP_OB = 3, OP_PART = 4 };

struct AuxMaps { CUtensorMap xA, wq, wqkv, wo, wob, k, v, oA, oS, obA, obS, qkvS, qkvQ, qkvK, part; };

__device__ __forceinline__ void mbar_wait_long(uint32_t b, uint32_t par) {
  int n = 0;
#pragma unroll 1
  while (!mbar_try(b, par)) { if (++n > (SPIN_MAX << 4)) { g_err = 8; break; } }
}
__device__ __forceinline__ uint64_t mk_desc(uint32_t addr, uint32_t lbo, uint32_t sbo, uint32_t mode) {
  return (uint64_t)((addr & 0x3FFFF) >> 4) | ((uint64_t)(lbo >> 4) << 16) | ((uint64_t)(sbo >> 4) << 32) | ((uint64_t)mode << 62);
}

__global__ void __launch_bounds__(384, 1)
aux_kernel(const __grid_constant__ AuxMaps tm, const bf16* __restrict__ x, const bf16* __restrict__ gate_w, bf16* __restrict__ out) {
  extern __shared__ __align__(1024) unsigned char smem[];
  const uint32_t sb = smem_u32(smem);
  const int tid = threadIdx.x, lane = tid & 31, wid = __shfl_sync(~0u, tid >> 5, 0);
  if (tid == 0) {
    for (int i = 0; i < NST; i++) { mbar_init(sb + A_FULL + i * 8, 1); mbar_init(sb + A_EMPTY + i * 8, 8); }
    for (int i = 0; i < 16; i++) mbar_init(sb + A_QBAR + i * 8, 4);
    asm volatile("fence.mbarrier_init.release.cluster;" ::: "memory");
    sts32(sb + A_MISC, *(volatile uint32_t*)&g_epoch + 1);
  }
  __syncthreads();
  const uint32_t epoch = lds32(sb + A_MISC);
  uint32_t st = 0, ph = 0;
  auto advance = [&]() { if (++st == NST) { st = 0; ph ^= 1; } };

  if (wid >= 8) {
    asm volatile("setmaxnreg.dec.sync.aligned.u32 40;");
    if (wid == 8 && lane == 0) {
      const uint32_t qbase = (epoch - 1) * (uint32_t)(NITEMS + AUX_GRID);
      auto cnt = [&](int c, uint32_t per) -> bool { return (int)(ldg_rlx32(&g_cnt[c * 8]) - epoch * per) >= 0; };
      auto ready = [&](uint32_t item) -> int {
        const int ty = item & 7, t = (item >> 3) & 31, a = (item >> 8) & 255, b = (item >> 17) & 127, n = (((item >> 24) + 1) >> 1) - b;
        int r;
        if (ty == IT_OUT) {
          const int c = C_O + t * 16 + b;
          const bool r0 = cnt(c, 2), r1 = cnt(c + (n > 1), 2), r2 = cnt(c + (n > 2) * 2, 2), r3 = cnt(c + (n > 3) * 3, 2);
          r = r0 ? (r1 ? (r2 ? (r3 ? 4 : 3) : 2) : 1) : 0;
        } else if (ty == IT_XATT) {
          const uint4 v = ldg_rlx128(&g_segcnt[4 * t]);
          const uint32_t e = epoch * 96;
          r = cnt(C_GATE + t, 1) & ((int)(v.x - e) >= 0) & ((int)(v.y - e) >= 0) & ((int)(v.z - e) >= 0) & ((int)(v.w - e) >= 0);
        } else if (ty == IT_BATT) {
          r = cnt(C_GATE + (t >> 1), 1) & cnt(C_QKV + (t >> 1), 10) & cnt(C_QKV + (max(t - 1, 0) >> 1), 10);
        } else {
          r = cnt(ty == IT_INIT ? C_OB + t : C_ACC + 2 * t + (a & 1), ty == IT_INIT ? 8 : 66);
        }
        asm volatile("fence.acquire.gpu; fence.proxy.async.global;" ::: "memory");
        return r;
      };
      uint32_t item = IT_GATE;
      int trail = 0;
      auto slot = [&](uint32_t bytes) -> uint32_t {
        mbar_wait_long(sb + A_EMPTY + st * 8, ph ^ 1);
        sts32(sb + A_ITEM + st * 4, item);
        if (bytes) mbar_expect(sb + A_FULL + st * 8, bytes); else mbar_arrive(sb + A_FULL + st * 8);
        return sb + st * STG;
      };
#pragma unroll 1
      while (true) {
        const uint32_t nidx = atomicAdd(&g_queue, 1u) - qbase;
        const uint32_t nitem = nidx < (uint32_t)NITEMS ? c_items.v[nidx] : (uint32_t)IT_END;
        int rdy = (0x78 >> (nitem & 7)) & 1 ? ready(nitem) : 0;
#pragma unroll 1
        for (; trail; trail--) { slot(0); advance(); }
        item = nitem;
        int k = (item & 7) == IT_OUT ? ((item >> 16) & 255) * 6 : 0;
        const int k1 = (item & 7) == IT_OUT ? (item >> 24) * 6 : (0x01140103001c1401ull >> ((item & 7) * 8)) & 255;
#pragma unroll 1
        for (; k < k1; k++) {
          item = pin(item);
          const int ty = item & 7, t = (item >> 3) & 31, a = (item >> 8) & 255;
          const bool out_ = ty == IT_OUT, gemm1 = ty == IT_QKV || ty == IT_XATT;
          const int dep = out_ ? k / 12 - ((item >> 17) & 127) : (ty == IT_XATT ? (k >= 20) - 1 : ((0x70 >> ty) & 1) - 1);
          if (rdy <= dep || (k == 12 && ty == IT_XATT)) {
            int n = 0;
#pragma unroll 1
            while ((rdy = ready(pin(item))) <= dep) {
              if (++n > SPIN_MAX) { g_err = 7; break; }
              __nanosleep(20);
            }
          }
          const uint32_t fb = sb + A_FULL + st * 8;
          if (out_ || ty == IT_INIT) {
            const uint32_t d = slot(28672);
            tma_load2(d, out_ ? &tm.oA : &tm.obA, k * 32, t * 128, fb);
            tma_load3(d + 8192, out_ ? &tm.wo : &tm.wob, 0, k * 32, a * 5, fb);
          } else if (gemm1 && k < 20) {
            const uint32_t d = slot(32768);
            tma_load2(d, &tm.xA, k * 32, t * 128, fb);
            tma_load3(d + 8192, ty == IT_QKV ? &tm.wqkv : &tm.wq, 0, k * 32, a * 6, fb);
          } else if (gemm1) {
            const uint32_t d = slot(30720);
            tma_load3(d, k < 24 ? &tm.k : &tm.v, 0, (4 * t + (k & 2)) * LK, (2 * a + (k & 1)) * 3, fb);
          } else if (ty == IT_BATT) {
            const uint32_t d = slot(k ? 25600 : 20480);
            tma_load2(d, k ? &tm.qkvK : &tm.qkvQ, k * 640 + a * 160, t * 64 - (k ? 16 : 0), fb);
          } else {
            slot(0);
            mbar_wait_long(sb + A_EMPTY + st * 8, ph);
          }
          advance();
        }
        if ((item & 7) == IT_END) {
          if (nidx == (uint32_t)(NITEMS + AUX_GRID - 1)) g_epoch = epoch;
          break;
        }
        trail = (0x4a >> (item & 7)) & 1 ? 4 : 0;
      }
      asm volatile("griddepcontrol.wait;" ::: "memory");
    } else if ((wid == 9 || wid == 10) && lane == 0) {
      const uint32_t qb = sb + A_QBAR + (wid - 9) * 64, qe = sb + A_QENT + (wid - 9) * 128;
      for (uint32_t e = 0;; e++) {
        mbar_wait_long(qb + (e & 7) * 8, (e >> 3) & 1);
        const uint4 en = lds128(qe + (e & 7) * 16);
        const int op = en.x & 15, sg = (en.x >> 4) & 15, rel = (en.x >> 8) & 15, nb = (en.x >> 12) & 15;
        if (op == OP_END) break;
        const uint32_t src = sb + sg * STG;
        if (op == OP_O) tma_store3(&tm.oS, src, 0, en.y, en.z);
        else if (op == OP_QKV) tma_store3(&tm.qkvS, src, 0, en.y, en.z);
        else if (op == OP_OB) tma_store2(&tm.obS, src, en.z, en.y);
        else { for (int i = 0; i < nb; i++) tma_store3(&tm.part, src + i * 8192, 0, en.y, en.z + i); }
        bulk_commit();
        bulk_wait_read0();
        asm volatile("mbarrier.arrive.shared::cta.b64 _, [%0], %1;" ::"r"(sb + A_EMPTY + sg * 8), "r"(rel) : "memory");
        if (en.w) {
          bulk_wait0();
          asm volatile("red.relaxed.gpu.global.add.u32 [%0], %1;" ::"l"(&g_cnt[((en.w & 0xFFFF) - 1) * 8]), "r"((en.w >> 16) + 1) : "memory");
        }
      }
      bulk_wait0();
    }
  } else {
    asm volatile("setmaxnreg.inc.sync.aligned.u32 232;");
    const int g = wid >> 2, w = wid & 3;
    uint32_t qn = 0;
    auto wait_full = [&]() { mbar_wait_long(sb + A_FULL + st * 8, ph); };
    auto release = [&](uint32_t s_) { if (lane == 0) mbar_arrive(sb + A_EMPTY + s_ * 8); };
    auto take_pair = [&]() -> uint32_t {
      wait_full();
      const uint32_t s0 = st; advance();
      wait_full();
      const uint32_t s1 = st; advance();
      release(g ? s0 : s1);
      return g ? s1 : s0;
    };
    auto push = [&](uint32_t w0, uint32_t w1, uint32_t w2, uint32_t w3) {
      fence_async_smem();
      if (w == 0 && lane == 0) sts128(sb + A_QENT + g * 128 + (qn & 7) * 16, w0, w1, w2, w3);
      __syncwarp();
      if (lane == 0) mbar_arrive(sb + A_QBAR + g * 64 + (qn & 7) * 8);
      qn++;
    };
    const uint32_t stm = (16 * w + (lane & 7) + (lane & 8)) * 128, stx = lane & 7, sth = lane >> 4;
    auto stage_bf16 = [&](uint32_t dst, const float* d, float s0, float s1, int nks = 12) {
#pragma unroll
      for (int ks = 0; ks < nks; ks++)
        stsm4(dst + (ks >> 2) * 8192 + stm + (((2 * (ks & 3) + sth) ^ stx) << 4), pack2(d[8 * ks] * s0, d[8 * ks + 1] * s0), pack2(d[8 * ks + 2] * s1, d[8 * ks + 3] * s1),
              pack2(d[8 * ks + 4] * s0, d[8 * ks + 5] * s0), pack2(d[8 * ks + 6] * s1, d[8 * ks + 7] * s1));
    };
#pragma unroll 1
    while (true) {
      wait_full();
      const uint32_t item = lds32(sb + A_ITEM + st * 4);
      const int ty = item & 7, t = (item >> 3) & 31, a = (item >> 8) & 255;
      if (ty == IT_QKV || ty == IT_XATT) {
        float acc[192] = {};
        uint32_t prev = 0;
#pragma unroll 1
        for (int k = 0; k < 20; k++) {
          if (k) wait_full();
          const uint32_t s_ = sb + st * STG;
          const uint64_t da = mk_desc(s_, 16, 512, 2), db = mk_desc(s_ + 8192 + g * 12288, 4096, 1024, 1);
          wg_fence();
          wgmma_ss192t(acc, da, db, k);
          wgmma_ss192t(acc + 96, da + 256, db, k);
          wgmma_ss192t(acc, da + 2, db + 128, 1);
          wgmma_ss192t(acc + 96, da + 258, db + 128, 1);
          wg_commit();
          if (k) { wg_wait1(); release(prev); }
          prev = st; advance();
        }
        wg_wait0();
        fence_regs<192>(acc);
        release(prev);
        if (ty == IT_QKV) {
#pragma unroll
          for (int q = 0; q < 2; q++) {
            const uint32_t m = take_pair();
            stage_bf16(sb + m * STG, acc + q * 96, 1.f, 1.f);
            push(OP_QKV | (m << 4) | (4 << 8), t * 128 + q * 64, a * 6 + g * 3, q ? C_QKV + t + 1 : 0);
          }
        } else {
          uint32_t qf[24][4];
#pragma unroll
          for (int ks = 23; ks >= 0; ks--)
#pragma unroll
            for (int j = 0; j < 4; j++)
              asm volatile("cvt.rn.bf16x2.f32 %0, %1, %2;" : "=r"(qf[ks][j]) : "f"(acc[8 * ks + 2 * j + 1]), "f"(acc[8 * ks + 2 * j]));
          float sc[2][40] = {};
          uint32_t kst[2];
#pragma unroll
          for (int q = 0; q < 2; q++) {
            kst[q] = take_pair();
            const uint64_t db = mk_desc(sb + kst[q] * STG, 16, 1024, 1);
            wg_fence();
#pragma unroll
            for (int ks = 0; ks < 12; ks++) wgmma_rs80(sc[q], qf[q * 12 + ks], db + (((ks >> 2) * 10240 + (ks & 3) * 32) >> 4), ks);
            wg_commit();
          }
          const int tt = 16 * (w & 1) + (lane >> 2) - 2 * (lane & 3);
          const float* gp = g_gate + t * 128 + 16 * w + (lane >> 2);
          const float gt[4] = {__ldcg(gp), __ldcg(gp + 8), __ldcg(gp + 64), __ldcg(gp + 72)};
          uint32_t pf[2][5][4];
          float rs[2][2];
          auto softmax = [&](const float* s_, uint32_t (&p)[5][4], float* r) {
            constexpr float SCL = 0.07216878364870322f * 1.4426950408889634f;
            float v[20];
#pragma unroll
            for (int i = 0; i < 20; i++) {
              v[i] = w >= 2 ? s_[20 + i] : s_[i];
              if (i >= 4 && 8 * ((i >> 2) - 1) + (i & 1) > tt + ((i & 2) ? 8 : 0)) v[i] = -INFINITY;
            }
            uint32_t pt[5][2];
#pragma unroll
            for (int h = 0; h < 2; h++) {
              float mx = fmaxf(v[2 * h], v[2 * h + 1]);
#pragma unroll
              for (int j = 1; j < 5; j++) mx = fmaxf(mx, fmaxf(v[4 * j + 2 * h], v[4 * j + 2 * h + 1]));
              mx = fmaxf(mx, __shfl_xor_sync(~0u, mx, 1));
              mx = fmaxf(mx, __shfl_xor_sync(~0u, mx, 2));
              const float mo = mx * SCL;
              float sum = 0.f;
#pragma unroll
              for (int j = 0; j < 5; j++) {
                const float e0 = ex2(fmaf(v[4 * j + 2 * h], SCL, -mo)), e1 = ex2(fmaf(v[4 * j + 2 * h + 1], SCL, -mo));
                pt[j][h] = pack2(e0, e1);
                sum += bf_lo(pt[j][h]) + bf_hi(pt[j][h]);
              }
              sum += __shfl_xor_sync(~0u, sum, 1);
              sum += __shfl_xor_sync(~0u, sum, 2);
              r[h] = rcp(sum);
            }
#pragma unroll
            for (int J = 0; J < 10; J++)
#pragma unroll
              for (int h = 0; h < 2; h++) p[J >> 1][(J & 1) * 2 + h] = (J >= 5) == (w >= 2) ? pt[J % 5][h] : 0u;
          };
          wg_wait1();
          fence_regs<40>(sc[0]);
          release(kst[0]);
          softmax(sc[0], pf[0], rs[0]);
#pragma unroll
          for (int q = 0; q < 2; q++) {
            const uint32_t m = take_pair();
            const uint64_t db = mk_desc(sb + m * STG, 10240, 1024, 1);
            float o[96] = {};
            wg_fence();
#pragma unroll
            for (int ks = 0; ks < 5; ks++) wgmma_rs192t(o, pf[q][ks], db + ks * 128, ks);
            wg_commit();
            if (q == 0) {
              wg_wait1();
              fence_regs<40>(sc[1]);
              release(kst[1]);
              softmax(sc[1], pf[1], rs[1]);
            }
            wg_wait0();
            fence_regs<96>(o);
            bar_sync(1 + g, 128);
            stage_bf16(sb + m * STG, o, rs[q][0] * gt[2 * q], rs[q][1] * gt[2 * q + 1]);
            push(OP_O | (m << 4) | (4 << 8), t * 128 + q * 64, a * 6 + g * 3, q ? C_O + t * 16 + a + 1 : 0);
          }
        }
      } else if (ty == IT_OUT || ty == IT_INIT) {
        float acc[160] = {};
        const int hb = (item >> 16) & 255, nh = (item >> 24) - hb, nk = ty == IT_OUT ? nh * 6 : 20, jh = a & 1;
        const uint32_t ln = pin(lane), ao = (g * 64 + 16 * w + (ln & 15)) * 64 + (((ln >> 4) ^ ((ln >> 1) & 3)) << 4);
#pragma unroll 1
        for (int k = 0; k < nk; k += 2) {
          uint32_t af[4][4], sg[2];
#pragma unroll
          for (int e = 0; e < 2; e++) {
            if (k + e) wait_full();
            sg[e] = st;
            ldsm4(af[2 * e], sb + st * STG + ao);
            ldsm4(af[2 * e + 1], sb + st * STG + (ao ^ 32));
            advance();
          }
          wg_fence();
#pragma unroll
          for (int e = 0; e < 4; e++) {
            const uint64_t db = mk_desc(sb + sg[e >> 1] * STG + 8192 + (e & 1) * 2048, 4096, 1024, 1);
            wgmma_rs192t(acc, af[e], db, 1);
            wgmma_rs128t(acc + 96, af[e], db + 768, 1);
          }
          wg_commit();
          wg_wait0();
          release(sg[0]); release(sg[1]);
        }
        fence_regs<160>(acc);
        const uint32_t row = (ty == IT_OUT ? c_items.pb[t] + hb / nh : c_items.pb[t + 1] - 1) * 128 + g * 64;
#pragma unroll
        for (int q = 0; q < 2; q++) {
          const uint32_t m = take_pair();
          stage_bf16(sb + m * STG, acc + q * 96, 1.f, 1.f, q ? 8 : 12);
          push(OP_PART | (m << 4) | (4 << 8) | ((3 - q) << 12), row, jh * 5 + q * 3, q ? (C_ACC + 2 * t + jh + 1) | ((ty == IT_OUT ? nh - 1 : 0) << 16) : 0);
        }
      } else if (ty == IT_BATT) {
        const uint32_t sq = st; advance();
        wait_full();
        const uint32_t sk = st; advance();
        wait_full();
        const uint32_t sv = st; advance();
        const int h = tid & 7;
#pragma unroll 1
        for (int p = 0; p < 2; p++) {
          const int tok = (tid >> 3) + 32 * p, pos = t * 64 + tok;
          const uint32_t qa = sb + sq * STG + tok * 320 + h * 40, ka = sb + sk * STG + (tok + 16) * 320 + h * 40, va = sb + sv * STG + (tok + 16) * 320 + h * 40;
          const float gt = __ldcg(g_gate + 2048 + pos);
          float q[20], l[8];
#pragma unroll
          for (int i = 0; i < 5; i++) { const uint2 u = lds64(qa + i * 8); q[4 * i] = bf_lo(u.x); q[4 * i + 1] = bf_hi(u.x); q[4 * i + 2] = bf_lo(u.y); q[4 * i + 3] = bf_hi(u.y); }
          float mx = -INFINITY;
#pragma unroll
          for (int j = 0; j < 8; j++) {
            float s0 = 0.f, s1 = 0.f;
#pragma unroll
            for (int i = 0; i < 5; i++) {
              const uint2 u = lds64(ka - j * 640 + i * 8);
              s0 = fmaf(q[4 * i], bf_lo(u.x), s0); s1 = fmaf(q[4 * i + 1], bf_hi(u.x), s1);
              s0 = fmaf(q[4 * i + 2], bf_lo(u.y), s0); s1 = fmaf(q[4 * i + 3], bf_hi(u.y), s1);
            }
            l[j] = pos - 2 * j >= 0 ? s0 + s1 : -INFINITY;
            mx = fmaxf(mx, l[j]);
          }
          constexpr float SCL = 0.22360679774997896f * 1.4426950408889634f;
          const float mo = mx * SCL;
          float sum = 0.f;
#pragma unroll
          for (int j = 0; j < 8; j++) { l[j] = ex2(fmaf(l[j], SCL, -mo)); sum += l[j]; }
          const float r = gt * rcp(sum);
#pragma unroll
          for (int i = 0; i < 20; i++) q[i] = 0.f;
#pragma unroll
          for (int j = 0; j < 8; j++) {
#pragma unroll
            for (int i = 0; i < 5; i++) {
              const uint2 u = lds64(va - j * 640 + i * 8);
              q[4 * i] = fmaf(l[j], bf_lo(u.x), q[4 * i]); q[4 * i + 1] = fmaf(l[j], bf_hi(u.x), q[4 * i + 1]);
              q[4 * i + 2] = fmaf(l[j], bf_lo(u.y), q[4 * i + 2]); q[4 * i + 3] = fmaf(l[j], bf_hi(u.y), q[4 * i + 3]);
            }
          }
#pragma unroll
          for (int i = 0; i < 5; i++) sts64(qa + i * 8, pack2(q[4 * i] * r, q[4 * i + 1] * r), pack2(q[4 * i + 2] * r, q[4 * i + 3] * r));
        }
        __syncwarp();
        release(sk); release(sv);
        fence_async_smem();
        bar_sync(3, 256);
        if (g == 0) push(OP_OB | (sq << 4) | (8 << 8), t * 64, a * 160, C_OB + (t >> 1) + 1);
      } else if (ty == IT_GATE) {
        release(st); advance();
        uint4 gw[3];
#pragma unroll
        for (int i = 0; i < 3; i++) gw[i] = (i < 2 || lane < 16) ? __ldg((const uint4*)gate_w + lane + 32 * i) : make_uint4(0, 0, 0, 0);
#pragma unroll 4
        for (int r = 0; r < 16; r++) {
          const int row = t * 128 + wid * 16 + r;
          float s_ = 0.f;
#pragma unroll
          for (int i = 0; i < 3; i++) {
            const uint4 v = (i < 2 || lane < 16) ? __ldg((const uint4*)(x + (size_t)row * DM) + lane + 32 * i) : make_uint4(0, 0, 0, 0);
            const uint32_t p0 = hmul2(v.x, gw[i].x), p1 = hmul2(v.y, gw[i].y), p2 = hmul2(v.z, gw[i].z), p3 = hmul2(v.w, gw[i].w);
            s_ += ((bf_lo(p0) + bf_hi(p0)) + (bf_lo(p1) + bf_hi(p1))) + ((bf_lo(p2) + bf_hi(p2)) + (bf_lo(p3) + bf_hi(p3)));
          }
#pragma unroll
          for (int o = 16; o; o >>= 1) s_ += __shfl_xor_sync(~0u, s_, o);
          const float z = bf_lo(pack2(s_, 0.f));
          const float gv = bf_lo(pack2(1.f / (1.f + __expf(-z)), 0.f));
          if (lane == 0) { g_gate[row] = gv; g_gate[2048 + row] = bf_lo(pack2(1.f - gv, 0.f)); }
        }
        __threadfence();
        bar_sync(3, 256);
        if (tid == 0) asm volatile("red.release.gpu.global.add.u32 [%0], 1;" ::"l"(&g_cnt[(C_GATE + t) * 8]) : "memory");
      } else if (ty == IT_CVT) {
        release(st); advance();
        const int r0 = ((item >> 16) & 255) * 8, lim = (item >> 24) * 640, np = c_items.pb[t + 1] - c_items.pb[t];
        const int td = pin(tid);
        auto add_parts = [&](auto NI_, auto U0_) {
          constexpr int NI = decltype(NI_)::value, U0 = decltype(U0_)::value;
          uint32_t off[NI];
          float sum[NI][4];
          const char* src = (const char*)(g_part + ((size_t)c_items.pb[t] * 128 + r0) * DM + a * 320);
#pragma unroll
          for (int i = 0; i < NI; i++) { const int e = min(td + i * 256, lim - 1); off[i] = (e / 80) * (DM * 2) + (e % 80) * 8; }
          auto round = [&](auto U_, bool first) {
            constexpr int U = decltype(U_)::value;
            uint2 v[NI][U];
#pragma unroll
            for (int i = 0; i < NI; i++) {
              const char* q0 = src + off[i];
#pragma unroll
              for (int q = 0; q < U; q++) v[i][q] = __ldcg((const uint2*)(q0 + q * (128 * DM * 2)));
            }
            src += U * (128 * DM * 2);
#pragma unroll
            for (int i = 0; i < NI; i++) {
              if (first) sum[i][0] = sum[i][1] = sum[i][2] = sum[i][3] = 0.f;
#pragma unroll
              for (int q = 0; q < U; q++) {
                sum[i][0] += bf_lo(v[i][q].x); sum[i][1] += bf_hi(v[i][q].x); sum[i][2] += bf_lo(v[i][q].y); sum[i][3] += bf_hi(v[i][q].y);
              }
            }
          };
          round(U0_, true);
          if (U0 == 9) {
#pragma unroll 1
            for (int q = U0; q < np; q += 8) round(std::integral_constant<int, 8>{}, false);
          }
          char* dst = (char*)(out + (t * 128 + r0) * DM + a * 320);
#pragma unroll
          for (int i = 0; i < NI; i++)
            if (td + i * 256 < lim) *(uint2*)(dst + off[i]) = make_uint2(pack2(sum[i][0], sum[i][1]), pack2(sum[i][2], sum[i][3]));
        };
        if (np == 5) add_parts(std::integral_constant<int, 10>{}, std::integral_constant<int, 5>{});
        else add_parts(std::integral_constant<int, 5>{}, std::integral_constant<int, 9>{});
      } else {
        release(st);
        push(OP_END, 0, 0, 0);
        break;
      }
    }
  }
}

typedef CUresult (*EncFn)(CUtensorMap*, CUtensorMapDataType, cuuint32_t, void*, const cuuint64_t*, const cuuint64_t*, const cuuint32_t*,
                          const cuuint32_t*, CUtensorMapInterleave, CUtensorMapSwizzle, CUtensorMapL2promotion, CUtensorMapFloatOOBfill);

#define PROMO CU_TENSOR_MAP_L2_PROMOTION_L2_128B
void make_map(EncFn enc, CUtensorMap* tm, const void* base, int rank, const cuuint64_t* dims, const cuuint64_t* strides, const cuuint32_t* box,
              CUtensorMapSwizzle sw = CU_TENSOR_MAP_SWIZZLE_128B, CUtensorMapDataType dt = CU_TENSOR_MAP_DATA_TYPE_BFLOAT16) {
  const cuuint32_t es[5] = {1, 1, 1, 1, 1};
  enc(tm, dt, rank, const_cast<void*>(base), dims, strides, box, es, CU_TENSOR_MAP_INTERLEAVE_NONE, sw, PROMO,
      CU_TENSOR_MAP_FLOAT_OOB_FILL_NONE);
}
void map_blk(EncFn enc, CUtensorMap* tm, const void* base, int rows, int cols, int brows, int bblk) {
  const cuuint64_t d[3] = {64, (cuuint64_t)rows, (cuuint64_t)cols / 64}, st[2] = {(cuuint64_t)cols * 2, 128};
  const cuuint32_t b[3] = {64, (cuuint32_t)brows, (cuuint32_t)bblk};
  make_map(enc, tm, base, 3, d, st, b);
}
void map_2d(EncFn enc, CUtensorMap* tm, const void* base, int rows, int cols, int brows, int bcols, CUtensorMapSwizzle sw) {
  const cuuint64_t d[2] = {(cuuint64_t)cols, (cuuint64_t)rows}, st[1] = {(cuuint64_t)cols * 2};
  const cuuint32_t b[2] = {(cuuint32_t)bcols, (cuuint32_t)brows};
  make_map(enc, tm, base, 2, d, st, b, sw);
}

}

extern "C" void kernel_launch(void* const* d_in, const int* in_sizes, int n_in, void* d_out, int out_size) {
  const bf16* x = (const bf16*)d_in[0];
  const bf16* mem0 = (const bf16*)d_in[1];
  const bf16* Wq = (const bf16*)d_in[2];
  const bf16* Wk = (const bf16*)d_in[3];
  const bf16* Wv = (const bf16*)d_in[4];
  const bf16* Wo = (const bf16*)d_in[5];
  const bf16* wqkv = (const bf16*)d_in[8];
  const bf16* wob = (const bf16*)d_in[9];
  const bf16* gate_w = (const bf16*)d_in[10];
  static EncFn enc = nullptr;
  static void *pK = nullptr, *pV = nullptr, *pO = nullptr, *pQ = nullptr, *pB = nullptr, *pA = nullptr;
  if (!enc) {
    void* fn = nullptr;
    cudaDriverEntryPointQueryResult qr;
    cudaGetDriverEntryPoint("cuTensorMapEncodeTiled", &fn, cudaEnableDefault, &qr);
    enc = (EncFn)fn;
    cudaGetSymbolAddress(&pK, g_K);
    cudaGetSymbolAddress(&pV, g_V);
    cudaGetSymbolAddress(&pO, g_O);
    cudaGetSymbolAddress(&pQ, g_qkv);
    cudaGetSymbolAddress(&pB, g_Ob);
    cudaGetSymbolAddress(&pA, g_part);
    cudaFuncSetAttribute(rec_kernel, cudaFuncAttributeMaxDynamicSharedMemorySize, R_SMEM_ALLOC);
    cudaFuncSetAttribute(aux_kernel, cudaFuncAttributeMaxDynamicSharedMemorySize, A_SMEM);
  }
  CUtensorMap tmX, tmK, tmV, tmWq, tmWq2, tmWk, tmWv, tmWo;
  map_2d(enc, &tmWq, Wq, DM, HD, 144, 64, CU_TENSOR_MAP_SWIZZLE_128B);
  map_2d(enc, &tmWq2, Wq, DM, HD, 32, 64, CU_TENSOR_MAP_SWIZZLE_128B);
  map_2d(enc, &tmWk, Wk, DM, HD, 128, 64, CU_TENSOR_MAP_SWIZZLE_128B);
  map_2d(enc, &tmWv, Wv, DM, HD, 128, 64, CU_TENSOR_MAP_SWIZZLE_128B);
  {
    const cuuint64_t d[3] = {32, HD, 20}, st[2] = {DM * 2, 64};
    const cuuint32_t b[3] = {32, 64, 7};
    make_map(enc, &tmWo, Wo, 3, d, st, b, CU_TENSOR_MAP_SWIZZLE_64B);
  }
  map_blk(enc, &tmX, x, S_TOK, DM, 32, 10);
  map_2d(enc, &tmK, pK, NSEG * LK, HD, LK, 64, CU_TENSOR_MAP_SWIZZLE_128B);
  map_2d(enc, &tmV, pV, NSEG * LK, HD, LK, 64, CU_TENSOR_MAP_SWIZZLE_128B);
  AuxMaps am;
  map_2d(enc, &am.xA, x, S_TOK, DM, 128, 32, CU_TENSOR_MAP_SWIZZLE_64B);
  map_blk(enc, &am.wq, Wq, DM, HD, 32, 6);
  map_blk(enc, &am.wqkv, wqkv, DM, 3 * DM, 32, 6);
  map_blk(enc, &am.wo, Wo, HD, DM, 32, 5);
  map_blk(enc, &am.wob, wob, DM, DM, 32, 5);
  map_blk(enc, &am.k, pK, NSEG * LK, HD, 80, 3);
  map_blk(enc, &am.v, pV, NSEG * LK, HD, 80, 3);
  map_2d(enc, &am.oA, pO, S_TOK, HD, 128, 32, CU_TENSOR_MAP_SWIZZLE_64B);
  map_blk(enc, &am.oS, pO, S_TOK, HD, 64, 3);
  map_2d(enc, &am.obA, pB, S_TOK, DM, 128, 32, CU_TENSOR_MAP_SWIZZLE_64B);
  map_2d(enc, &am.obS, pB, S_TOK, DM, 64, 160, CU_TENSOR_MAP_SWIZZLE_NONE);
  map_blk(enc, &am.qkvS, pQ, S_TOK, 3 * DM, 64, 3);
  map_2d(enc, &am.qkvQ, pQ, S_TOK, 3 * DM, 64, 160, CU_TENSOR_MAP_SWIZZLE_NONE);
  map_2d(enc, &am.qkvK, pQ, S_TOK, 3 * DM, 80, 160, CU_TENSOR_MAP_SWIZZLE_NONE);
  map_blk(enc, &am.part, pA, part_base(16) * 128, DM, 64, 1);
  rec_kernel<<<96, 256, R_SMEM_ALLOC, cudaStreamPerThread>>>(tmX, tmK, tmV, tmWq, tmWq2, tmWk, tmWv, tmWo, mem0, Wq, Wo, x);
  cudaLaunchConfig_t cfg = {};
  cfg.gridDim = dim3(AUX_GRID); cfg.blockDim = dim3(384); cfg.dynamicSmemBytes = A_SMEM; cfg.stream = cudaStreamPerThread;
  cudaLaunchAttribute at[1];
  at[0].id = cudaLaunchAttributeProgrammaticStreamSerialization;
  at[0].val.programmaticStreamSerializationAllowed = 1;
  cfg.attrs = at;
  cfg.numAttrs = 1;
  cudaLaunchKernelEx(&cfg, aux_kernel, am, x, gate_w, (bf16*)d_out);
}
```

```cpp
#include <cuda_runtime.h>
#include <cuda_bf16.h>
#include <cuda.h>
#include <stdint.h>
#include <type_traits>

typedef __nv_bfloat16 bf16;

namespace {

constexpr int S_TOK = 2048, DM = 640, NH = 32, DH = 192, HD = NH * DH, SEG = 32, NSEG = 64, MT = 8, LK = 40;
constexpr int SPIN_MAX = 1 << 20;

#define RB_LINE 384
constexpr int RB_SIZE = 160 * RB_LINE;
__device__ __align__(4096) unsigned char g_red[4 * RB_SIZE];
__device__ unsigned long long g_rec[96];
__device__ uint32_t g_epoch;
__device__ uint32_t g_err;
__device__ __align__(16) uint32_t g_segcnt[NSEG];
__device__ __align__(1024) bf16 g_K[NSEG * LK * HD];
__device__ __align__(1024) bf16 g_V[NSEG * LK * HD];
__device__ __align__(1024) bf16 g_O[S_TOK * HD];
__device__ __align__(1024) bf16 g_qkv[S_TOK * 3 * DM];
__device__ __align__(1024) bf16 g_Ob[S_TOK * DM];
__device__ float g_gate[2 * S_TOK];
__device__ uint32_t g_cnt[512 * 8];
__device__ __align__(128) uint32_t g_queue[3 * 32];
__device__ uint32_t g_prog;
#define GTR(i) do {} while (0)
#define GTA(i) do {} while (0)

__device__ __forceinline__ uint32_t smem_u32(const void* p) { return (uint32_t)__cvta_generic_to_shared(p); }
__device__ __forceinline__ uint32_t clk32() { uint32_t t; asm volatile("mov.u32 %0, %%clock;" : "=r"(t)::"memory"); return t; }
__device__ __forceinline__ uint32_t mapa(uint32_t a, uint32_t r) { uint32_t o; asm("mapa.shared::cluster.u32 %0, %1, %2;" : "=r"(o) : "r"(a), "r"(r)); return o; }
__device__ __forceinline__ void mbar_init(uint32_t b, uint32_t c) { asm volatile("mbarrier.init.shared::cta.b64 [%0], %1;" ::"r"(b), "r"(c) : "memory"); }
__device__ __forceinline__ void mbar_expect(uint32_t b, uint32_t bytes) { asm volatile("mbarrier.arrive.expect_tx.shared::cta.b64 _, [%0], %1;" ::"r"(b), "r"(bytes) : "memory"); }
__device__ __forceinline__ void mbar_arrive(uint32_t b) { asm volatile("mbarrier.arrive.shared::cta.b64 _, [%0];" ::"r"(b) : "memory"); }
__device__ __forceinline__ bool mbar_try(uint32_t b, uint32_t par) {
  uint32_t p;
  asm volatile("{.reg .pred p; mbarrier.try_wait.parity.shared::cta.b64 p, [%1], %2; selp.u32 %0,1,0,p;}" : "=r"(p) : "r"(b), "r"(par) : "memory");
  return p;
}
__device__ __forceinline__ bool mbar_test(uint32_t b, uint32_t par) {
  uint32_t p;
  asm volatile("{.reg .pred p; mbarrier.test_wait.parity.shared::cta.b64 p, [%1], %2; selp.u32 %0,1,0,p;}" : "=r"(p) : "r"(b), "r"(par) : "memory");
  return p;
}
__device__ __forceinline__ bool mbar_try_cl(uint32_t b, uint32_t par) {
  uint32_t p;
  asm volatile("{.reg .pred p; mbarrier.try_wait.parity.acquire.cluster.shared::cta.b64 p, [%1], %2; selp.u32 %0,1,0,p;}" : "=r"(p) : "r"(b), "r"(par) : "memory");
  return p;
}
__device__ __forceinline__ void mbar_wait(uint32_t b, uint32_t par) {
  int n = 0;
#pragma unroll 1
  while (!mbar_try(b, par)) { if (++n > SPIN_MAX) { g_err = 1; break; } }
}
__device__ __forceinline__ void mbar_wait_cl(uint32_t b, uint32_t par) {
  int n = 0;
#pragma unroll 1
  while (!mbar_try_cl(b, par)) { if (++n > SPIN_MAX) { g_err = 2; break; } }
}
__device__ __forceinline__ void cluster_sync() { asm volatile("barrier.cluster.arrive.release.aligned; barrier.cluster.wait.acquire.aligned;" ::: "memory"); }
__device__ __forceinline__ void bar_sync(int id, int n) { asm volatile("bar.sync %0, %1;" ::"r"(id), "r"(n) : "memory"); }
__device__ __forceinline__ void bar_arrive(int id, int n) { asm volatile("bar.arrive %0, %1;" ::"r"(id), "r"(n) : "memory"); }
__device__ __forceinline__ void fence_async_smem() { asm volatile("fence.proxy.async.shared::cta;" ::: "memory"); }
__device__ __forceinline__ void ldsm4(uint32_t* r, uint32_t a) {
  asm volatile("ldmatrix.sync.aligned.m8n8.x4.shared.b16 {%0,%1,%2,%3}, [%4];" : "=r"(r[0]), "=r"(r[1]), "=r"(r[2]), "=r"(r[3]) : "r"(a) : "memory");
}
__device__ __forceinline__ void ldsm4t(uint32_t* r, uint32_t a) {
  asm volatile("ldmatrix.sync.aligned.m8n8.x4.trans.shared.b16 {%0,%1,%2,%3}, [%4];" : "=r"(r[0]), "=r"(r[1]), "=r"(r[2]), "=r"(r[3]) : "r"(a) : "memory");
}
__device__ __forceinline__ void ldsm2t(uint32_t* r, uint32_t a) {
  asm volatile("ldmatrix.sync.aligned.m8n8.x2.trans.shared.b16 {%0,%1}, [%2];" : "=r"(r[0]), "=r"(r[1]) : "r"(a) : "memory");
}
__device__ __forceinline__ void stsm4t(uint32_t a, uint32_t r0, uint32_t r1, uint32_t r2, uint32_t r3) {
  asm volatile("stmatrix.sync.aligned.m8n8.x4.trans.shared.b16 [%0], {%1,%2,%3,%4};" ::"r"(a), "r"(r0), "r"(r1), "r"(r2), "r"(r3) : "memory");
}
__device__ __forceinline__ void stsm2t(uint32_t a, uint32_t r0, uint32_t r1) {
  asm volatile("stmatrix.sync.aligned.m8n8.x2.trans.shared.b16 [%0], {%1,%2};" ::"r"(a), "r"(r0), "r"(r1) : "memory");
}
__device__ __forceinline__ uint32_t movmat(uint32_t a) { uint32_t d; asm volatile("movmatrix.sync.aligned.m8n8.trans.b16 %0, %1;" : "=r"(d) : "r"(a)); return d; }
__device__ __forceinline__ void mma16816(float* d, const uint32_t* a, uint32_t b0, uint32_t b1) {
  asm volatile("mma.sync.aligned.m16n8k16.row.col.f32.bf16.bf16.f32 {%0,%1,%2,%3}, {%4,%5,%6,%7}, {%8,%9}, {%0,%1,%2,%3};"
               : "+f"(d[0]), "+f"(d[1]), "+f"(d[2]), "+f"(d[3]) : "r"(a[0]), "r"(a[1]), "r"(a[2]), "r"(a[3]), "r"(b0), "r"(b1));
}
__device__ __forceinline__ void mma1688(float* d, uint32_t a0, uint32_t a1, uint32_t b0) {
  asm volatile("mma.sync.aligned.m16n8k8.row.col.f32.bf16.bf16.f32 {%0,%1,%2,%3}, {%4,%5}, {%6}, {%0,%1,%2,%3};"
               : "+f"(d[0]), "+f"(d[1]), "+f"(d[2]), "+f"(d[3]) : "r"(a0), "r"(a1), "r"(b0));
}
__device__ __forceinline__ uint32_t pack2(float lo, float hi) { uint32_t r; asm("cvt.rn.bf16x2.f32 %0, %1, %2;" : "=r"(r) : "f"(hi), "f"(lo)); return r; }
__device__ __forceinline__ float bf_lo(uint32_t w) { return __uint_as_float(w << 16); }
__device__ __forceinline__ float bf_hi(uint32_t w) { return __uint_as_float(w & 0xffff0000u); }
__device__ __forceinline__ float ex2(float x) { float y; asm("ex2.approx.ftz.f32 %0, %1;" : "=f"(y) : "f"(x)); return y; }
__device__ __forceinline__ void sts128(uint32_t a, uint32_t x, uint32_t y, uint32_t z, uint32_t w) { asm volatile("st.shared.v4.b32 [%0], {%1,%2,%3,%4};" ::"r"(a), "r"(x), "r"(y), "r"(z), "r"(w) : "memory"); }
__device__ __forceinline__ void sts128f(uint32_t a, float x, float y, float z, float w) { asm volatile("st.shared.v4.f32 [%0], {%1,%2,%3,%4};" ::"r"(a), "f"(x), "f"(y), "f"(z), "f"(w) : "memory"); }
__device__ __forceinline__ void sts64f(uint32_t a, float x, float y) { asm volatile("st.shared.v2.f32 [%0], {%1,%2};" ::"r"(a), "f"(x), "f"(y) : "memory"); }
__device__ __forceinline__ void sts32(uint32_t a, uint32_t x) { asm volatile("st.shared.b32 [%0], %1;" ::"r"(a), "r"(x) : "memory"); }
__device__ __forceinline__ void smax32(uint32_t a, uint32_t x) { asm volatile("red.shared.max.u32 [%0], %1;" ::"r"(a), "r"(x) : "memory"); }
__device__ __forceinline__ uint32_t lds32(uint32_t a) { uint32_t v; asm volatile("ld.shared.b32 %0, [%1];" : "=r"(v) : "r"(a) : "memory"); return v; }
__device__ __forceinline__ float4 lds128f(uint32_t a) { float4 v; asm volatile("ld.shared.v4.f32 {%0,%1,%2,%3}, [%4];" : "=f"(v.x), "=f"(v.y), "=f"(v.z), "=f"(v.w) : "r"(a) : "memory"); return v; }
__device__ __forceinline__ uint4 lds128(uint32_t a) { uint4 v; asm volatile("ld.shared.v4.b32 {%0,%1,%2,%3}, [%4];" : "=r"(v.x), "=r"(v.y), "=r"(v.z), "=r"(v.w) : "r"(a) : "memory"); return v; }
__device__ __forceinline__ float2 lds64f(uint32_t a) { float2 v; asm volatile("ld.shared.v2.f32 {%0,%1}, [%2];" : "=f"(v.x), "=f"(v.y) : "r"(a) : "memory"); return v; }
__device__ __forceinline__ void st_async2(uint32_t a, uint32_t x, uint32_t y, uint32_t bar) {
  asm volatile("st.async.weak.shared::cluster.mbarrier::complete_tx::bytes.v2.b32 [%0], {%1,%2}, [%3];" ::"r"(a), "r"(x), "r"(y), "r"(bar) : "memory");
}
__device__ __forceinline__ void st_async4(uint32_t a, uint32_t x, uint32_t y, uint32_t z, uint32_t w, uint32_t bar) {
  asm volatile("st.async.weak.shared::cluster.mbarrier::complete_tx::bytes.v4.b32 [%0], {%1,%2,%3,%4}, [%5];" ::"r"(a), "r"(x), "r"(y), "r"(z), "r"(w), "r"(bar) : "memory");
}
__device__ __forceinline__ void sts64(uint32_t a, uint32_t x, uint32_t y) { asm volatile("st.shared.v2.b32 [%0], {%1,%2};" ::"r"(a), "r"(x), "r"(y) : "memory"); }
__device__ __forceinline__ bool bar_red_or(int id, int n, bool q) {
  uint32_t r;
  asm volatile("{.reg .pred p, q; setp.ne.u32 q, %3, 0; barrier.cta.red.or.aligned.pred p, %1, %2, q; selp.u32 %0,1,0,p;}" : "=r"(r) : "r"(id), "r"(n), "r"((uint32_t)q) : "memory");
  return r;
}
__device__ __forceinline__ float rcp(float x) { float y; asm("rcp.approx.ftz.f32 %0, %1;" : "=f"(y) : "f"(x)); return y; }
__device__ __forceinline__ uint32_t hadd2(uint32_t a, uint32_t b) { uint32_t r; asm("add.rn.bf16x2 %0, %1, %2;" : "=r"(r) : "r"(a), "r"(b)); return r; }
__device__ __forceinline__ uint32_t pin(uint32_t v) { asm volatile("" : "+r"(v)); return v; }
template <int ID> __device__ __forceinline__ void sched_fence_(uint32_t a) {
  asm volatile("{.reg .pred p;\nsetp.eq.u32 p, %0, %1;\nSF: @p pmevent 0;\n@p bra.uni SF;}" ::"r"(a), "n"(0x40000000 + ID) : "memory");
}
#define sched_fence(a) sched_fence_<__LINE__>(a)
__device__ __forceinline__ bool elect() {
  uint32_t p;
  asm volatile("{.reg .pred p; elect.sync _|p, 0xffffffff; selp.u32 %0,1,0,p;}" : "=r"(p));
  return p;
}
__device__ __forceinline__ uint32_t opaque(uint32_t v) { return __shfl_sync(~0u, v, threadIdx.x & 31); }
__device__ __forceinline__ uint4 ldg_rlx128(const void* p) {
  uint4 v; asm volatile("ld.relaxed.gpu.global.v4.b32 {%0,%1,%2,%3}, [%4];" : "=r"(v.x), "=r"(v.y), "=r"(v.z), "=r"(v.w) : "l"(p) : "memory"); return v;
}
__device__ __forceinline__ uint2 ldg_rlx64(const void* p) {
  uint2 v; asm volatile("{.reg .b64 t; ld.relaxed.gpu.global.b64 t, [%2]; mov.b64 {%0,%1}, t;}" : "=r"(v.x), "=r"(v.y) : "l"(p) : "memory"); return v;
}
__device__ __forceinline__ uint32_t hmaxabs2(uint32_t a, uint32_t b) { uint32_t r; asm("max.xorsign.abs.bf16x2 %0, %1, %2;" : "=r"(r) : "r"(a), "r"(b)); return r; }
__device__ __forceinline__ uint32_t ldg_rlx32(const void* p) {
  uint32_t v; asm volatile("ld.relaxed.gpu.global.b32 %0, [%1];" : "=r"(v) : "l"(p) : "memory"); return v;
}
__device__ __forceinline__ void spin_until(uint32_t t0, int d) {
#pragma unroll 1
  while ((int)(clk32() - t0) < d) {}
}
__device__ __forceinline__ void stg_rlx64(void* p, uint32_t a, uint32_t b) {
  asm volatile("{.reg .b64 t; mov.b64 t, {%1,%2}; st.relaxed.gpu.global.b64 [%0], t;}" ::"l"(p), "r"(a), "r"(b) : "memory");
}
__device__ __forceinline__ uint32_t ldg_acq32(const void* p) { uint32_t v; asm volatile("ld.acquire.gpu.global.b32 %0, [%1];" : "=r"(v) : "l"(p) : "memory"); return v; }
__device__ __forceinline__ void stg_rel32(void* p, uint32_t v) { asm volatile("st.release.gpu.global.b32 [%0], %1;" ::"l"(p), "r"(v) : "memory"); }
__device__ __forceinline__ void cp_async16(uint32_t dst, const void* src) { asm volatile("cp.async.cg.shared.global [%0], [%1], 16;" ::"r"(dst), "l"(src) : "memory"); }
__device__ __forceinline__ void cp_async_wait_all() { asm volatile("cp.async.wait_all;" ::: "memory"); }
__device__ __forceinline__ void prefetch_l2(const void* p) { asm volatile("prefetch.global.L2 [%0];" ::"l"(p)); }
__device__ __forceinline__ void tma_load3(uint32_t dst, const CUtensorMap* tm, int c0, int c1, int c2, uint32_t bar) {
  asm volatile("cp.async.bulk.tensor.3d.shared::cluster.global.mbarrier::complete_tx::bytes [%0], [%1, {%3,%4,%5}], [%2];"
               ::"r"(dst), "l"(tm), "r"(bar), "r"(c0), "r"(c1), "r"(c2) : "memory");
}
__device__ __forceinline__ void tma_load2(uint32_t dst, const CUtensorMap* tm, int c0, int c1, uint32_t bar) {
  asm volatile("cp.async.bulk.tensor.2d.shared::cluster.global.mbarrier::complete_tx::bytes [%0], [%1, {%3,%4}], [%2];"
               ::"r"(dst), "l"(tm), "r"(bar), "r"(c0), "r"(c1) : "memory");
}
__device__ __forceinline__ void bulk_load(uint32_t dst, const void* src, uint32_t bytes, uint32_t bar) {
  asm volatile("cp.async.bulk.shared::cluster.global.mbarrier::complete_tx::bytes [%0], [%1], %2, [%3];" ::"r"(dst), "l"(src), "r"(bytes), "r"(bar) : "memory");
}
__device__ __forceinline__ void prefetch_map(const CUtensorMap* tm) { asm volatile("prefetch.tensormap [%0];" ::"l"(tm) : "memory"); }
__device__ __forceinline__ void tma_store2(const CUtensorMap* tm, uint32_t src, int c0, int c1) {
  asm volatile("cp.async.bulk.tensor.2d.global.shared::cta.bulk_group [%0, {%2,%3}], [%1];" ::"l"(tm), "r"(src), "r"(c0), "r"(c1) : "memory");
}
__device__ __forceinline__ void bulk_commit() { asm volatile("cp.async.bulk.commit_group;" ::: "memory"); }
__device__ __forceinline__ void bulk_wait0() { asm volatile("cp.async.bulk.wait_group 0;" ::: "memory"); }
__device__ __forceinline__ void bulk_wait_read0() { asm volatile("cp.async.bulk.wait_group.read 0;" ::: "memory"); }
__device__ __forceinline__ void wg_fence() { asm volatile("wgmma.fence.sync.aligned;" ::: "memory"); }
__device__ __forceinline__ void wg_commit() { asm volatile("wgmma.commit_group.sync.aligned;" ::: "memory"); }
__device__ __forceinline__ void wg_wait0() { asm volatile("wgmma.wait_group.sync.aligned 0;" ::: "memory"); }
__device__ __forceinline__ uint64_t desc_sw128(uint32_t addr) {
  return (uint64_t)((addr & 0x3FFFF) >> 4) | ((uint64_t)1 << 16) | ((uint64_t)64 << 32) | ((uint64_t)1 << 62);
}
template <int ACC>
__device__ __forceinline__ void wgmma_rs32(float* d, const uint32_t* a, uint64_t db) {
  asm volatile("{.reg .pred p; setp.ne.b32 p, %21, 0;\n"
               "wgmma.mma_async.sync.aligned.m64n32k16.f32.bf16.bf16 {%0,%1,%2,%3,%4,%5,%6,%7,%8,%9,%10,%11,%12,%13,%14,%15}, {%16,%17,%18,%19}, %20, p, 1, 1, 0;}"
               : "+f"(d[0]), "+f"(d[1]), "+f"(d[2]), "+f"(d[3]), "+f"(d[4]), "+f"(d[5]), "+f"(d[6]), "+f"(d[7]), "+f"(d[8]), "+f"(d[9]),
                 "+f"(d[10]), "+f"(d[11]), "+f"(d[12]), "+f"(d[13]), "+f"(d[14]), "+f"(d[15])
               : "r"(a[0]), "r"(a[1]), "r"(a[2]), "r"(a[3]), "l"(db), "n"(ACC));
}

template <int N> __device__ __forceinline__ void fence_regs(float* d) {
#pragma unroll
  for (int i = 0; i < N; i++) asm volatile("" : "+f"(d[i])::"memory");
}
__device__ __forceinline__ void wg_wait1() { asm volatile("wgmma.wait_group.sync.aligned 1;" ::: "memory"); }
__device__ __forceinline__ void tma_store3(const CUtensorMap* tm, uint32_t src, int c0, int c1, int c2) {
  asm volatile("cp.async.bulk.tensor.3d.global.shared::cta.bulk_group [%0, {%2,%3,%4}], [%1];" ::"l"(tm), "r"(src), "r"(c0), "r"(c1), "r"(c2) : "memory");
}
__device__ __forceinline__ void tma_red3(const CUtensorMap* tm, uint32_t src, int c0, int c1, int c2) {
  asm volatile("cp.reduce.async.bulk.tensor.3d.global.shared::cta.add.bulk_group [%0, {%2,%3,%4}], [%1];" ::"l"(tm), "r"(src), "r"(c0), "r"(c1), "r"(c2) : "memory");
}
__device__ __forceinline__ void stsm4(uint32_t a, uint32_t r0, uint32_t r1, uint32_t r2, uint32_t r3) {
  asm volatile("stmatrix.sync.aligned.m8n8.x4.shared.b16 [%0], {%1,%2,%3,%4};" ::"r"(a), "r"(r0), "r"(r1), "r"(r2), "r"(r3) : "memory");
}
__device__ __forceinline__ uint2 lds64(uint32_t a) { uint2 v; asm volatile("ld.shared.v2.b32 {%0,%1}, [%2];" : "=r"(v.x), "=r"(v.y) : "r"(a) : "memory"); return v; }
__device__ __forceinline__ uint32_t hmul2(uint32_t a, uint32_t b) { uint32_t r; asm("mul.rn.bf16x2 %0, %1, %2;" : "=r"(r) : "r"(a), "r"(b)); return r; }
__device__ __forceinline__ void wgmma_ss192t(float* d, uint64_t da, uint64_t db, int acc) {
  asm volatile("{.reg .pred p; setp.ne.b32 p, %98, 0;\n"
    "wgmma.mma_async.sync.aligned.m64n192k16.f32.bf16.bf16 "
    "{%0,%1,%2,%3,%4,%5,%6,%7,%8,%9,%10,%11,%12,%13,%14,%15,%16,%17,%18,%19,%20,%21,%22,%23,%24,%25,%26,%27,%28,%29,%30,%31,%32,%33,%34,%35,%36,%37,%38,%39,%40,%41,%42,%43,%44,%45,%46,%47,%48,%49,%50,%51,%52,%53,%54,%55,%56,%57,%58,%59,%60,%61,%62,%63,%64,%65,%66,%67,%68,%69,%70,%71,%72,%73,%74,%75,%76,%77,%78,%79,%80,%81,%82,%83,%84,%85,%86,%87,%88,%89,%90,%91,%92,%93,%94,%95}, %96, %97, p, 1, 1, 0, 1;}"
    : "+f"(d[0]), "+f"(d[1]), "+f"(d[2]), "+f"(d[3]), "+f"(d[4]), "+f"(d[5]), "+f"(d[6]), "+f"(d[7]), "+f"(d[8]), "+f"(d[9]), "+f"(d[10]), "+f"(d[11]),
      "+f"(d[12]), "+f"(d[13]), "+f"(d[14]), "+f"(d[15]), "+f"(d[16]), "+f"(d[17]), "+f"(d[18]), "+f"(d[19]), "+f"(d[20]), "+f"(d[21]), "+f"(d[22]),
      "+f"(d[23]), "+f"(d[24]), "+f"(d[25]), "+f"(d[26]), "+f"(d[27]), "+f"(d[28]), "+f"(d[29]), "+f"(d[30]), "+f"(d[31]), "+f"(d[32]), "+f"(d[33]),
      "+f"(d[34]), "+f"(d[35]), "+f"(d[36]), "+f"(d[37]), "+f"(d[38]), "+f"(d[39]), "+f"(d[40]), "+f"(d[41]), "+f"(d[42]), "+f"(d[43]), "+f"(d[44]),
      "+f"(d[45]), "+f"(d[46]), "+f"(d[47]), "+f"(d[48]), "+f"(d[49]), "+f"(d[50]), "+f"(d[51]), "+f"(d[52]), "+f"(d[53]), "+f"(d[54]), "+f"(d[55]),
      "+f"(d[56]), "+f"(d[57]), "+f"(d[58]), "+f"(d[59]), "+f"(d[60]), "+f"(d[61]), "+f"(d[62]), "+f"(d[63]), "+f"(d[64]), "+f"(d[65]), "+f"(d[66]),
      "+f"(d[67]), "+f"(d[68]), "+f"(d[69]), "+f"(d[70]), "+f"(d[71]), "+f"(d[72]), "+f"(d[73]), "+f"(d[74]), "+f"(d[75]), "+f"(d[76]), "+f"(d[77]),
      "+f"(d[78]), "+f"(d[79]), "+f"(d[80]), "+f"(d[81]), "+f"(d[82]), "+f"(d[83]), "+f"(d[84]), "+f"(d[85]), "+f"(d[86]), "+f"(d[87]), "+f"(d[88]),
      "+f"(d[89]), "+f"(d[90]), "+f"(d[91]), "+f"(d[92]), "+f"(d[93]), "+f"(d[94]), "+f"(d[95])
    : "l"(da), "l"(db), "r"(acc));
}
__device__ __forceinline__ void wgmma_rs128t(float* d, const uint32_t* a, uint64_t db, int acc) {
  asm volatile("{.reg .pred p; setp.ne.b32 p, %69, 0;\n"
    "wgmma.mma_async.sync.aligned.m64n128k16.f32.bf16.bf16 "
    "{%0,%1,%2,%3,%4,%5,%6,%7,%8,%9,%10,%11,%12,%13,%14,%15,%16,%17,%18,%19,%20,%21,%22,%23,%24,%25,%26,%27,%28,%29,%30,%31,%32,%33,%34,%35,%36,%37,%38,%39,%40,%41,%42,%43,%44,%45,%46,%47,%48,%49,%50,%51,%52,%53,%54,%55,%56,%57,%58,%59,%60,%61,%62,%63}, {%64,%65,%66,%67}, %68, p, 1, 1, 1;}"
    : "+f"(d[0]), "+f"(d[1]), "+f"(d[2]), "+f"(d[3]), "+f"(d[4]), "+f"(d[5]), "+f"(d[6]), "+f"(d[7]), "+f"(d[8]), "+f"(d[9]), "+f"(d[10]), "+f"(d[11]),
      "+f"(d[12]), "+f"(d[13]), "+f"(d[14]), "+f"(d[15]), "+f"(d[16]), "+f"(d[17]), "+f"(d[18]), "+f"(d[19]), "+f"(d[20]), "+f"(d[21]), "+f"(d[22]),
      "+f"(d[23]), "+f"(d[24]), "+f"(d[25]), "+f"(d[26]), "+f"(d[27]), "+f"(d[28]), "+f"(d[29]), "+f"(d[30]), "+f"(d[31]), "+f"(d[32]), "+f"(d[33]),
      "+f"(d[34]), "+f"(d[35]), "+f"(d[36]), "+f"(d[37]), "+f"(d[38]), "+f"(d[39]), "+f"(d[40]), "+f"(d[41]), "+f"(d[42]), "+f"(d[43]), "+f"(d[44]),
      "+f"(d[45]), "+f"(d[46]), "+f"(d[47]), "+f"(d[48]), "+f"(d[49]), "+f"(d[50]), "+f"(d[51]), "+f"(d[52]), "+f"(d[53]), "+f"(d[54]), "+f"(d[55]),
      "+f"(d[56]), "+f"(d[57]), "+f"(d[58]), "+f"(d[59]), "+f"(d[60]), "+f"(d[61]), "+f"(d[62]), "+f"(d[63])
    : "r"(a[0]), "r"(a[1]), "r"(a[2]), "r"(a[3]), "l"(db), "r"(acc));
}
__device__ __forceinline__ void wgmma_rs80(float* d, const uint32_t* a, uint64_t db, int acc) {
  asm volatile("{.reg .pred p; setp.ne.b32 p, %45, 0;\n"
    "wgmma.mma_async.sync.aligned.m64n80k16.f32.bf16.bf16 "
    "{%0,%1,%2,%3,%4,%5,%6,%7,%8,%9,%10,%11,%12,%13,%14,%15,%16,%17,%18,%19,%20,%21,%22,%23,%24,%25,%26,%27,%28,%29,%30,%31,%32,%33,%34,%35,%36,%37,%38,%39}, {%40,%41,%42,%43}, %44, p, 1, 1, 0;}"
    : "+f"(d[0]), "+f"(d[1]), "+f"(d[2]), "+f"(d[3]), "+f"(d[4]), "+f"(d[5]), "+f"(d[6]), "+f"(d[7]), "+f"(d[8]), "+f"(d[9]), "+f"(d[10]), "+f"(d[11]),
      "+f"(d[12]), "+f"(d[13]), "+f"(d[14]), "+f"(d[15]), "+f"(d[16]), "+f"(d[17]), "+f"(d[18]), "+f"(d[19]), "+f"(d[20]), "+f"(d[21]), "+f"(d[22]),
      "+f"(d[23]), "+f"(d[24]), "+f"(d[25]), "+f"(d[26]), "+f"(d[27]), "+f"(d[28]), "+f"(d[29]), "+f"(d[30]), "+f"(d[31]), "+f"(d[32]), "+f"(d[33]),
      "+f"(d[34]), "+f"(d[35]), "+f"(d[36]), "+f"(d[37]), "+f"(d[38]), "+f"(d[39])
    : "r"(a[0]), "r"(a[1]), "r"(a[2]), "r"(a[3]), "l"(db), "r"(acc));
}
__device__ __forceinline__ void wgmma_rs192t(float* d, const uint32_t* a, uint64_t db, int acc) {
  asm volatile("{.reg .pred p; setp.ne.b32 p, %101, 0;\n"
    "wgmma.mma_async.sync.aligned.m64n192k16.f32.bf16.bf16 "
    "{%0,%1,%2,%3,%4,%5,%6,%7,%8,%9,%10,%11,%12,%13,%14,%15,%16,%17,%18,%19,%20,%21,%22,%23,%24,%25,%26,%27,%28,%29,%30,%31,%32,%33,%34,%35,%36,%37,%38,%39,%40,%41,%42,%43,%44,%45,%46,%47,%48,%49,%50,%51,%52,%53,%54,%55,%56,%57,%58,%59,%60,%61,%62,%63,%64,%65,%66,%67,%68,%69,%70,%71,%72,%73,%74,%75,%76,%77,%78,%79,%80,%81,%82,%83,%84,%85,%86,%87,%88,%89,%90,%91,%92,%93,%94,%95}, {%96,%97,%98,%99}, %100, p, 1, 1, 1;}"
    : "+f"(d[0]), "+f"(d[1]), "+f"(d[2]), "+f"(d[3]), "+f"(d[4]), "+f"(d[5]), "+f"(d[6]), "+f"(d[7]), "+f"(d[8]), "+f"(d[9]), "+f"(d[10]), "+f"(d[11]),
      "+f"(d[12]), "+f"(d[13]), "+f"(d[14]), "+f"(d[15]), "+f"(d[16]), "+f"(d[17]), "+f"(d[18]), "+f"(d[19]), "+f"(d[20]), "+f"(d[21]), "+f"(d[22]),
      "+f"(d[23]), "+f"(d[24]), "+f"(d[25]), "+f"(d[26]), "+f"(d[27]), "+f"(d[28]), "+f"(d[29]), "+f"(d[30]), "+f"(d[31]), "+f"(d[32]), "+f"(d[33]),
      "+f"(d[34]), "+f"(d[35]), "+f"(d[36]), "+f"(d[37]), "+f"(d[38]), "+f"(d[39]), "+f"(d[40]), "+f"(d[41]), "+f"(d[42]), "+f"(d[43]), "+f"(d[44]),
      "+f"(d[45]), "+f"(d[46]), "+f"(d[47]), "+f"(d[48]), "+f"(d[49]), "+f"(d[50]), "+f"(d[51]), "+f"(d[52]), "+f"(d[53]), "+f"(d[54]), "+f"(d[55]),
      "+f"(d[56]), "+f"(d[57]), "+f"(d[58]), "+f"(d[59]), "+f"(d[60]), "+f"(d[61]), "+f"(d[62]), "+f"(d[63]), "+f"(d[64]), "+f"(d[65]), "+f"(d[66]),
      "+f"(d[67]), "+f"(d[68]), "+f"(d[69]), "+f"(d[70]), "+f"(d[71]), "+f"(d[72]), "+f"(d[73]), "+f"(d[74]), "+f"(d[75]), "+f"(d[76]), "+f"(d[77]),
      "+f"(d[78]), "+f"(d[79]), "+f"(d[80]), "+f"(d[81]), "+f"(d[82]), "+f"(d[83]), "+f"(d[84]), "+f"(d[85]), "+f"(d[86]), "+f"(d[87]), "+f"(d[88]),
      "+f"(d[89]), "+f"(d[90]), "+f"(d[91]), "+f"(d[92]), "+f"(d[93]), "+f"(d[94]), "+f"(d[95])
    : "r"(a[0]), "r"(a[1]), "r"(a[2]), "r"(a[3]), "l"(db), "r"(acc));
}

constexpr int NPQ = 2;
#define NQ 12
#define NQ_WIN 8
#define NO_EARLY 6
#define NO_MID 9
#define NW1 16
#define NW1A 10
#define VLD 6
#define VB 0
#define XPF 3
#define WSPLIT 8
#define PEARLY 0
#define NQ_W1 8
#define B5LATE 0
#define WD 750
#define DFENCE 0
#define PDS 300
#define PDT 50
#define PD 900
constexpr int R_WQ = 0;
constexpr int R_WO = R_WQ + 8 * (20 - NPQ) * 512;
constexpr int R_XT = R_WO + 14 * 12 * 512;
constexpr int R_MEM = R_XT;
constexpr int R_QB = R_XT + 40960;
constexpr int R_QA = R_QB + 1024;
constexpr int R_O2 = R_QA + 1024;
constexpr int R_VS = R_O2 + 1024;
constexpr int R_KT = R_VS + 1024;
constexpr int R_VT = R_KT + 5120;
constexpr int R_V1 = R_VT + 5120;
constexpr int R_SX = R_V1 + 8192;
constexpr int R_VM = R_SX + 4608;
constexpr int R_BAR = R_VM + 2048;
constexpr int R_MI = R_BAR + 64;
constexpr int R_SMEM = R_MI + 64;
static_assert(NPQ == 2 && R_XT % 1024 == 0 && R_KT % 1024 == 0 && R_VT % 1024 == 0 && R_V1 % 1024 == 0 && R_WO % 1024 == 0, "align");
constexpr int R_SMEM_ALLOC = R_SMEM;
static_assert(R_SMEM_ALLOC <= 232448, "smem");

#define TR(i) do {} while (0)

__device__ __forceinline__ void red_pair(unsigned char* p, float lo, float hi) {
  const int b = __float2int_rn(lo), a = __float2int_rn(hi);
  asm volatile("{.reg .b64 t; mov.b64 t, {%1,%2}; red.relaxed.gpu.global.add.u64 [%0], t;}" ::"l"(p), "r"(b + ((1 << 29) + (1 << 23))), "r"(a * 8) : "memory");
}
__device__ __forceinline__ unsigned long long swap0(unsigned char* p) {
  unsigned long long r;
  asm volatile("atom.relaxed.gpu.global.exch.b64 %0, [%1], 0;" : "=l"(r) : "l"(p) : "memory");
  return r;
}
__device__ __forceinline__ uint32_t dec_pair(uint32_t lo, uint32_t hi, uint32_t bias) { return pack2((float)(int)(lo * 8u + bias), (float)(int)hi); }

__global__ void __cluster_dims__(3, 1, 1) __launch_bounds__(256, 1)
rec_kernel(const __grid_constant__ CUtensorMap tmX, const __grid_constant__ CUtensorMap tmK, const __grid_constant__ CUtensorMap tmV,
           const __grid_constant__ CUtensorMap tmWq, const __grid_constant__ CUtensorMap tmWq2, const __grid_constant__ CUtensorMap tmWk,
           const __grid_constant__ CUtensorMap tmWv, const __grid_constant__ CUtensorMap tmWo, const bf16* __restrict__ mem0,
           const bf16* __restrict__ Wq, const bf16* __restrict__ Wo, const bf16* __restrict__ x) {
  extern __shared__ __align__(1024) unsigned char smem[];
  const uint32_t sb = smem_u32(smem);
  const int tid = threadIdx.x, lane = tid & 31, wid = __shfl_sync(~0u, tid >> 5, 0), g = wid >> 2, w = wid & 3;
  const int cta = blockIdx.x, head = cta / 3, rank = cta % 3;
  const int D0 = head * DH + rank * 64;
  const int tile0 = rank == 0 ? 0 : (rank == 1 ? 14 : 26);
  const uint32_t XBAR = sb + R_BAR, SBAR = XBAR + 8, OBAR = XBAR + 16, VBAR = XBAR + 24, FBAR = XBAR + 32, WBAR = XBAR + 40;
  constexpr uint32_t ONES = 0x3F803F80u;
  asm volatile("griddepcontrol.launch_dependents;" ::: "memory");
  GTR(0);
  if (wid == 0) {
    if (lane == 0) {
      mbar_init(XBAR, 1); mbar_init(SBAR, 4); mbar_init(OBAR, 5); mbar_init(VBAR, 1); mbar_init(FBAR, 2);
      mbar_init(WBAR, 1); mbar_init(WBAR + 8, 1); mbar_init(WBAR + 16, 1);
      asm volatile("fence.mbarrier_init.release.cluster;" ::: "memory");
      mbar_expect(WBAR, 81920); mbar_expect(WBAR + 8, 81920 + 2 * NPQ * 2048); mbar_expect(XBAR, 40960);
      mbar_expect(SBAR, 3072); mbar_expect(OBAR, 2048); mbar_expect(VBAR, 8192);
      sts128(sb + R_MI + 48, 0, 0, 0, 0);
    }
    __syncwarp();
    if (lane < 5) tma_load2(sb + lane * 16384, &tmWk, D0, lane * 128, WBAR);
    if (lane == 5) tma_load3(sb + R_XT, &tmX, 0, 0, 0, XBAR);
    if (lane < 5) tma_load2(lane < 4 ? sb + 81920 + lane * 16384 : sb + R_QB, &tmWv, D0, lane * 128, WBAR + 8);
    if (lane < 2) tma_load2(sb + R_QB + 16384 + lane * 4096, &tmWq2, D0, lane * 320, WBAR + 8);
  }
  if (tid == 32) { prefetch_map(&tmWq); prefetch_map(&tmWo); prefetch_map(&tmK); prefetch_map(&tmV); }
  if (tid >= 64 && tid < 144) prefetch_l2(mem0 + (tid - 64) * 64);
  __syncthreads();
  GTR(1);
#pragma unroll
  for (int i = 0; i < 5; i++) { const int l = tid + i * 256; prefetch_l2((l < 640 ? Wq : Wo - 40960) + (size_t)cta * 40960 + l * 64); }
  uint32_t ww[40][4], wqp[NPQ][4];
  {
    uint32_t xm = 0;
#pragma unroll
    for (int i = 0; i < 7; i++) {
      const int v = tid + i * 256, gv = cta * 1707 + v;
      if (v < 1707 && gv < S_TOK * DM / 8) {
        const uint4 q = __ldg((const uint4*)x + gv);
        xm = hmaxabs2(hmaxabs2(xm, hmaxabs2(q.x, q.y)), hmaxabs2(q.z, q.w));
      }
    }
    xm = __reduce_max_sync(~0u, max((xm << 16) & 0x7fffffffu, xm & 0x7fff0000u));
    const uint32_t p = sb + (lane >> 4) * 1024 + (lane & 7) * 128 + (((2 * w + ((lane >> 3) & 1)) ^ (lane & 7)) << 4);
    mbar_wait(WBAR + 8 * g, 0);
    GTR(2);
#pragma unroll
    for (int f = 0; f < 40; f++) ldsm4t(ww[f], (f >= 32 && g == 1) ? p + R_QB + (f - 32) * 2048 : p + g * 81920 + f * 2048);
    mbar_wait(WBAR + 8, 0);
    GTR(3);
#pragma unroll
    for (int f = 0; f < NPQ; f++) ldsm4t(wqp[f], p + R_QB + 16384 + g * 4096 + f * 2048);
    __syncthreads();
    asm volatile("barrier.cluster.arrive.relaxed.aligned;" ::: "memory");
    if (wid == 0) {
      if (lane == 0) mbar_expect(WBAR + 16, 18 * 4096 + 21 * 4096);
      __syncwarp();
      if (lane < 4) tma_load2(sb + R_WQ + lane * 18432, &tmWq, D0, (lane >> 1) * 320 + 32 + (lane & 1) * 144, WBAR + 16);
      else if (lane < 7) tma_load3(sb + R_WO + ((lane - 1 - rank) % 3) * 28672, &tmWo, 0, head * DH + (lane - 4) * 64, tile0 >> 1, WBAR + 16);
      __syncwarp();
    }
    float nv[4] = {0.f, 0.f, 0.f, 0.f};
#pragma unroll
    for (int f = 0; f < 40; f++) {
      const uint32_t a[4] = {ww[f][0] & 0x7fff7fffu, ww[f][1] & 0x7fff7fffu, ww[f][2] & 0x7fff7fffu, ww[f][3] & 0x7fff7fffu};
      mma16816(nv, a, ONES, ONES);
    }
    const uint32_t mv = __reduce_max_sync(~0u, __float_as_uint(fmaxf(nv[0], nv[2])));
    if (lane == 0) { if (g == 1) smax32(sb + R_MI + 48, mv); smax32(sb + R_MI + 52, xm); }
  }
  GTR(4);

  const uint32_t rF_ = opaque(sb + lane * 16);
  const uint32_t rP_ = opaque(sb + (lane >> 4) * 1024 + (lane & 7) * 128 + (((2 * w + ((lane >> 3) & 1)) ^ (lane & 7)) << 4));
  const int tA = g == 1 ? 2 * w : (rank != 1 ? (w < 2 ? 8 + 2 * w : 10 + w) : 8 + w);
  const bool two = g == 1 || (w < 2 && rank != 1);
  const uint32_t r1 = rank == 2 ? 0 : rank + 1, r2 = rank == 0 ? 2 : rank - 1;
  const uint32_t rW_ = opaque(sb + R_WO + (tA >> 1) * 4096 + ((lane >> 4) * 8 + (lane & 7)) * 64 +
                             (((2 * (tA & 1) + ((lane >> 3) & 1)) ^ ((lane >> 1) & 3)) << 4));
  uint32_t wqt[NQ][4];
  float u = 1.f;
  uint32_t t0 = 0;
  int s = -1;

#define WOFF(ks) (((ks) >> 2) * 28672 + ((ks) & 3) * 1024)
#define XDESC(j) (((uint64_t)0x40000040 << 32) | (dlo + ((((j) >> 2) * 4096 + ((j) & 3) * 32) >> 4)))

  auto window = [&](auto G_, auto FIRST_) {
    constexpr int G = decltype(G_)::value;
    constexpr bool FIRST = decltype(FIRST_)::value;
    const uint32_t rF = pin(rF_), rP = pin(rP_);
    float d[16];
    const uint32_t dlo = pin(((sb + R_XT) >> 4) | 0x10000);
    const uint32_t wqS = rP + R_WQ + G * (20 - NPQ) * 2048;
    uint4 y[5];
    unsigned long long zr = 0;
    const uint32_t t = w * 32 + ((rF - sb) >> 4);
    if (G == 0) zr = swap0(g_red + (((s + 2) & 3) * RB_SIZE + ((cta % 20) * 8 + (t >> 4)) * RB_LINE + (t & 15) * 8));
    if (G == 0) {
      if (!FIRST && w == 3) {
        if (elect()) {
          mbar_expect(SBAR, 3072); mbar_expect(OBAR, 2048); mbar_expect(VBAR, 8192);
          asm volatile("mbarrier.arrive.relaxed.cluster.shared::cluster.b64 _, [%0];" ::"r"(mapa(FBAR, r1)) : "memory");
          asm volatile("mbarrier.arrive.relaxed.cluster.shared::cluster.b64 _, [%0];" ::"r"(mapa(FBAR, r2)) : "memory");
        }
        __syncwarp();
      }
    }
    const unsigned char* yp = g_red + ((s & 3) * RB_SIZE + (G * 80 + (t >> 3)) * RB_LINE + (t & 7) * 16);
    auto poll = [&]() {
      TR(10);
      spin_until(t0, PD);
#pragma unroll
      for (int q = 0; q < 5; q++) y[q] = ldg_rlx128(yp + q * 16 * RB_LINE);
      TR(9);
      sched_fence(sb);
    };
    constexpr int WS = FIRST || G == 1 ? 40 : WSPLIT;
    if (!FIRST && G == 0) {
#pragma unroll
      for (int f = 0; f < NQ_WIN; f++) ldsm4t(wqt[f], wqS + f * 2048);
      asm volatile("" : "+l"(yp));
      mbar_wait(XBAR, (s + 1) & 1);
      spin_until(t0, WD);
    } else {
      mbar_wait(XBAR, (s + 1) & 1);
    }
    TR(11);
    wg_fence();
    wgmma_rs32<0>(d, ww[0], XDESC(0));
#pragma unroll
    for (int j = 1; j < WS; j++) wgmma_rs32<1>(d, ww[j], XDESC(j));
    if (FIRST) {
      const unsigned short* m = (const unsigned short*)mem0 + (t & 1) * 4 * DM + G * 320 + (t >> 1);
#pragma unroll
      for (int q = 0; q < 5; q++) y[q] = make_uint4(m[q * 64], m[q * 64 + DM], m[q * 64 + 2 * DM], m[q * 64 + 3 * DM]);
    } else if (G == 0) {
      poll();
    }
#pragma unroll
    for (int j = WS; j < 40; j++) wgmma_rs32<1>(d, ww[j], XDESC(j));
    wg_commit();
    if (!FIRST && G == 1) {
      asm volatile("" : "+l"(yp));
      if (PEARLY) poll();
      mbar_wait(FBAR, s & 1);
#pragma unroll
      for (int f = 0; f < NQ_W1; f++) ldsm4t(wqt[f], wqS + f * 2048);
    }
    if (FIRST) asm volatile("barrier.cluster.wait.acquire.aligned;" ::: "memory");
    wg_wait0();
    fence_regs<16>(d);
    TR(13);
    bar_arrive(8 + G, 256);
    if (!FIRST && G == 1 && !PEARLY) poll();
    {
      uint32_t pk[8];
#pragma unroll
      for (int q = 0; q < 8; q++) pk[q] = pack2(d[2 * q], d[2 * q + 1]);
      stsm4t(rP + (G == 1 ? R_VT : R_KT) + 1024, pk[0], pk[1], pk[2], pk[3]);
      stsm4t(rP + (G == 1 ? R_VT : R_KT) + 3072, pk[4], pk[5], pk[6], pk[7]);
      if (G == 1) {
        const uint32_t e1 = mapa(rF + R_V1 + 4096 + w * 512, r1), e2 = mapa(rF + R_V1 + w * 512, r2), b1 = mapa(VBAR, r1), b2 = mapa(VBAR, r2);
        st_async4(e1, pk[0], pk[1], pk[2], pk[3], b1);
        st_async4(e2, pk[0], pk[1], pk[2], pk[3], b2);
        st_async4(e1 + 2048, pk[4], pk[5], pk[6], pk[7], b1);
        st_async4(e2 + 2048, pk[4], pk[5], pk[6], pk[7], b2);
      }
    }
    if (FIRST) {
      mbar_wait(WBAR + 16, 0);
      const uint32_t woA = rW_;
      float na[4] = {0.f, 0.f, 0.f, 0.f}, nb[4] = {0.f, 0.f, 0.f, 0.f};
#pragma unroll
      for (int ks = 0; ks < 12; ks++) {
        uint32_t a[4], b[4];
        ldsm4t(a, woA + WOFF(ks));
        ldsm4t(b, (two ? woA ^ 32 : woA) + WOFF(ks));
#pragma unroll
        for (int q = 0; q < 4; q++) { a[q] &= 0x7fff7fffu; b[q] &= 0x7fff7fffu; }
        mma16816(na, a, ONES, ONES);
        mma16816(nb, b, ONES, ONES);
      }
      const uint32_t mo = __reduce_max_sync(~0u, __float_as_uint(fmaxf(fmaxf(na[0], na[2]), fmaxf(nb[0], nb[2]))));
      if (rF == sb) smax32(sb + R_MI + 56, mo);
      __syncthreads();
      if (G == 1 && w == 2) {
        const uint4 r = lds128(sb + R_MI + 48);
        const uint32_t epoch = *(volatile uint32_t*)&g_epoch + 1;
        if (rF == sb) stg_rlx64(&g_rec[cta], (r.y & 0xffff0000u) | (epoch & 0xffffu), ((r.x + 0xffffu) & 0xffff0000u) | ((r.z + 0xffffu) >> 16));
      }
    }
#pragma unroll
    for (int f = FIRST ? 0 : (G == 1 ? NQ_W1 : NQ_WIN); f < NQ; f++) ldsm4t(wqt[f], wqS + f * 2048);
    if (FIRST || DFENCE) sched_fence(sb);
    TR(14);
    const uint32_t ma = sb + R_MEM + G * 5120 + t * 8;
    if (FIRST) {
      bar_sync(9 - G, 256);
#pragma unroll
      for (int j = 0; j < 5; j++) sts64(ma + j * 1024, y[j].x | (y[j].y << 16), y[j].z | (y[j].w << 16));
    } else {
      int n = 0;
#pragma unroll 1
      while (!__all_sync(~0u, (y[0].y & y[0].w & y[1].y) & (y[1].w & y[2].y & y[2].w) & (y[3].y & y[3].w & y[4].y) & (y[4].w & 4))) {
#pragma unroll
        for (int j = 0; j < 5; j++) if (!(y[j].y & y[j].w & 4)) y[j] = ldg_rlx128(yp + j * 16 * RB_LINE);
        if (++n > SPIN_MAX) { g_err = 5; break; }
      }
      const uint32_t bias = 0x80000000u + (sb >> 31);
      bar_sync(9 - G, 256);
#pragma unroll
      for (int j = 0; j < 5; j++) sts64(ma + j * 1024, dec_pair(y[j].x, y[j].y, bias), dec_pair(y[j].z, y[j].w, bias));
    }
    if (G == 0 && zr == ~0ull) g_err = 9;
    TR(0);
  };

  auto oproj = [&](auto TWO_, auto NPRE_, auto& wot, const uint32_t rF, const uint32_t woA, const uint32_t woB,
                   float sm0, float sm1, bool have_sums) {
    constexpr bool TWO = decltype(TWO_)::value;
    constexpr int NPRE = decltype(NPRE_)::value;
    float c[4][4];
#pragma unroll
    for (int q = 0; q < 4; q++) c[q][0] = c[q][1] = c[q][2] = c[q][3] = 0.f;
    unsigned char* sp = g_red + ((s & 3) * RB_SIZE + (4 * (tile0 + tA) + ((rF - sb) >> 8)) * RB_LINE + (((rF - sb) >> 1) & 120));
    bar_sync(3, 256);
    TR(8);
    uint4 ob[6];
    ob[0] = lds128(rF + R_QB); ob[1] = lds128(rF + R_QB + 512);
    const float2 su = lds64f(sb + R_MI + 48);
    if (!have_sums) { const float2 t = lds64f(sb + R_MI + 16 + (((rF - sb) >> 1) & 24)); sm0 = t.x; sm1 = t.y; }
#pragma unroll
    for (int p = 0; p < 6; p++) {
      if (p + 2 < 6) ob[p + 2] = lds128(rF + (p < 2 ? R_QA : R_O2) + (p & 1) * 512);
#pragma unroll
      for (int e = 0; e < 2; e++) {
        const int ks = 2 * p + e;
        const uint32_t b0 = e ? ob[p].z : ob[p].x, b1 = e ? ob[p].w : ob[p].y;
        if (TWO) {
          const int iA = 2 * ks, iB = iA + 1;
          mma16816(c[e], wot[iA % NPRE], b0, b1);
          if (iA + NPRE < 24) ldsm4t(wot[iA % NPRE], woA + WOFF((iA + NPRE) >> 1));
          mma16816(c[2 + e], wot[iB % NPRE], b0, b1);
          if (iB + NPRE < 24) ldsm4t(wot[iB % NPRE], woB + WOFF((iB + NPRE) >> 1));
        } else {
          mma16816(c[ks & 3], wot[ks], b0, b1);
        }
      }
    }
    const float f0 = su.x * rcp(sm0), f1 = su.x * rcp(sm1);
    t0 = clk32() + (TWO ? (have_sums ? -PDT : 0) : PDS);
    u = su.y;
    if (TWO) {
      red_pair(sp, (c[0][0] + c[1][0]) * f0, (c[0][1] + c[1][1]) * f1);
      red_pair(sp + 2 * RB_LINE, (c[0][2] + c[1][2]) * f0, (c[0][3] + c[1][3]) * f1);
      red_pair(sp + 4 * RB_LINE, (c[2][0] + c[3][0]) * f0, (c[2][1] + c[3][1]) * f1);
      red_pair(sp + 6 * RB_LINE, (c[2][2] + c[3][2]) * f0, (c[2][3] + c[3][3]) * f1);
    } else {
      red_pair(sp, ((c[0][0] + c[1][0]) + (c[2][0] + c[3][0])) * f0, ((c[0][1] + c[1][1]) + (c[2][1] + c[3][1])) * f1);
      red_pair(sp + 2 * RB_LINE, ((c[0][2] + c[1][2]) + (c[2][2] + c[3][2])) * f0, ((c[0][3] + c[1][3]) + (c[2][3] + c[3][3])) * f1);
    }
    TR(15);
  };

  auto step = [&](auto G_, auto LAST_) {
    constexpr int G = decltype(G_)::value;
    constexpr bool LAST = decltype(LAST_)::value;
    __syncthreads();
    const uint32_t rF = pin(rF_), rP = pin(rP_);
    TR(1);
    const uint32_t wqS = rP + R_WQ + G * (20 - NPQ) * 2048, rM = rF + R_MEM;
    const uint32_t l8 = sb + ((rF - sb) >> 1) + w * 256;
    const uint32_t woA = pin(rW_), woB = woA ^ 32;
    float aq[2][4] = {};
    const uint32_t ln = (rF - sb) >> 4;
    const uint32_t rS = sb + (ln & 7) * 128 + (ln < 16 ? R_QB + (ln & 8) * 128 + (((2 * w + G) ^ (ln & 7)) << 4) : R_KT + (((2 * w + ((ln >> 3) & 1)) ^ (ln & 7)) << 4));
    auto qmma = [&](int f, uint32_t b0, uint32_t b1) {
      if (f < NPQ) mma16816(aq[f & 1], wqp[f], b0, b1);
      else {
        const int slot = (f - NPQ) % NQ;
        mma16816(aq[f & 1], wqt[slot], b0, b1);
        if (f + NQ < 20) ldsm4t(wqt[slot], wqS + (f - NPQ + NQ) * 2048);
      }
    };
    if constexpr (G == 1) {
      uint32_t bb[20][4];
      if (!LAST) {
        ldsm4t(bb[10], rM + 5120);
        ldsm4t(bb[11], rM + 5632);
#pragma unroll
        for (int i = 10; i < 20; i++) {
          if (i + 2 < 20) ldsm4t(bb[i + 2], rM + (i + 2) * 512);
          qmma(2 * i - 20, bb[i][0], bb[i][1]);
          qmma(2 * i - 19, bb[i][2], bb[i][3]);
        }
        stsm2t(rS, pack2(aq[0][0] + aq[1][0], aq[0][1] + aq[1][1]), pack2(aq[0][2] + aq[1][2], aq[0][3] + aq[1][3]));
        bar_arrive(1, 256);
      }
      TR(2);
      float av[4][4] = {};
      uint32_t m0 = 0, m1 = 0;
      auto vmma = [&](auto MAX_) {
#pragma unroll
        for (int n = 0; n < 20; n++) {
          const int i = (n + 10) % 20;
          if (LAST && n < 8) ldsm4t(bb[(n + 10) % 20], rM + ((n + 10) % 20) * 512);
          if (LAST && n == 0) { ldsm4t(bb[18], rM + 18 * 512); ldsm4t(bb[19], rM + 19 * 512); }
          if (n == VB && !LAST) { bar_sync(5, 256); sched_fence(sb); }
          if (n == VLD) {
            if (VB != VLD && !LAST) sched_fence(sb);
#pragma unroll
            for (int q = 0; q < 10; q++) ldsm4t(bb[q], rM + q * 512);
            if (!LAST) sched_fence(sb);
          }
          mma16816(av[(2 * n) & 3], ww[2 * i], bb[i][0], bb[i][1]);
          mma16816(av[(2 * n + 1) & 3], ww[2 * i + 1], bb[i][2], bb[i][3]);
          if (decltype(MAX_)::value) { m0 = hmaxabs2(m0, hmaxabs2(bb[i][0], bb[i][1])); m1 = hmaxabs2(m1, hmaxabs2(bb[i][2], bb[i][3])); }
        }
      };
      auto vout = [&]() {
        const uint32_t vm0 = pack2(((av[0][0] + av[1][0]) + (av[2][0] + av[3][0])) * u, ((av[0][1] + av[1][1]) + (av[2][1] + av[3][1])) * u);
        const uint32_t vm1 = pack2(((av[0][2] + av[1][2]) + (av[2][2] + av[3][2])) * u, ((av[0][3] + av[1][3]) + (av[2][3] + av[3][3])) * u);
        if (!LAST) {
          st_async2(mapa(l8 + R_VM + 1024, r1), vm0, vm1, mapa(OBAR, r1));
          st_async2(mapa(l8 + R_VM, r2), vm0, vm1, mapa(OBAR, r2));
          sts64(l8 + R_VS, vm0, vm1);
          __syncwarp();
          if (rF == sb) mbar_arrive(OBAR);
        }
        stsm2t(rP + R_VT, vm0, vm1);
      };
      if (LAST) { vmma(std::false_type{}); vout(); return; }
      uint32_t wot[NW1][4];
      auto wpre = [&](int i0, int i1) {
#pragma unroll
        for (int i = i0; i < i1; i++) ldsm4t(wot[i], ((i & 1) ? woB : woA) + WOFF(i >> 1));
      };
      if (w != 1) {
        vmma(std::false_type{});
        bar_arrive(7, 128);
        vout();
        bar_arrive(2, 128);
        TR(5);
        wpre(0, NW1A);
      } else {
        vmma(std::true_type{});
        bar_sync(7, 128);
        if (elect()) { mbar_expect(XBAR, 40960); tma_load3(sb + R_XT, &tmX, 0, (s + 1) * SEG, 0, XBAR); }
        __syncwarp();
        vout();
        if (XPF && s + XPF < NSEG && rF - sb < 64 && cta < 80) prefetch_l2(x + (size_t)(s + XPF) * SEG * DM + cta * 256 + (rF - sb) * 4);
        TR(5);
        m0 = hmaxabs2(m0, m1);
        const uint32_t mx = __reduce_max_sync(~0u, max((m0 << 16) & 0x7fffffffu, m0 & 0x7fff0000u));
        const float2 mi = lds64f(sb + R_MI + 8);
        wpre(0, NW1A);
        bar_sync(2, 128);
        if (elect()) {
          fence_async_smem();
          if (s > 0) {
            bulk_wait0();
            asm volatile("red.relaxed.gpu.global.add.u32 [%0], 1;" ::"l"(&g_segcnt[s - 1]) : "memory");
            asm volatile("red.relaxed.gpu.global.add.u32 [%0], 1;" ::"l"(&g_prog) : "memory");
          }
          tma_store2(&tmK, sb + R_KT, D0, s * LK);
          tma_store2(&tmV, sb + R_VT, D0, s * LK);
          bulk_commit();
        }
        __syncwarp();
        float wb = mi.x, xm = mi.y;
        if (s == 0) {
          const uint32_t epoch = *(volatile uint32_t*)&g_epoch + 1;
          uint32_t av_ = 0, ao = 0, xi = 0;
#pragma unroll 1
          for (int j = 0; j < 3; j++) {
            uint2 r;
            int n = 0;
#pragma unroll 1
            while (true) {
              r = ldg_rlx64(&g_rec[j * 32 + ((rF - sb) >> 4)]);
              if (((r.x ^ epoch) & 0xffffu) == 0) break;
              if (++n > SPIN_MAX) { g_err = 6; break; }
            }
            av_ = max(av_, r.y & 0xffff0000u); ao = max(ao, r.y << 16); xi = max(xi, r.x & 0xffff0000u);
          }
          av_ = __reduce_max_sync(~0u, av_); ao = __reduce_max_sync(~0u, ao); xi = __reduce_max_sync(~0u, xi);
          wb = __uint_as_float(av_) * __uint_as_float(ao) * 33.f; xm = __uint_as_float(xi);
          if (rF == sb) sts64f(sb + R_MI + 8, wb, xm);
          __syncwarp();
        }
        const float hm = fmaxf(__uint_as_float(mx) * u, xm);
        const uint32_t eb = min(max(__float_as_uint(hm * wb) >> 23, 40u), 200u);
        if (rF == sb) sts64(sb + R_MI + 48, (280u - eb) << 23, (eb - 29u) << 23);
        if (elect()) bulk_wait_read0();
        __syncwarp();
      }
      if (NW1A < NW1) {
        bar_sync(4, 256);
        wpre(NW1A, NW1);
      }
      TR(6);
      oproj(std::true_type{}, std::integral_constant<int, NW1>{}, wot, rF, woA, woB, 0.f, 0.f, false);
    } else {
      {
        uint32_t bb[20][4];
        float ak[4][4] = {};
        ldsm4t(bb[0], rM);
        ldsm4t(bb[10], rM + 5120);
#pragma unroll
        for (int i = 0; i < 10; i++) {
          if (i + 1 < 10) { ldsm4t(bb[i + 1], rM + (i + 1) * 512); ldsm4t(bb[i + 11], rM + (i + 11) * 512); }
          mma16816(ak[0], ww[2 * i], bb[i][0], bb[i][1]);
          if (!LAST) qmma(2 * i, bb[i][0], bb[i][1]);
          mma16816(ak[1], ww[2 * i + 1], bb[i][2], bb[i][3]);
          if (!LAST) qmma(2 * i + 1, bb[i][2], bb[i][3]);
          mma16816(ak[2], ww[2 * i + 20], bb[i + 10][0], bb[i + 10][1]);
          mma16816(ak[3], ww[2 * i + 21], bb[i + 10][2], bb[i + 10][3]);
        }
#pragma unroll
        for (int q = 0; q < 4; q++) { ak[0][q] += ak[2][q]; ak[1][q] += ak[3][q]; }
        stsm4t(rS, pack2(aq[0][0] + aq[1][0], aq[0][1] + aq[1][1]), pack2(aq[0][2] + aq[1][2], aq[0][3] + aq[1][3]),
               pack2((ak[0][0] + ak[1][0]) * u, (ak[0][1] + ak[1][1]) * u), pack2((ak[0][2] + ak[1][2]) * u, (ak[0][3] + ak[1][3]) * u));
      }
      if (LAST) return;
      bar_sync(1, 256);
      if (!B5LATE) bar_arrive(5, 256);
      TR(2);
      if (w != 3) {
        uint32_t qa[4][4], kk[4][4];
        float x[4][4] = {};
#pragma unroll
        for (int i = 0; i < 4; i++) { ldsm4(qa[i], (rP ^ (i << 5)) + R_QB); ldsm4(kk[i], ((rP ^ (i << 5)) + w * 2048) + R_KT); }
        const uint32_t dst = rF + R_SX + rank * 1536 + w * 512;
        const uint32_t e1 = mapa(dst, r1), e2 = mapa(dst, r2), s1 = mapa(SBAR, r1), s2 = mapa(SBAR, r2);
#pragma unroll
        for (int i = 0; i < 4; i++) { mma16816(x[i & 1], qa[i], kk[i][0], kk[i][1]); mma16816(x[2 + (i & 1)], qa[i], kk[i][2], kk[i][3]); }
        const uint32_t u0 = __float_as_uint((x[0][0] + x[0][2]) + (x[1][0] + x[1][2])), u1 = __float_as_uint((x[0][1] + x[0][3]) + (x[1][1] + x[1][3]));
        const uint32_t u2 = __float_as_uint((x[2][0] + x[2][2]) + (x[3][0] + x[3][2])), u3 = __float_as_uint((x[2][1] + x[2][3]) + (x[3][1] + x[3][3]));
        st_async4(e1, u0, u1, u2, u3, s1);
        st_async4(e2, u0, u1, u2, u3, s2);
        sts128(dst, u0, u1, u2, u3);
        __syncwarp();
        if (rF == sb) mbar_arrive(SBAR);
      }
      if (B5LATE) bar_arrive(5, 256);
      TR(4);
      mbar_wait(VBAR, s & 1);
      uint32_t wot[12][4], va[3][8];
      ldsm4t(va[0], rP + R_VT + 1024); ldsm4t(va[0] + 4, rP + R_VT + 3072);
#pragma unroll
      for (int q = 0; q < 4; q++) {
        const uint4 t = lds128(rF + R_V1 + w * 512 + q * 2048);
        uint32_t* v = va[1 + (q >> 1)] + (q & 1) * 4;
        v[0] = t.x; v[1] = t.y; v[2] = t.z; v[3] = t.w;
      }
      auto wpre = [&](int i0, int i1) {
        if (two) {
#pragma unroll
          for (int i = i0; i < i1; i++) ldsm4t(wot[i], ((i & 1) ? woB : woA) + WOFF(i >> 1));
        } else {
#pragma unroll
          for (int i = i0; i < i1; i++) ldsm4t(wot[i], woA + WOFF(i));
        }
      };
      wpre(0, NO_EARLY);
      const uint32_t dst = rF + (w >> 1) * 512 + (w & 1) * 8;
      const float scl = u * (0.07216878364870322f * 1.4426950408889634f);
      mbar_wait(SBAR, s & 1);
      TR(6);
      float sc[10];
      {
        const float4 a0 = lds128f(rF + R_SX), b0 = lds128f(rF + R_SX + 1536), c0 = lds128f(rF + R_SX + 3072);
        const float4 a1 = lds128f(rF + R_SX + 512), b1 = lds128f(rF + R_SX + 2048), c1 = lds128f(rF + R_SX + 3584);
        const float2 a2 = lds64f(rF + R_SX + 1024), b2 = lds64f(rF + R_SX + 2560), c2 = lds64f(rF + R_SX + 4096);
        sc[8] = a0.x + b0.x + c0.x; sc[9] = a0.y + b0.y + c0.y; sc[0] = a0.z + b0.z + c0.z; sc[1] = a0.w + b0.w + c0.w;
        sc[2] = a1.x + b1.x + c1.x; sc[3] = a1.y + b1.y + c1.y; sc[4] = a1.z + b1.z + c1.z; sc[5] = a1.w + b1.w + c1.w;
        sc[6] = a2.x + b2.x + c2.x; sc[7] = a2.y + b2.y + c2.y;
      }
      float mx = fmaxf(fmaxf(fmaxf(sc[0], sc[1]), fmaxf(sc[2], sc[3])), fmaxf(fmaxf(sc[4], sc[5]), fmaxf(sc[6], sc[7])));
      mx = fmaxf(mx, fmaxf(sc[8], sc[9]));
      mx = fmaxf(mx, __shfl_xor_sync(~0u, mx, 1));
      const bool vok = mbar_test(OBAR, s & 1);
      mx = fmaxf(mx, __shfl_xor_sync(~0u, mx, 2));
      if (NW1A < NW1) bar_arrive(4, 256);
      const float mo = mx * scl;
      uint32_t pb[5];
#pragma unroll
      for (int j = 0; j < 5; j++) pb[j] = pack2(ex2(fmaf(sc[2 * j], scl, -mo)), ex2(fmaf(sc[2 * j + 1], scl, -mo)));
      if (!vok) mbar_wait(OBAR, s & 1);
      const uint2 m0 = lds64(l8 + R_VS), m1 = lds64(l8 + R_VM), m2 = lds64(l8 + R_VM + 1024);
      const uint32_t ones[4] = {ONES, ONES, ONES, ONES};
      float o[3][4], o2[3][4], sm[4] = {0.f, 0.f, 0.f, 0.f}, sn[4] = {0.f, 0.f, 0.f, 0.f}, so[4] = {0.f, 0.f, 0.f, 0.f};
#pragma unroll
      for (int b = 0; b < 3; b++) {
        o[b][0] = o[b][1] = o[b][2] = o[b][3] = o2[b][0] = o2[b][1] = o2[b][2] = o2[b][3] = 0.f;
        mma16816(o[b], va[b], pb[0], pb[1]);
      }
#pragma unroll
      for (int b = 0; b < 3; b++) mma16816(o2[b], va[b] + 4, pb[2], pb[3]);
      mma1688(o[0], m0.x, m0.y, pb[4]);
      mma1688(o[1], m1.x, m1.y, pb[4]);
      mma1688(o[2], m2.x, m2.y, pb[4]);
      mma16816(sm, ones, pb[0], pb[1]);
      mma16816(sn, ones, pb[2], pb[3]);
      mma1688(so, ONES, ONES, pb[4]);
      wpre(NO_EARLY, NO_MID);
#pragma unroll
      for (int b = 0; b < 3; b++)
        sts64(dst + (b == 0 ? R_QB : (b == 1 ? R_QA : R_O2)), movmat(pack2(o[b][0] + o2[b][0], o[b][1] + o2[b][1])),
              movmat(pack2(o[b][2] + o2[b][2], o[b][3] + o2[b][3])));
      sm[0] += sn[0] + so[0]; sm[1] += sn[1] + so[1];
      if (rF - sb < 64) sts64f(sb + R_MI + 16 + ((rF - sb) >> 1), sm[0], sm[1]);
      wpre(NO_MID, 12);
      TR(7);
      if (two) oproj(std::true_type{}, std::integral_constant<int, 12>{}, wot, rF, woA, woB, sm[0], sm[1], true);
      else oproj(std::false_type{}, std::integral_constant<int, 12>{}, wot, rF, woA, woB, sm[0], sm[1], true);
    }
  };

  GTR(5); GTR(6);
  if (g == 0) {
    window(std::integral_constant<int, 0>{}, std::true_type{});
    GTR(7);
#pragma unroll 1
    for (s = 0; s < NSEG - 1; s++) {
      step(std::integral_constant<int, 0>{}, std::false_type{});
      window(std::integral_constant<int, 0>{}, std::false_type{});
    }
    step(std::integral_constant<int, 0>{}, std::true_type{});
  } else {
    window(std::integral_constant<int, 1>{}, std::true_type{});
#pragma unroll 1
    for (s = 0; s < NSEG - 1; s++) {
      step(std::integral_constant<int, 1>{}, std::false_type{});
      window(std::integral_constant<int, 1>{}, std::false_type{});
    }
    step(std::integral_constant<int, 1>{}, std::true_type{});
  }
  __syncthreads();
  if (tid == 160) {
    fence_async_smem();
    tma_store2(&tmK, sb + R_KT, D0, (NSEG - 1) * LK);
    tma_store2(&tmV, sb + R_VT, D0, (NSEG - 1) * LK);
    bulk_commit();
    bulk_wait0();
    asm volatile("red.relaxed.gpu.global.add.u32 [%0], 1;" ::"l"(&g_segcnt[NSEG - 2]) : "memory");
    asm volatile("red.relaxed.gpu.global.add.u32 [%0], 1;" ::"l"(&g_segcnt[NSEG - 1]) : "memory");
    asm volatile("red.relaxed.gpu.global.add.u32 [%0], 2;" ::"l"(&g_prog) : "memory");
  }
  GTR(8);
  if (tid == 0) mbar_wait(VBAR, (NSEG - 1) & 1);
  GTR(9);
}

enum { IT_GATE = 0, IT_QKV = 1, IT_XATT = 2, IT_OUT = 3, IT_BATT = 4, IT_CVT = 5, IT_INIT = 6, IT_END = 7 };
constexpr int C_GATE = 0, C_QKV = 16, C_OB = 32, C_ACC = 48, C_O = 80;
constexpr uint32_t NONE = ~0u;
#define T8 9
#define T16 13
#define T32 16
#define XD 0x5689aaaaaaaaaaaaull
#define KREQ 4
#define CREQ 3
#define PP 3
#define CLAG 3
#define CTAIL 10
constexpr int k_nsplit(int t) { return t >= T32 ? 32 : (t >= T16 ? 16 : (t >= T8 ? 8 : 4)); }
__host__ __device__ constexpr uint32_t mk_item(int ty, int t, int a, int b = 0, int c = 0) { return ty | (t << 3) | (a << 8) | (b << 16) | (c << 24); }
constexpr int part_base(int t) { return t ? part_base(t - 1) + k_nsplit(t - 1) + 1 : 0; }
struct ItemTab { uint32_t v[1280]; uint32_t pb[17]; int n; };
constexpr ItemTab make_items() {
  ItemTab T{};
  int n = 0;
  for (int t = 0; t < 16; t++) T.v[n++] = mk_item(IT_GATE, t, 0);
  for (int t = 0; t < 16; t++) for (int a = 0; a < 5; a++) T.v[n++] = mk_item(IT_QKV, t, a);
  for (int t = 0; t < 32; t++) for (int a = 0; a < 4; a++) T.v[n++] = mk_item(IT_BATT, t, a);
  for (int t = 0; t < 16; t++) for (int a = 0; a < 2; a++) T.v[n++] = mk_item(IT_INIT, t, a);
  auto outp = [&](int u) {
    const int ns = k_nsplit(u);
    for (int q = 0; q < ns; q++) for (int a = 0; a < 2; a++) T.v[n++] = mk_item(IT_OUT, u, a, q * 32 / ns, (q + 1) * 32 / ns);
  };
  auto cvt = [&](int v) {
    const int ns = k_nsplit(v), a = ns > 8 ? 4 : 8, c = ns == 4 ? 4 : 1;
    for (int q = 0; q < 128; q += a * c) T.v[n++] = mk_item(IT_CVT, v, a, q / 4, c);
  };
  for (int t = 0; t <= 16; t++) T.pb[t] = part_base(t);
  int cv = 0;
  for (int t = 0; t < 16; t++) {
    outp(t);
    if (t >= CLAG && t < CTAIL) cvt(cv++);
  }
  while (cv < 16) cvt(cv++);
  T.n = n;
  return T;
}
constexpr ItemTab k_items_host = make_items();
constexpr int NITEMS = k_items_host.n;
__constant__ ItemTab c_items = make_items();
__device__ __align__(1024) bf16 g_part[part_base(16) * 128 * DM];

constexpr int AUX_GRID = 132, NST = 7, STG = 32768;
constexpr int A_FULL = NST * STG, A_EMPTY = A_FULL + 64, A_ITEM = A_EMPTY + 64, A_QBAR = A_ITEM + 32, A_QENT = A_QBAR + 128, A_MISC = A_QENT + 256,
              A_SMEM = A_MISC + 64, A_REQ = A_FULL + 56, A_RSP = A_EMPTY + 56, A_MAIL = A_MISC + 48;
static_assert(A_SMEM <= 232448, "smem");
enum { OP_END = 0, OP_O = 1, OP_QKV = 2, OP_OB = 3, OP_PART = 4 };

struct AuxMaps { CUtensorMap xA, wq, wqkv, wo, wob, k, v, oA, oS, obA, obS, qkvS, qkvQ, qkvK, part; };

__device__ __forceinline__ void mbar_wait_long(uint32_t b, uint32_t par) {
  int n = 0;
#pragma unroll 1
  while (!mbar_try(b, par)) { if (++n > (SPIN_MAX << 4)) { g_err = 8; break; } }
}
__device__ __forceinline__ uint64_t mk_desc(uint32_t addr, uint32_t lbo, uint32_t sbo, uint32_t mode) {
  return (uint64_t)((addr & 0x3FFFF) >> 4) | ((uint64_t)(lbo >> 4) << 16) | ((uint64_t)(sbo >> 4) << 32) | ((uint64_t)mode << 62);
}

__global__ void __launch_bounds__(384, 1)
aux_kernel(const __grid_constant__ AuxMaps tm, const bf16* __restrict__ x, const bf16* __restrict__ gate_w, bf16* __restrict__ out) {
  extern __shared__ __align__(1024) unsigned char smem[];
  const uint32_t sb = smem_u32(smem);
  const int tid = threadIdx.x, lane = tid & 31, wid = __shfl_sync(~0u, tid >> 5, 0);
  uint32_t epoch = 0, j0 = 0;
  if (tid == 352) GTA(0);
  if (tid >= 256) epoch = *(volatile uint32_t*)&g_epoch + 1;
  if (tid == 352) j0 = atomicAdd(&g_queue[32], 1u);
  if (tid == 0) {
    mbar_init(sb + A_REQ, 1); mbar_init(sb + A_RSP, 1);
    for (int i = 0; i < NST; i++) { mbar_init(sb + A_FULL + i * 8, 1); mbar_init(sb + A_EMPTY + i * 8, 8); }
    for (int i = 0; i < 16; i++) mbar_init(sb + A_QBAR + i * 8, 4);
    asm volatile("fence.mbarrier_init.release.cluster;" ::: "memory");
  }
  if (tid < 15) prefetch_map(&tm.xA + tid);
  if (tid == 352) GTA(4);
  __syncthreads();
  if (tid == 352) GTA(5);
  uint32_t st = 0, ph = 0;
  auto advance = [&]() { if (++st == NST) { st = 0; ph ^= 1; } };

  if (wid >= 8) {
    asm volatile("setmaxnreg.dec.sync.aligned.u32 40;");
    if (tid == 352) GTA(6);
    auto cnt = [&](int c, uint32_t per) -> bool { return (int)(ldg_rlx32(&g_cnt[c * 8]) - epoch * per) >= 0; };
    auto ready = [&](uint32_t item) -> int {
      const int ty = item & 7, t = (item >> 3) & 31, b = (item >> 17) & 127, n = (((item >> 24) + 1) >> 1) - b;
      int r;
      if (ty == IT_OUT) {
        const int c = C_O + t * 16 + b;
        const bool r0 = cnt(c, 2), r1 = cnt(c + (n > 1), 2), r2 = cnt(c + (n > 2) * 2, 2), r3 = cnt(c + (n > 3) * 3, 2);
        r = r0 ? (r1 ? (r2 ? (r3 ? 4 : 3) : 2) : 1) : 0;
      } else if (ty == IT_XATT) {
        const uint4 v = ldg_rlx128(&g_segcnt[4 * t]);
        const uint32_t e = epoch * 96;
        r = ((int)(v.x - e) >= 0) & ((int)(v.y - e) >= 0) & ((int)(v.z - e) >= 0) & ((int)(v.w - e) >= 0);
      } else if (ty == IT_BATT) {
        r = cnt(C_GATE, 16) & cnt(C_QKV + (t >> 1), 10) & cnt(C_QKV + (max(t - 1, 0) >> 1), 10);
      } else {
        r = ty <= IT_QKV || cnt(ty == IT_INIT ? C_OB + t : C_ACC + t, ty == IT_INIT ? 8 : 132);
      }
      asm volatile("fence.acquire.gpu; fence.proxy.async.global;" ::: "memory");
      return r;
    };
    if (wid == 11 && lane == 0) {
      uint32_t pend = j0 < (uint32_t)NITEMS ? c_items.v[j0] : (uint32_t)IT_END;
      bool xleft = true;
      uint32_t nidx = 0, pidx = j0;
      GTA(1);
      if (pend != 12345) GTA(2);
#pragma unroll 1
      for (uint32_t e = 0;; e++) {
        if (e) mbar_wait_long(sb + A_REQ, (e - 1) & 1);
        uint32_t item = NONE;
        int rdy = 0, spins = 0;
#pragma unroll 1
        while (true) {
          const bool fresh = pend == NONE;
          if (xleft) {
            const uint4 c = ldg_rlx128(&g_queue[0]);
            const uint32_t pr = ldg_rlx32(&g_prog) - (epoch - 1) * (96 * NSEG);
            const bool gates = cnt(C_GATE, 16);
            if (!fresh) rdy = ready(pend);
            auto full = [](uint32_t v) { v = (v | (v >> 2)) & 0x30303030u; return __popc((v | (v >> 1)) & 0x10101010u); };
            const int t = full(c.x) + full(c.y) + full(c.z) + full(c.w);
            xleft = t < 16;
            if (xleft && gates && (int)pr >= 96 * (4 * t - 8 + (int)((XD >> 4 * t) & 15))) {
              const uint32_t j = (atomicAdd(&g_queue[t >> 2], 1u << (t & 3) * 8) >> (t & 3) * 8) & 255;
              if (j < 16) { item = mk_item(IT_XATT, t, j); rdy = 0; nidx = NITEMS + 132 + t * 16 + j; }
            }
          } else if (!fresh) {
            rdy = ready(pend);
          }
          if (item == NONE) {
            if (fresh) {
              pidx = atomicAdd(&g_queue[32], 1u);
              pend = pidx < (uint32_t)NITEMS ? c_items.v[pidx] : (uint32_t)IT_END;
              rdy = ready(pend);
            }
            const int need = (pend & 7) == IT_OUT && xleft ? (((pend >> 24) + 1) >> 1) - ((pend >> 17) & 127) : 1;
            if (pend == IT_END ? !xleft : rdy >= need) { item = pend; pend = NONE; nidx = pidx; }
          }
          if (item != NONE) break;
          if (++spins > SPIN_MAX) { g_err = 10; item = IT_END; break; }
          __nanosleep(50);
        }
        if (e == 0) GTA(3);
        sts128(sb + A_MAIL, item, rdy, nidx, 0);
        mbar_arrive(sb + A_RSP);
        if (item == IT_END) break;
      }
      if (atomicAdd(&g_queue[64], 1u) == AUX_GRID - 1) { *(uint4*)g_queue = make_uint4(0, 0, 0, 0); g_queue[32] = 0; g_queue[64] = 0; g_epoch = epoch; }
      asm volatile("griddepcontrol.wait;" ::: "memory");
    } else if (wid == 8 && lane == 0) {
      uint32_t item = 0;
      auto slot = [&](uint32_t bytes) -> uint32_t {
        mbar_wait_long(sb + A_EMPTY + st * 8, ph ^ 1);
        sts32(sb + A_ITEM + st * 4, item);
        if (bytes) mbar_expect(sb + A_FULL + st * 8, bytes); else mbar_arrive(sb + A_FULL + st * 8);
        return sb + st * STG;
      };
#pragma unroll 1
      for (uint32_t e = 0;; e++) {
        mbar_wait_long(sb + A_RSP, e & 1);
        const uint4 mail = lds128(sb + A_MAIL);
        asm volatile("fence.proxy.async.global;" ::: "memory");
        item = mail.x;
        int rdy = mail.y;
        if ((item & 7) == IT_CVT) {
          const int t = (item >> 3) & 31, rows = (item >> 8) & 255, p0 = c_items.pb[t], np = c_items.pb[t + 1] - p0, per = 24 / rows;
          const uint32_t st0 = st, ph0 = ph;
          const char* src = (const char*)(g_part + ((size_t)p0 * 128 + ((item >> 16) & 255) * 4) * DM);
#pragma unroll 1
          for (int j = item >> 24; j; j--, src += rows * (DM * 2)) {
            if (j == 1 && (CREQ == 0 || (item >> 24) > 1)) mbar_arrive(sb + A_REQ);
#pragma unroll 1
            for (int p = 0; p < np; p += per) {
              const int n = min(per, np - p);
              const uint32_t d = slot(n * rows * (DM * 2));
#pragma unroll 1
              for (int q = 0; q < n; q++) bulk_load(d + q * rows * (DM * 2), src + (size_t)(p + q) * (128 * DM * 2), rows * (DM * 2), sb + A_FULL + st * 8);
              advance();
            }
          }
          if (CREQ && (item >> 24) == 1) {
            if (CREQ == 2) mbar_wait_long(sb + A_FULL + st0 * 8, ph0);
            if (CREQ == 3) mbar_wait_long(sb + A_EMPTY + st0 * 8, ph0);
            mbar_arrive(sb + A_REQ);
          }
          continue;
        }
        int k = (item & 7) == IT_OUT ? ((item >> 16) & 255) * 6 : 0;
        const int k1 = (item & 7) == IT_OUT ? (item >> 24) * 6 : (0x01140103001c1401ull >> ((item & 7) * 8)) & 255;
        const int kreq = max(k1 - KREQ, k);
#pragma unroll 1
        for (; k < k1; k++) {
          item = pin(item);
          const int ty = item & 7, t = (item >> 3) & 31, a = (item >> 8) & 255;
          const bool out_ = ty == IT_OUT, gemm1 = ty == IT_QKV || ty == IT_XATT;
          const int dep = out_ ? k / 12 - ((item >> 17) & 127) : (ty == IT_XATT ? (k >= 20) - 1 : -1);
          if (rdy <= dep || (k == 12 && ty == IT_XATT)) {
            int n = 0;
#pragma unroll 1
            while ((rdy = ready(pin(item))) <= dep) {
              if (++n > SPIN_MAX) { g_err = 7; break; }
              __nanosleep(20);
            }
          }
          const uint32_t fb = sb + A_FULL + st * 8;
          if (out_ || ty == IT_INIT) {
            const uint32_t d = slot(28672);
            tma_load2(d, out_ ? &tm.oA : &tm.obA, k * 32, t * 128, fb);
            tma_load3(d + 8192, out_ ? &tm.wo : &tm.wob, 0, k * 32, a * 5, fb);
          } else if (gemm1 && k < 20) {
            const uint32_t d = slot(32768);
            tma_load2(d, &tm.xA, k * 32, t * 128, fb);
            tma_load3(d + 8192, ty == IT_QKV ? &tm.wqkv : &tm.wq, 0, k * 32, a * 6, fb);
          } else if (gemm1) {
            const uint32_t d = slot(30720);
            tma_load3(d, k < 24 ? &tm.k : &tm.v, 0, (4 * t + (k & 2)) * LK, (2 * a + (k & 1)) * 3, fb);
          } else if (ty == IT_BATT) {
            const uint32_t d = slot(k ? 25600 : 20480);
            tma_load2(d, k ? &tm.qkvK : &tm.qkvQ, k * 640 + a * 160, t * 64 - (k ? 16 : 0), fb);
          } else {
            slot(0);
          }
          if (k == kreq) mbar_arrive(sb + A_REQ);
          advance();
        }
        if (item == IT_END) break;
        if ((0x4a >> (item & 7)) & 1) {
#pragma unroll 1
          for (k = 0; k < 4; k++) { slot(0); advance(); }
        }
      }
    } else if ((wid == 9 || wid == 10) && lane == 0) {
      const uint32_t qb = sb + A_QBAR + (wid - 9) * 64, qe = sb + A_QENT + (wid - 9) * 128;
      for (uint32_t e = 0;; e++) {
        mbar_wait_long(qb + (e & 7) * 8, (e >> 3) & 1);
        const uint4 en = lds128(qe + (e & 7) * 16);
        const int op = en.x & 15, sg = (en.x >> 4) & 15, rel = (en.x >> 8) & 15, nb = (en.x >> 12) & 15;
        if (op == OP_END) break;
        const uint32_t src = sb + sg * STG;
        if (op == OP_O) tma_store3(&tm.oS, src, 0, en.y, en.z);
        else if (op == OP_QKV) tma_store3(&tm.qkvS, src, 0, en.y, en.z);
        else if (op == OP_OB) tma_store2(&tm.obS, src, en.z, en.y);
        else { for (int i = 0; i < nb; i++) tma_store3(&tm.part, src + i * 8192, 0, en.y, en.z + i); }
        bulk_commit();
        bulk_wait_read0();
        asm volatile("mbarrier.arrive.shared::cta.b64 _, [%0], %1;" ::"r"(sb + A_EMPTY + sg * 8), "r"(rel) : "memory");
        if (en.w) {
          bulk_wait0();
          asm volatile("red.relaxed.gpu.global.add.u32 [%0], %1;" ::"l"(&g_cnt[((en.w & 0xFFFF) - 1) * 8]), "r"((en.w >> 16) + 1) : "memory");
        }
      }
      bulk_wait0();
    }
  } else {
    asm volatile("setmaxnreg.inc.sync.aligned.u32 232;");
    const int g = wid >> 2, w = wid & 3;
    uint32_t qn = 0;
    auto wait_full = [&]() { mbar_wait_long(sb + A_FULL + st * 8, ph); };
    auto release = [&](uint32_t s_) { if (lane == 0) mbar_arrive(sb + A_EMPTY + s_ * 8); };
    auto take_pair = [&]() -> uint32_t {
      wait_full();
      const uint32_t s0 = st; advance();
      wait_full();
      const uint32_t s1 = st; advance();
      release(g ? s0 : s1);
      return g ? s1 : s0;
    };
    auto push = [&](uint32_t w0, uint32_t w1, uint32_t w2, uint32_t w3) {
      fence_async_smem();
      if (w == 0 && lane == 0) sts128(sb + A_QENT + g * 128 + (qn & 7) * 16, w0, w1, w2, w3);
      __syncwarp();
      if (lane == 0) mbar_arrive(sb + A_QBAR + g * 64 + (qn & 7) * 8);
      qn++;
    };
    const uint32_t stm = (16 * w + (lane & 7) + (lane & 8)) * 128, stx = lane & 7, sth = lane >> 4;
    auto stage_bf16 = [&](uint32_t dst, const float* d, float s0, float s1, int nks = 12) {
#pragma unroll
      for (int ks = 0; ks < nks; ks++)
        stsm4(dst + (ks >> 2) * 8192 + stm + (((2 * (ks & 3) + sth) ^ stx) << 4), pack2(d[8 * ks] * s0, d[8 * ks + 1] * s0), pack2(d[8 * ks + 2] * s1, d[8 * ks + 3] * s1),
              pack2(d[8 * ks + 4] * s0, d[8 * ks + 5] * s0), pack2(d[8 * ks + 6] * s1, d[8 * ks + 7] * s1));
    };
#pragma unroll 1
    while (true) {
      wait_full();
      const uint32_t item = lds32(sb + A_ITEM + st * 4);
      const int ty = item & 7, t = (item >> 3) & 31, a = (item >> 8) & 255;
      if (ty == IT_QKV || ty == IT_XATT) {
        float acc[192] = {};
        uint32_t prev = 0;
#pragma unroll 1
        for (int k = 0; k < 20; k++) {
          if (k) wait_full();
          const uint32_t s_ = sb + st * STG;
          const uint64_t da = mk_desc(s_, 16, 512, 2), db = mk_desc(s_ + 8192 + g * 12288, 4096, 1024, 1);
          wg_fence();
          wgmma_ss192t(acc, da, db, k);
          wgmma_ss192t(acc + 96, da + 256, db, k);
          wgmma_ss192t(acc, da + 2, db + 128, 1);
          wgmma_ss192t(acc + 96, da + 258, db + 128, 1);
          wg_commit();
          if (k) { wg_wait1(); release(prev); }
          prev = st; advance();
        }
        wg_wait0();
        fence_regs<192>(acc);
        release(prev);
        if (ty == IT_QKV) {
#pragma unroll
          for (int q = 0; q < 2; q++) {
            const uint32_t m = take_pair();
            stage_bf16(sb + m * STG, acc + q * 96, 1.f, 1.f);
            push(OP_QKV | (m << 4) | (4 << 8), t * 128 + q * 64, a * 6 + g * 3, q ? C_QKV + t + 1 : 0);
          }
        } else {
          uint32_t qf[24][4];
#pragma unroll
          for (int ks = 23; ks >= 0; ks--)
#pragma unroll
            for (int j = 0; j < 4; j++)
              asm volatile("cvt.rn.bf16x2.f32 %0, %1, %2;" : "=r"(qf[ks][j]) : "f"(acc[8 * ks + 2 * j + 1]), "f"(acc[8 * ks + 2 * j]));
          float sc[2][40] = {};
          uint32_t kst[2];
#pragma unroll
          for (int q = 0; q < 2; q++) {
            kst[q] = take_pair();
            const uint64_t db = mk_desc(sb + kst[q] * STG, 16, 1024, 1);
            wg_fence();
#pragma unroll
            for (int ks = 0; ks < 12; ks++) wgmma_rs80(sc[q], qf[q * 12 + ks], db + (((ks >> 2) * 10240 + (ks & 3) * 32) >> 4), ks);
            wg_commit();
          }
          const int tt = 16 * (w & 1) + (lane >> 2) - 2 * (lane & 3);
          const float* gp = g_gate + t * 128 + 16 * w + (lane >> 2);
          const float gt[4] = {__ldcg(gp), __ldcg(gp + 8), __ldcg(gp + 64), __ldcg(gp + 72)};
          uint32_t pf[2][5][4];
          float rs[2][2];
          auto softmax = [&](const float* s_, uint32_t (&p)[5][4], float* r) {
            constexpr float SCL = 0.07216878364870322f * 1.4426950408889634f;
            float v[20];
#pragma unroll
            for (int i = 0; i < 20; i++) {
              v[i] = w >= 2 ? s_[20 + i] : s_[i];
              if (i >= 4 && 8 * ((i >> 2) - 1) + (i & 1) > tt + ((i & 2) ? 8 : 0)) v[i] = -INFINITY;
            }
            uint32_t pt[5][2];
#pragma unroll
            for (int h = 0; h < 2; h++) {
              float mx = fmaxf(v[2 * h], v[2 * h + 1]);
#pragma unroll
              for (int j = 1; j < 5; j++) mx = fmaxf(mx, fmaxf(v[4 * j + 2 * h], v[4 * j + 2 * h + 1]));
              mx = fmaxf(mx, __shfl_xor_sync(~0u, mx, 1));
              mx = fmaxf(mx, __shfl_xor_sync(~0u, mx, 2));
              const float mo = mx * SCL;
              float sum = 0.f;
#pragma unroll
              for (int j = 0; j < 5; j++) {
                const float e0 = ex2(fmaf(v[4 * j + 2 * h], SCL, -mo)), e1 = ex2(fmaf(v[4 * j + 2 * h + 1], SCL, -mo));
                pt[j][h] = pack2(e0, e1);
                sum += bf_lo(pt[j][h]) + bf_hi(pt[j][h]);
              }
              sum += __shfl_xor_sync(~0u, sum, 1);
              sum += __shfl_xor_sync(~0u, sum, 2);
              r[h] = rcp(sum);
            }
#pragma unroll
            for (int J = 0; J < 10; J++)
#pragma unroll
              for (int h = 0; h < 2; h++) p[J >> 1][(J & 1) * 2 + h] = (J >= 5) == (w >= 2) ? pt[J % 5][h] : 0u;
          };
          wg_wait1();
          fence_regs<40>(sc[0]);
          release(kst[0]);
          softmax(sc[0], pf[0], rs[0]);
#pragma unroll
          for (int q = 0; q < 2; q++) {
            const uint32_t m = take_pair();
            const uint64_t db = mk_desc(sb + m * STG, 10240, 1024, 1);
            float o[96] = {};
            wg_fence();
#pragma unroll
            for (int ks = 0; ks < 5; ks++) wgmma_rs192t(o, pf[q][ks], db + ks * 128, ks);
            wg_commit();
            if (q == 0) {
              wg_wait1();
              fence_regs<40>(sc[1]);
              release(kst[1]);
              softmax(sc[1], pf[1], rs[1]);
            }
            wg_wait0();
            fence_regs<96>(o);
            bar_sync(1 + g, 128);
            stage_bf16(sb + m * STG, o, rs[q][0] * gt[2 * q], rs[q][1] * gt[2 * q + 1]);
            push(OP_O | (m << 4) | (4 << 8), t * 128 + q * 64, a * 6 + g * 3, q ? C_O + t * 16 + a + 1 : 0);
          }
        }
      } else if (ty == IT_OUT || ty == IT_INIT) {
        float acc[160] = {};
        const int hb = (item >> 16) & 255, nh = (item >> 24) - hb, nk = ty == IT_OUT ? nh * 6 : 20, jh = a & 1;
        const uint32_t ln = pin(lane), ao = (g * 64 + 16 * w + (ln & 15)) * 64 + (((ln >> 4) ^ ((ln >> 1) & 3)) << 4);
        if (PP && g == 1) bar_arrive(4, 256);
#pragma unroll 1
        for (int k = 0; k < nk; k += 2) {
          uint32_t af[4][4], sg[2];
#pragma unroll
          for (int e = 0; e < 2; e++) {
            if (k + e) wait_full();
            sg[e] = st;
            ldsm4(af[2 * e], sb + st * STG + ao);
            ldsm4(af[2 * e + 1], sb + st * STG + (ao ^ 32));
            advance();
          }
          if (PP) bar_sync(4 + g, 256);
          wg_fence();
#pragma unroll
          for (int e = 0; e < 4; e++) {
            const uint64_t db = mk_desc(sb + sg[e >> 1] * STG + 8192 + (e & 1) * 2048, 4096, 1024, 1);
            if (PP == 2 && e == 3 && (g == 0 || k + 2 < nk)) bar_arrive(5 - g, 256);
            wgmma_rs192t(acc, af[e], db, 1);
            if (PP == 3 && e == 3 && (g == 0 || k + 2 < nk)) bar_arrive(5 - g, 256);
            wgmma_rs128t(acc + 96, af[e], db + 768, 1);
          }
          wg_commit();
          if (PP == 1 && (g == 0 || k + 2 < nk)) bar_arrive(5 - g, 256);
          wg_wait0();
          release(sg[0]); release(sg[1]);
        }
        fence_regs<160>(acc);
        const uint32_t row = (ty == IT_OUT ? c_items.pb[t] + hb / nh : c_items.pb[t + 1] - 1) * 128 + g * 64;
#pragma unroll
        for (int q = 0; q < 2; q++) {
          const uint32_t m = take_pair();
          stage_bf16(sb + m * STG, acc + q * 96, 1.f, 1.f, q ? 8 : 12);
          push(OP_PART | (m << 4) | (4 << 8) | ((3 - q) << 12), row, jh * 5 + q * 3, q ? (C_ACC + t + 1) | ((ty == IT_OUT ? nh - 1 : 0) << 16) : 0);
        }
      } else if (ty == IT_BATT) {
        const uint32_t sq = st; advance();
        wait_full();
        const uint32_t sk = st; advance();
        wait_full();
        const uint32_t sv = st; advance();
        const int h = tid & 7;
#pragma unroll 1
        for (int p = 0; p < 2; p++) {
          const int tok = (tid >> 3) + 32 * p, pos = t * 64 + tok;
          const uint32_t qa = sb + sq * STG + tok * 320 + h * 40, ka = sb + sk * STG + (tok + 16) * 320 + h * 40, va = sb + sv * STG + (tok + 16) * 320 + h * 40;
          const float gt = __ldcg(g_gate + 2048 + pos);
          float q[20], l[8];
#pragma unroll
          for (int i = 0; i < 5; i++) { const uint2 u = lds64(qa + i * 8); q[4 * i] = bf_lo(u.x); q[4 * i + 1] = bf_hi(u.x); q[4 * i + 2] = bf_lo(u.y); q[4 * i + 3] = bf_hi(u.y); }
          float mx = -INFINITY;
#pragma unroll
          for (int j = 0; j < 8; j++) {
            float s0 = 0.f, s1 = 0.f;
#pragma unroll
            for (int i = 0; i < 5; i++) {
              const uint2 u = lds64(ka - j * 640 + i * 8);
              s0 = fmaf(q[4 * i], bf_lo(u.x), s0); s1 = fmaf(q[4 * i + 1], bf_hi(u.x), s1);
              s0 = fmaf(q[4 * i + 2], bf_lo(u.y), s0); s1 = fmaf(q[4 * i + 3], bf_hi(u.y), s1);
            }
            l[j] = pos - 2 * j >= 0 ? s0 + s1 : -INFINITY;
            mx = fmaxf(mx, l[j]);
          }
          constexpr float SCL = 0.22360679774997896f * 1.4426950408889634f;
          const float mo = mx * SCL;
          float sum = 0.f;
#pragma unroll
          for (int j = 0; j < 8; j++) { l[j] = ex2(fmaf(l[j], SCL, -mo)); sum += l[j]; }
          const float r = gt * rcp(sum);
#pragma unroll
          for (int i = 0; i < 20; i++) q[i] = 0.f;
#pragma unroll
          for (int j = 0; j < 8; j++) {
#pragma unroll
            for (int i = 0; i < 5; i++) {
              const uint2 u = lds64(va - j * 640 + i * 8);
              q[4 * i] = fmaf(l[j], bf_lo(u.x), q[4 * i]); q[4 * i + 1] = fmaf(l[j], bf_hi(u.x), q[4 * i + 1]);
              q[4 * i + 2] = fmaf(l[j], bf_lo(u.y), q[4 * i + 2]); q[4 * i + 3] = fmaf(l[j], bf_hi(u.y), q[4 * i + 3]);
            }
          }
#pragma unroll
          for (int i = 0; i < 5; i++) sts64(qa + i * 8, pack2(q[4 * i] * r, q[4 * i + 1] * r), pack2(q[4 * i + 2] * r, q[4 * i + 3] * r));
        }
        __syncwarp();
        release(sk); release(sv);
        fence_async_smem();
        bar_sync(3, 256);
        if (g == 0) push(OP_OB | (sq << 4) | (8 << 8), t * 64, a * 160, C_OB + (t >> 1) + 1);
      } else if (ty == IT_GATE) {
        release(st); advance();
        uint4 gw[3];
#pragma unroll
        for (int i = 0; i < 3; i++) gw[i] = (i < 2 || lane < 16) ? __ldg((const uint4*)gate_w + lane + 32 * i) : make_uint4(0, 0, 0, 0);
        const uint4* xr = (const uint4*)(x + (size_t)(t * 128 + wid * 16) * DM) + lane;
        uint4 v[16][3];
#pragma unroll
        for (int r = 0; r < 16; r++)
#pragma unroll
          for (int i = 0; i < 3; i++) v[r][i] = (i < 2 || lane < 16) ? __ldg(xr + r * (DM / 8) + 32 * i) : make_uint4(0, 0, 0, 0);
        float z = 0.f;
#pragma unroll
        for (int r = 0; r < 16; r++) {
          float s_ = 0.f;
#pragma unroll
          for (int i = 0; i < 3; i++) {
            const uint32_t p0 = hmul2(v[r][i].x, gw[i].x), p1 = hmul2(v[r][i].y, gw[i].y), p2 = hmul2(v[r][i].z, gw[i].z), p3 = hmul2(v[r][i].w, gw[i].w);
            s_ += ((bf_lo(p0) + bf_hi(p0)) + (bf_lo(p1) + bf_hi(p1))) + ((bf_lo(p2) + bf_hi(p2)) + (bf_lo(p3) + bf_hi(p3)));
          }
#pragma unroll
          for (int o = 16; o; o >>= 1) s_ += __shfl_xor_sync(~0u, s_, o);
          if (lane == r) z = s_;
        }
        z = bf_lo(pack2(z, 0.f));
        const float gv = bf_lo(pack2(1.f / (1.f + __expf(-z)), 0.f));
        if (lane < 16) { g_gate[t * 128 + wid * 16 + lane] = gv; g_gate[2048 + t * 128 + wid * 16 + lane] = bf_lo(pack2(1.f - gv, 0.f)); }
        __threadfence();
        bar_sync(3, 256);
        if (tid == 0) asm volatile("red.release.gpu.global.add.u32 [%0], 1;" ::"l"(&g_cnt[C_GATE * 8]) : "memory");
      } else if (ty == IT_CVT) {
        const int np = c_items.pb[t + 1] - c_items.pb[t];
        auto add_parts = [&](auto W_) {
          constexpr int W = decltype(W_)::value, PER = 6 / W, CH = W * 4 * (DM * 2);
          char* dst = (char*)(out + (t * 128 + ((item >> 16) & 255) * 4) * DM) + tid * (W * 4);
#pragma unroll 1
          for (int j = item >> 24; j; j--, dst += CH) {
            float sum[5][2 * W] = {};
#pragma unroll 1
            for (int p = 0; p < np; p += PER) {
              wait_full();
              const uint32_t src = sb + st * STG + tid * (W * 4);
#pragma unroll
              for (int q = 0; q < PER; q++) {
                if (p + q < np) {
#pragma unroll
                  for (int i = 0; i < 5; i++) {
                    if (W == 2) {
                      const uint2 v = lds64(src + q * CH + i * 2048);
                      sum[i][0] += bf_lo(v.x); sum[i][1] += bf_hi(v.x); sum[i][2 * W - 2] += bf_lo(v.y); sum[i][2 * W - 1] += bf_hi(v.y);
                    } else {
                      const uint32_t v = lds32(src + q * CH + i * 1024);
                      sum[i][0] += bf_lo(v); sum[i][1] += bf_hi(v);
                    }
                  }
                }
              }
              __syncwarp();
              release(st); advance();
            }
#pragma unroll
            for (int i = 0; i < 5; i++) {
              if (W == 2) *(uint2*)(dst + i * 2048) = make_uint2(pack2(sum[i][0], sum[i][1]), pack2(sum[i][2 * W - 2], sum[i][2 * W - 1]));
              else *(uint32_t*)(dst + i * 1024) = pack2(sum[i][0], sum[i][1]);
            }
          }
        };
        if (a == 8) add_parts(std::integral_constant<int, 2>{});
        else add_parts(std::integral_constant<int, 1>{});
      } else {
        release(st);
        push(OP_END, 0, 0, 0);
        break;
      }
    }
  }
}

typedef CUresult (*EncFn)(CUtensorMap*, CUtensorMapDataType, cuuint32_t, void*, const cuuint64_t*, const cuuint64_t*, const cuuint32_t*,
                          const cuuint32_t*, CUtensorMapInterleave, CUtensorMapSwizzle, CUtensorMapL2promotion, CUtensorMapFloatOOBfill);

#define PROMO CU_TENSOR_MAP_L2_PROMOTION_L2_128B
void make_map(EncFn enc, CUtensorMap* tm, const void* base, int rank, const cuuint64_t* dims, const cuuint64_t* strides, const cuuint32_t* box,
              CUtensorMapSwizzle sw = CU_TENSOR_MAP_SWIZZLE_128B, CUtensorMapDataType dt = CU_TENSOR_MAP_DATA_TYPE_BFLOAT16) {
  const cuuint32_t es[5] = {1, 1, 1, 1, 1};
  enc(tm, dt, rank, const_cast<void*>(base), dims, strides, box, es, CU_TENSOR_MAP_INTERLEAVE_NONE, sw, PROMO,
      CU_TENSOR_MAP_FLOAT_OOB_FILL_NONE);
}
void map_blk(EncFn enc, CUtensorMap* tm, const void* base, int rows, int cols, int brows, int bblk) {
  const cuuint64_t d[3] = {64, (cuuint64_t)rows, (cuuint64_t)cols / 64}, st[2] = {(cuuint64_t)cols * 2, 128};
  const cuuint32_t b[3] = {64, (cuuint32_t)brows, (cuuint32_t)bblk};
  make_map(enc, tm, base, 3, d, st, b);
}
void map_2d(EncFn enc, CUtensorMap* tm, const void* base, int rows, int cols, int brows, int bcols, CUtensorMapSwizzle sw) {
  const cuuint64_t d[2] = {(cuuint64_t)cols, (cuuint64_t)rows}, st[1] = {(cuuint64_t)cols * 2};
  const cuuint32_t b[2] = {(cuuint32_t)bcols, (cuuint32_t)brows};
  make_map(enc, tm, base, 2, d, st, b, sw);
}

}

extern "C" void kernel_launch(void* const* d_in, const int* in_sizes, int n_in, void* d_out, int out_size) {
  const bf16* x = (const bf16*)d_in[0];
  const bf16* mem0 = (const bf16*)d_in[1];
  const bf16* Wq = (const bf16*)d_in[2];
  const bf16* Wk = (const bf16*)d_in[3];
  const bf16* Wv = (const bf16*)d_in[4];
  const bf16* Wo = (const bf16*)d_in[5];
  const bf16* wqkv = (const bf16*)d_in[8];
  const bf16* wob = (const bf16*)d_in[9];
  const bf16* gate_w = (const bf16*)d_in[10];
  static EncFn enc = nullptr;
  static void *pK = nullptr, *pV = nullptr, *pO = nullptr, *pQ = nullptr, *pB = nullptr, *pA = nullptr;
  if (!enc) {
    void* fn = nullptr;
    cudaDriverEntryPointQueryResult qr;
    cudaGetDriverEntryPoint("cuTensorMapEncodeTiled", &fn, cudaEnableDefault, &qr);
    enc = (EncFn)fn;
    cudaGetSymbolAddress(&pK, g_K);
    cudaGetSymbolAddress(&pV, g_V);
    cudaGetSymbolAddress(&pO, g_O);
    cudaGetSymbolAddress(&pQ, g_qkv);
    cudaGetSymbolAddress(&pB, g_Ob);
    cudaGetSymbolAddress(&pA, g_part);
    cudaFuncSetAttribute(rec_kernel, cudaFuncAttributeMaxDynamicSharedMemorySize, R_SMEM_ALLOC);
    cudaFuncSetAttribute(aux_kernel, cudaFuncAttributeMaxDynamicSharedMemorySize, A_SMEM);
  }
  CUtensorMap tmX, tmK, tmV, tmWq, tmWq2, tmWk, tmWv, tmWo;
  map_2d(enc, &tmWq, Wq, DM, HD, 144, 64, CU_TENSOR_MAP_SWIZZLE_128B);
  map_2d(enc, &tmWq2, Wq, DM, HD, 32, 64, CU_TENSOR_MAP_SWIZZLE_128B);
  map_2d(enc, &tmWk, Wk, DM, HD, 128, 64, CU_TENSOR_MAP_SWIZZLE_128B);
  map_2d(enc, &tmWv, Wv, DM, HD, 128, 64, CU_TENSOR_MAP_SWIZZLE_128B);
  {
    const cuuint64_t d[3] = {32, HD, 20}, st[2] = {DM * 2, 64};
    const cuuint32_t b[3] = {32, 64, 7};
    make_map(enc, &tmWo, Wo, 3, d, st, b, CU_TENSOR_MAP_SWIZZLE_64B);
  }
  map_blk(enc, &tmX, x, S_TOK, DM, 32, 10);
  map_2d(enc, &tmK, pK, NSEG * LK, HD, LK, 64, CU_TENSOR_MAP_SWIZZLE_128B);
  map_2d(enc, &tmV, pV, NSEG * LK, HD, LK, 64, CU_TENSOR_MAP_SWIZZLE_128B);
  AuxMaps am;
  map_2d(enc, &am.xA, x, S_TOK, DM, 128, 32, CU_TENSOR_MAP_SWIZZLE_64B);
  map_blk(enc, &am.wq, Wq, DM, HD, 32, 6);
  map_blk(enc, &am.wqkv, wqkv, DM, 3 * DM, 32, 6);
  map_blk(enc, &am.wo, Wo, HD, DM, 32, 5);
  map_blk(enc, &am.wob, wob, DM, DM, 32, 5);
  map_blk(enc, &am.k, pK, NSEG * LK, HD, 80, 3);
  map_blk(enc, &am.v, pV, NSEG * LK, HD, 80, 3);
  map_2d(enc, &am.oA, pO, S_TOK, HD, 128, 32, CU_TENSOR_MAP_SWIZZLE_64B);
  map_blk(enc, &am.oS, pO, S_TOK, HD, 64, 3);
  map_2d(enc, &am.obA, pB, S_TOK, DM, 128, 32, CU_TENSOR_MAP_SWIZZLE_64B);
  map_2d(enc, &am.obS, pB, S_TOK, DM, 64, 160, CU_TENSOR_MAP_SWIZZLE_NONE);
  map_blk(enc, &am.qkvS, pQ, S_TOK, 3 * DM, 64, 3);
  map_2d(enc, &am.qkvQ, pQ, S_TOK, 3 * DM, 64, 160, CU_TENSOR_MAP_SWIZZLE_NONE);
  map_2d(enc, &am.qkvK, pQ, S_TOK, 3 * DM, 80, 160, CU_TENSOR_MAP_SWIZZLE_NONE);
  map_blk(enc, &am.part, pA, part_base(16) * 128, DM, 64, 1);
  rec_kernel<<<96, 256, R_SMEM_ALLOC, cudaStreamPerThread>>>(tmX, tmK, tmV, tmWq, tmWq2, tmWk, tmWv, tmWo, mem0, Wq, Wo, x);
  cudaLaunchConfig_t cfg = {};
  cfg.gridDim = dim3(AUX_GRID); cfg.blockDim = dim3(384); cfg.dynamicSmemBytes = A_SMEM; cfg.stream = cudaStreamPerThread;
  cudaLaunchAttribute at[1];
  at[0].id = cudaLaunchAttributeProgrammaticStreamSerialization;
  at[0].val.programmaticStreamSerializationAllowed = 1;
  cfg.attrs = at;
  cfg.numAttrs = 1;
  cudaLaunchKernelEx(&cfg, aux_kernel, am, x, gate_w, (bf16*)d_out);
}
```

```cpp
#include <cuda_runtime.h>
#include <cuda_bf16.h>
#include <cuda.h>
#include <stdint.h>
#include <type_traits>

typedef __nv_bfloat16 bf16;

namespace {

constexpr int S_TOK = 2048, DM = 640, NH = 32, DH = 192, HD = NH * DH, SEG = 32, NSEG = 64, MT = 8, LK = 40;
constexpr int SPIN_MAX = 1 << 20;

#define RB_LINE 384
constexpr int RB_SIZE = 160 * RB_LINE;
__device__ __align__(4096) unsigned char g_red[4 * RB_SIZE];
__device__ unsigned long long g_rec[96];
__device__ uint32_t g_epoch;
__device__ uint32_t g_err;
__device__ __align__(16) uint32_t g_segcnt[NSEG];
__device__ __align__(1024) bf16 g_K[NSEG * LK * HD];
__device__ __align__(1024) bf16 g_V[NSEG * LK * HD];
__device__ __align__(1024) bf16 g_O[S_TOK * HD];
__device__ __align__(1024) bf16 g_qkv[S_TOK * 3 * DM];
__device__ __align__(1024) bf16 g_Ob[S_TOK * DM];
__device__ float g_gate[2 * S_TOK];
__device__ uint32_t g_cnt[512 * 8];
__device__ __align__(128) uint32_t g_queue[3 * 32];
__device__ uint32_t g_prog;
#define GTR(i) do {} while (0)
#define GTA(i) do {} while (0)

__device__ __forceinline__ uint32_t smem_u32(const void* p) { return (uint32_t)__cvta_generic_to_shared(p); }
__device__ __forceinline__ uint32_t clk32() { uint32_t t; asm volatile("mov.u32 %0, %%clock;" : "=r"(t)::"memory"); return t; }
__device__ __forceinline__ uint32_t mapa(uint32_t a, uint32_t r) { uint32_t o; asm("mapa.shared::cluster.u32 %0, %1, %2;" : "=r"(o) : "r"(a), "r"(r)); return o; }
__device__ __forceinline__ void mbar_init(uint32_t b, uint32_t c) { asm volatile("mbarrier.init.shared::cta.b64 [%0], %1;" ::"r"(b), "r"(c) : "memory"); }
__device__ __forceinline__ void mbar_expect(uint32_t b, uint32_t bytes) { asm volatile("mbarrier.arrive.expect_tx.shared::cta.b64 _, [%0], %1;" ::"r"(b), "r"(bytes) : "memory"); }
__device__ __forceinline__ void mbar_arrive(uint32_t b) { asm volatile("mbarrier.arrive.shared::cta.b64 _, [%0];" ::"r"(b) : "memory"); }
__device__ __forceinline__ bool mbar_try(uint32_t b, uint32_t par) {
  uint32_t p;
  asm volatile("{.reg .pred p; mbarrier.try_wait.parity.shared::cta.b64 p, [%1], %2; selp.u32 %0,1,0,p;}" : "=r"(p) : "r"(b), "r"(par) : "memory");
  return p;
}
__device__ __forceinline__ bool mbar_test(uint32_t b, uint32_t par) {
  uint32_t p;
  asm volatile("{.reg .pred p; mbarrier.test_wait.parity.shared::cta.b64 p, [%1], %2; selp.u32 %0,1,0,p;}" : "=r"(p) : "r"(b), "r"(par) : "memory");
  return p;
}
__device__ __forceinline__ bool mbar_try_cl(uint32_t b, uint32_t par) {
  uint32_t p;
  asm volatile("{.reg .pred p; mbarrier.try_wait.parity.acquire.cluster.shared::cta.b64 p, [%1], %2; selp.u32 %0,1,0,p;}" : "=r"(p) : "r"(b), "r"(par) : "memory");
  return p;
}
__device__ __forceinline__ void mbar_wait(uint32_t b, uint32_t par) {
  int n = 0;
#pragma unroll 1
  while (!mbar_try(b, par)) { if (++n > SPIN_MAX) { g_err = 1; break; } }
}
__device__ __forceinline__ void mbar_wait_cl(uint32_t b, uint32_t par) {
  int n = 0;
#pragma unroll 1
  while (!mbar_try_cl(b, par)) { if (++n > SPIN_MAX) { g_err = 2; break; } }
}
__device__ __forceinline__ void cluster_sync() { asm volatile("barrier.cluster.arrive.release.aligned; barrier.cluster.wait.acquire.aligned;" ::: "memory"); }
__device__ __forceinline__ void bar_sync(int id, int n) { asm volatile("bar.sync %0, %1;" ::"r"(id), "r"(n) : "memory"); }
__device__ __forceinline__ void bar_arrive(int id, int n) { asm volatile("bar.arrive %0, %1;" ::"r"(id), "r"(n) : "memory"); }
__device__ __forceinline__ void fence_async_smem() { asm volatile("fence.proxy.async.shared::cta;" ::: "memory"); }
__device__ __forceinline__ void ldsm4(uint32_t* r, uint32_t a) {
  asm volatile("ldmatrix.sync.aligned.m8n8.x4.shared.b16 {%0,%1,%2,%3}, [%4];" : "=r"(r[0]), "=r"(r[1]), "=r"(r[2]), "=r"(r[3]) : "r"(a) : "memory");
}
__device__ __forceinline__ void ldsm4t(uint32_t* r, uint32_t a) {
  asm volatile("ldmatrix.sync.aligned.m8n8.x4.trans.shared.b16 {%0,%1,%2,%3}, [%4];" : "=r"(r[0]), "=r"(r[1]), "=r"(r[2]), "=r"(r[3]) : "r"(a) : "memory");
}
__device__ __forceinline__ void ldsm2t(uint32_t* r, uint32_t a) {
  asm volatile("ldmatrix.sync.aligned.m8n8.x2.trans.shared.b16 {%0,%1}, [%2];" : "=r"(r[0]), "=r"(r[1]) : "r"(a) : "memory");
}
__device__ __forceinline__ void stsm4t(uint32_t a, uint32_t r0, uint32_t r1, uint32_t r2, uint32_t r3) {
  asm volatile("stmatrix.sync.aligned.m8n8.x4.trans.shared.b16 [%0], {%1,%2,%3,%4};" ::"r"(a), "r"(r0), "r"(r1), "r"(r2), "r"(r3) : "memory");
}
__device__ __forceinline__ void stsm2t(uint32_t a, uint32_t r0, uint32_t r1) {
  asm volatile("stmatrix.sync.aligned.m8n8.x2.trans.shared.b16 [%0], {%1,%2};" ::"r"(a), "r"(r0), "r"(r1) : "memory");
}
__device__ __forceinline__ uint32_t movmat(uint32_t a) { uint32_t d; asm volatile("movmatrix.sync.aligned.m8n8.trans.b16 %0, %1;" : "=r"(d) : "r"(a)); return d; }
__device__ __forceinline__ void mma16816(float* d, const uint32_t* a, uint32_t b0, uint32_t b1) {
  asm volatile("mma.sync.aligned.m16n8k16.row.col.f32.bf16.bf16.f32 {%0,%1,%2,%3}, {%4,%5,%6,%7}, {%8,%9}, {%0,%1,%2,%3};"
               : "+f"(d[0]), "+f"(d[1]), "+f"(d[2]), "+f"(d[3]) : "r"(a[0]), "r"(a[1]), "r"(a[2]), "r"(a[3]), "r"(b0), "r"(b1));
}
__device__ __forceinline__ void mma1688(float* d, uint32_t a0, uint32_t a1, uint32_t b0) {
  asm volatile("mma.sync.aligned.m16n8k8.row.col.f32.bf16.bf16.f32 {%0,%1,%2,%3}, {%4,%5}, {%6}, {%0,%1,%2,%3};"
               : "+f"(d[0]), "+f"(d[1]), "+f"(d[2]), "+f"(d[3]) : "r"(a0), "r"(a1), "r"(b0));
}
__device__ __forceinline__ uint32_t pack2(float lo, float hi) { uint32_t r; asm("cvt.rn.bf16x2.f32 %0, %1, %2;" : "=r"(r) : "f"(hi), "f"(lo)); return r; }
__device__ __forceinline__ float bf_lo(uint32_t w) { return __uint_as_float(w << 16); }
__device__ __forceinline__ float bf_hi(uint32_t w) { return __uint_as_float(w & 0xffff0000u); }
__device__ __forceinline__ float ex2(float x) { float y; asm("ex2.approx.ftz.f32 %0, %1;" : "=f"(y) : "f"(x)); return y; }
__device__ __forceinline__ void sts128(uint32_t a, uint32_t x, uint32_t y, uint32_t z, uint32_t w) { asm volatile("st.shared.v4.b32 [%0], {%1,%2,%3,%4};" ::"r"(a), "r"(x), "r"(y), "r"(z), "r"(w) : "memory"); }
__device__ __forceinline__ void sts128f(uint32_t a, float x, float y, float z, float w) { asm volatile("st.shared.v4.f32 [%0], {%1,%2,%3,%4};" ::"r"(a), "f"(x), "f"(y), "f"(z), "f"(w) : "memory"); }
__device__ __forceinline__ void sts64f(uint32_t a, float x, float y) { asm volatile("st.shared.v2.f32 [%0], {%1,%2};" ::"r"(a), "f"(x), "f"(y) : "memory"); }
__device__ __forceinline__ void sts32(uint32_t a, uint32_t x) { asm volatile("st.shared.b32 [%0], %1;" ::"r"(a), "r"(x) : "memory"); }
__device__ __forceinline__ void smax32(uint32_t a, uint32_t x) { asm volatile("red.shared.max.u32 [%0], %1;" ::"r"(a), "r"(x) : "memory"); }
__device__ __forceinline__ uint32_t lds32(uint32_t a) { uint32_t v; asm volatile("ld.shared.b32 %0, [%1];" : "=r"(v) : "r"(a) : "memory"); return v; }
__device__ __forceinline__ float4 lds128f(uint32_t a) { float4 v; asm volatile("ld.shared.v4.f32 {%0,%1,%2,%3}, [%4];" : "=f"(v.x), "=f"(v.y), "=f"(v.z), "=f"(v.w) : "r"(a) : "memory"); return v; }
__device__ __forceinline__ uint4 lds128(uint32_t a) { uint4 v; asm volatile("ld.shared.v4.b32 {%0,%1,%2,%3}, [%4];" : "=r"(v.x), "=r"(v.y), "=r"(v.z), "=r"(v.w) : "r"(a) : "memory"); return v; }
__device__ __forceinline__ float2 lds64f(uint32_t a) { float2 v; asm volatile("ld.shared.v2.f32 {%0,%1}, [%2];" : "=f"(v.x), "=f"(v.y) : "r"(a) : "memory"); return v; }
__device__ __forceinline__ void st_async2(uint32_t a, uint32_t x, uint32_t y, uint32_t bar) {
  asm volatile("st.async.weak.shared::cluster.mbarrier::complete_tx::bytes.v2.b32 [%0], {%1,%2}, [%3];" ::"r"(a), "r"(x), "r"(y), "r"(bar) : "memory");
}
__device__ __forceinline__ void st_async4(uint32_t a, uint32_t x, uint32_t y, uint32_t z, uint32_t w, uint32_t bar) {
  asm volatile("st.async.weak.shared::cluster.mbarrier::complete_tx::bytes.v4.b32 [%0], {%1,%2,%3,%4}, [%5];" ::"r"(a), "r"(x), "r"(y), "r"(z), "r"(w), "r"(bar) : "memory");
}
__device__ __forceinline__ void sts64(uint32_t a, uint32_t x, uint32_t y) { asm volatile("st.shared.v2.b32 [%0], {%1,%2};" ::"r"(a), "r"(x), "r"(y) : "memory"); }
__device__ __forceinline__ bool bar_red_or(int id, int n, bool q) {
  uint32_t r;
  asm volatile("{.reg .pred p, q; setp.ne.u32 q, %3, 0; barrier.cta.red.or.aligned.pred p, %1, %2, q; selp.u32 %0,1,0,p;}" : "=r"(r) : "r"(id), "r"(n), "r"((uint32_t)q) : "memory");
  return r;
}
__device__ __forceinline__ float rcp(float x) { float y; asm("rcp.approx.ftz.f32 %0, %1;" : "=f"(y) : "f"(x)); return y; }
__device__ __forceinline__ uint32_t hadd2(uint32_t a, uint32_t b) { uint32_t r; asm("add.rn.bf16x2 %0, %1, %2;" : "=r"(r) : "r"(a), "r"(b)); return r; }
__device__ __forceinline__ uint32_t pin(uint32_t v) { asm volatile("" : "+r"(v)); return v; }
template <int ID> __device__ __forceinline__ void sched_fence_(uint32_t a) {
  asm volatile("{.reg .pred p;\nsetp.eq.u32 p, %0, %1;\nSF: @p pmevent 0;\n@p bra.uni SF;}" ::"r"(a), "n"(0x40000000 + ID) : "memory");
}
#define sched_fence(a) sched_fence_<__LINE__>(a)
__device__ __forceinline__ bool elect() {
  uint32_t p;
  asm volatile("{.reg .pred p; elect.sync _|p, 0xffffffff; selp.u32 %0,1,0,p;}" : "=r"(p));
  return p;
}
__device__ __forceinline__ uint32_t opaque(uint32_t v) { return __shfl_sync(~0u, v, threadIdx.x & 31); }
__device__ __forceinline__ uint4 ldg_rlx128(const void* p) {
  uint4 v; asm volatile("ld.relaxed.gpu.global.v4.b32 {%0,%1,%2,%3}, [%4];" : "=r"(v.x), "=r"(v.y), "=r"(v.z), "=r"(v.w) : "l"(p) : "memory"); return v;
}
__device__ __forceinline__ uint2 ldg_rlx64(const void* p) {
  uint2 v; asm volatile("{.reg .b64 t; ld.relaxed.gpu.global.b64 t, [%2]; mov.b64 {%0,%1}, t;}" : "=r"(v.x), "=r"(v.y) : "l"(p) : "memory"); return v;
}
__device__ __forceinline__ uint32_t hmaxabs2(uint32_t a, uint32_t b) { uint32_t r; asm("max.xorsign.abs.bf16x2 %0, %1, %2;" : "=r"(r) : "r"(a), "r"(b)); return r; }
__device__ __forceinline__ uint32_t ldg_rlx32(const void* p) {
  uint32_t v; asm volatile("ld.relaxed.gpu.global.b32 %0, [%1];" : "=r"(v) : "l"(p) : "memory"); return v;
}
__device__ __forceinline__ void spin_until(uint32_t t0, int d) {
#pragma unroll 1
  while ((int)(clk32() - t0) < d) {}
}
__device__ __forceinline__ void stg_rlx64(void* p, uint32_t a, uint32_t b) {
  asm volatile("{.reg .b64 t; mov.b64 t, {%1,%2}; st.relaxed.gpu.global.b64 [%0], t;}" ::"l"(p), "r"(a), "r"(b) : "memory");
}
__device__ __forceinline__ uint32_t ldg_acq32(const void* p) { uint32_t v; asm volatile("ld.acquire.gpu.global.b32 %0, [%1];" : "=r"(v) : "l"(p) : "memory"); return v; }
__device__ __forceinline__ void stg_rel32(void* p, uint32_t v) { asm volatile("st.release.gpu.global.b32 [%0], %1;" ::"l"(p), "r"(v) : "memory"); }
__device__ __forceinline__ void cp_async16(uint32_t dst, const void* src) { asm volatile("cp.async.cg.shared.global [%0], [%1], 16;" ::"r"(dst), "l"(src) : "memory"); }
__device__ __forceinline__ void cp_async_wait_all() { asm volatile("cp.async.wait_all;" ::: "memory"); }
__device__ __forceinline__ void prefetch_l2(const void* p) { asm volatile("prefetch.global.L2 [%0];" ::"l"(p)); }
__device__ __forceinline__ void tma_load3(uint32_t dst, const CUtensorMap* tm, int c0, int c1, int c2, uint32_t bar) {
  asm volatile("cp.async.bulk.tensor.3d.shared::cluster.global.mbarrier::complete_tx::bytes [%0], [%1, {%3,%4,%5}], [%2];"
               ::"r"(dst), "l"(tm), "r"(bar), "r"(c0), "r"(c1), "r"(c2) : "memory");
}
__device__ __forceinline__ void tma_load2(uint32_t dst, const CUtensorMap* tm, int c0, int c1, uint32_t bar) {
  asm volatile("cp.async.bulk.tensor.2d.shared::cluster.global.mbarrier::complete_tx::bytes [%0], [%1, {%3,%4}], [%2];"
               ::"r"(dst), "l"(tm), "r"(bar), "r"(c0), "r"(c1) : "memory");
}
__device__ __forceinline__ void bulk_load(uint32_t dst, const void* src, uint32_t bytes, uint32_t bar) {
  asm volatile("cp.async.bulk.shared::cluster.global.mbarrier::complete_tx::bytes [%0], [%1], %2, [%3];" ::"r"(dst), "l"(src), "r"(bytes), "r"(bar) : "memory");
}
__device__ __forceinline__ void prefetch_map(const CUtensorMap* tm) { asm volatile("prefetch.tensormap [%0];" ::"l"(tm) : "memory"); }
__device__ __forceinline__ void tma_store2(const CUtensorMap* tm, uint32_t src, int c0, int c1) {
  asm volatile("cp.async.bulk.tensor.2d.global.shared::cta.bulk_group [%0, {%2,%3}], [%1];" ::"l"(tm), "r"(src), "r"(c0), "r"(c1) : "memory");
}
__device__ __forceinline__ void bulk_commit() { asm volatile("cp.async.bulk.commit_group;" ::: "memory"); }
__device__ __forceinline__ void bulk_wait0() { asm volatile("cp.async.bulk.wait_group 0;" ::: "memory"); }
__device__ __forceinline__ void bulk_wait_read0() { asm volatile("cp.async.bulk.wait_group.read 0;" ::: "memory"); }
__device__ __forceinline__ void wg_fence() { asm volatile("wgmma.fence.sync.aligned;" ::: "memory"); }
__device__ __forceinline__ void wg_commit() { asm volatile("wgmma.commit_group.sync.aligned;" ::: "memory"); }
__device__ __forceinline__ void wg_wait0() { asm volatile("wgmma.wait_group.sync.aligned 0;" ::: "memory"); }
__device__ __forceinline__ uint64_t desc_sw128(uint32_t addr) {
  return (uint64_t)((addr & 0x3FFFF) >> 4) | ((uint64_t)1 << 16) | ((uint64_t)64 << 32) | ((uint64_t)1 << 62);
}
template <int ACC>
__device__ __forceinline__ void wgmma_rs32(float* d, const uint32_t* a, uint64_t db) {
  asm volatile("{.reg .pred p; setp.ne.b32 p, %21, 0;\n"
               "wgmma.mma_async.sync.aligned.m64n32k16.f32.bf16.bf16 {%0,%1,%2,%3,%4,%5,%6,%7,%8,%9,%10,%11,%12,%13,%14,%15}, {%16,%17,%18,%19}, %20, p, 1, 1, 0;}"
               : "+f"(d[0]), "+f"(d[1]), "+f"(d[2]), "+f"(d[3]), "+f"(d[4]), "+f"(d[5]), "+f"(d[6]), "+f"(d[7]), "+f"(d[8]), "+f"(d[9]),
                 "+f"(d[10]), "+f"(d[11]), "+f"(d[12]), "+f"(d[13]), "+f"(d[14]), "+f"(d[15])
               : "r"(a[0]), "r"(a[1]), "r"(a[2]), "r"(a[3]), "l"(db), "n"(ACC));
}

template <int N> __device__ __forceinline__ void fence_regs(float* d) {
#pragma unroll
  for (int i = 0; i < N; i++) asm volatile("" : "+f"(d[i])::"memory");
}
__device__ __forceinline__ void wg_wait1() { asm volatile("wgmma.wait_group.sync.aligned 1;" ::: "memory"); }
__device__ __forceinline__ void tma_store3(const CUtensorMap* tm, uint32_t src, int c0, int c1, int c2) {
  asm volatile("cp.async.bulk.tensor.3d.global.shared::cta.bulk_group [%0, {%2,%3,%4}], [%1];" ::"l"(tm), "r"(src), "r"(c0), "r"(c1), "r"(c2) : "memory");
}
__device__ __forceinline__ void tma_red3(const CUtensorMap* tm, uint32_t src, int c0, int c1, int c2) {
  asm volatile("cp.reduce.async.bulk.tensor.3d.global.shared::cta.add.bulk_group [%0, {%2,%3,%4}], [%1];" ::"l"(tm), "r"(src), "r"(c0), "r"(c1), "r"(c2) : "memory");
}
__device__ __forceinline__ void stsm4(uint32_t a, uint32_t r0, uint32_t r1, uint32_t r2, uint32_t r3) {
  asm volatile("stmatrix.sync.aligned.m8n8.x4.shared.b16 [%0], {%1,%2,%3,%4};" ::"r"(a), "r"(r0), "r"(r1), "r"(r2), "r"(r3) : "memory");
}
__device__ __forceinline__ uint2 lds64(uint32_t a) { uint2 v; asm volatile("ld.shared.v2.b32 {%0,%1}, [%2];" : "=r"(v.x), "=r"(v.y) : "r"(a) : "memory"); return v; }
__device__ __forceinline__ uint32_t hmul2(uint32_t a, uint32_t b) { uint32_t r; asm("mul.rn.bf16x2 %0, %1, %2;" : "=r"(r) : "r"(a), "r"(b)); return r; }
__device__ __forceinline__ void wgmma_ss192t(float* d, uint64_t da, uint64_t db, int acc) {
  asm volatile("{.reg .pred p; setp.ne.b32 p, %98, 0;\n"
    "wgmma.mma_async.sync.aligned.m64n192k16.f32.bf16.bf16 "
    "{%0,%1,%2,%3,%4,%5,%6,%7,%8,%9,%10,%11,%12,%13,%14,%15,%16,%17,%18,%19,%20,%21,%22,%23,%24,%25,%26,%27,%28,%29,%30,%31,%32,%33,%34,%35,%36,%37,%38,%39,%40,%41,%42,%43,%44,%45,%46,%47,%48,%49,%50,%51,%52,%53,%54,%55,%56,%57,%58,%59,%60,%61,%62,%63,%64,%65,%66,%67,%68,%69,%70,%71,%72,%73,%74,%75,%76,%77,%78,%79,%80,%81,%82,%83,%84,%85,%86,%87,%88,%89,%90,%91,%92,%93,%94,%95}, %96, %97, p, 1, 1, 0, 1;}"
    : "+f"(d[0]), "+f"(d[1]), "+f"(d[2]), "+f"(d[3]), "+f"(d[4]), "+f"(d[5]), "+f"(d[6]), "+f"(d[7]), "+f"(d[8]), "+f"(d[9]), "+f"(d[10]), "+f"(d[11]),
      "+f"(d[12]), "+f"(d[13]), "+f"(d[14]), "+f"(d[15]), "+f"(d[16]), "+f"(d[17]), "+f"(d[18]), "+f"(d[19]), "+f"(d[20]), "+f"(d[21]), "+f"(d[22]),
      "+f"(d[23]), "+f"(d[24]), "+f"(d[25]), "+f"(d[26]), "+f"(d[27]), "+f"(d[28]), "+f"(d[29]), "+f"(d[30]), "+f"(d[31]), "+f"(d[32]), "+f"(d[33]),
      "+f"(d[34]), "+f"(d[35]), "+f"(d[36]), "+f"(d[37]), "+f"(d[38]), "+f"(d[39]), "+f"(d[40]), "+f"(d[41]), "+f"(d[42]), "+f"(d[43]), "+f"(d[44]),
      "+f"(d[45]), "+f"(d[46]), "+f"(d[47]), "+f"(d[48]), "+f"(d[49]), "+f"(d[50]), "+f"(d[51]), "+f"(d[52]), "+f"(d[53]), "+f"(d[54]), "+f"(d[55]),
      "+f"(d[56]), "+f"(d[57]), "+f"(d[58]), "+f"(d[59]), "+f"(d[60]), "+f"(d[61]), "+f"(d[62]), "+f"(d[63]), "+f"(d[64]), "+f"(d[65]), "+f"(d[66]),
      "+f"(d[67]), "+f"(d[68]), "+f"(d[69]), "+f"(d[70]), "+f"(d[71]), "+f"(d[72]), "+f"(d[73]), "+f"(d[74]), "+f"(d[75]), "+f"(d[76]), "+f"(d[77]),
      "+f"(d[78]), "+f"(d[79]), "+f"(d[80]), "+f"(d[81]), "+f"(d[82]), "+f"(d[83]), "+f"(d[84]), "+f"(d[85]), "+f"(d[86]), "+f"(d[87]), "+f"(d[88]),
      "+f"(d[89]), "+f"(d[90]), "+f"(d[91]), "+f"(d[92]), "+f"(d[93]), "+f"(d[94]), "+f"(d[95])
    : "l"(da), "l"(db), "r"(acc));
}
__device__ __forceinline__ void wgmma_rs128t(float* d, const uint32_t* a, uint64_t db, int acc) {
  asm volatile("{.reg .pred p; setp.ne.b32 p, %69, 0;\n"
    "wgmma.mma_async.sync.aligned.m64n128k16.f32.bf16.bf16 "
    "{%0,%1,%2,%3,%4,%5,%6,%7,%8,%9,%10,%11,%12,%13,%14,%15,%16,%17,%18,%19,%20,%21,%22,%23,%24,%25,%26,%27,%28,%29,%30,%31,%32,%33,%34,%35,%36,%37,%38,%39,%40,%41,%42,%43,%44,%45,%46,%47,%48,%49,%50,%51,%52,%53,%54,%55,%56,%57,%58,%59,%60,%61,%62,%63}, {%64,%65,%66,%67}, %68, p, 1, 1, 1;}"
    : "+f"(d[0]), "+f"(d[1]), "+f"(d[2]), "+f"(d[3]), "+f"(d[4]), "+f"(d[5]), "+f"(d[6]), "+f"(d[7]), "+f"(d[8]), "+f"(d[9]), "+f"(d[10]), "+f"(d[11]),
      "+f"(d[12]), "+f"(d[13]), "+f"(d[14]), "+f"(d[15]), "+f"(d[16]), "+f"(d[17]), "+f"(d[18]), "+f"(d[19]), "+f"(d[20]), "+f"(d[21]), "+f"(d[22]),
      "+f"(d[23]), "+f"(d[24]), "+f"(d[25]), "+f"(d[26]), "+f"(d[27]), "+f"(d[28]), "+f"(d[29]), "+f"(d[30]), "+f"(d[31]), "+f"(d[32]), "+f"(d[33]),
      "+f"(d[34]), "+f"(d[35]), "+f"(d[36]), "+f"(d[37]), "+f"(d[38]), "+f"(d[39]), "+f"(d[40]), "+f"(d[41]), "+f"(d[42]), "+f"(d[43]), "+f"(d[44]),
      "+f"(d[45]), "+f"(d[46]), "+f"(d[47]), "+f"(d[48]), "+f"(d[49]), "+f"(d[50]), "+f"(d[51]), "+f"(d[52]), "+f"(d[53]), "+f"(d[54]), "+f"(d[55]),
      "+f"(d[56]), "+f"(d[57]), "+f"(d[58]), "+f"(d[59]), "+f"(d[60]), "+f"(d[61]), "+f"(d[62]), "+f"(d[63])
    : "r"(a[0]), "r"(a[1]), "r"(a[2]), "r"(a[3]), "l"(db), "r"(acc));
}
__device__ __forceinline__ void wgmma_rs80(float* d, const uint32_t* a, uint64_t db, int acc) {
  asm volatile("{.reg .pred p; setp.ne.b32 p, %45, 0;\n"
    "wgmma.mma_async.sync.aligned.m64n80k16.f32.bf16.bf16 "
    "{%0,%1,%2,%3,%4,%5,%6,%7,%8,%9,%10,%11,%12,%13,%14,%15,%16,%17,%18,%19,%20,%21,%22,%23,%24,%25,%26,%27,%28,%29,%30,%31,%32,%33,%34,%35,%36,%37,%38,%39}, {%40,%41,%42,%43}, %44, p, 1, 1, 0;}"
    : "+f"(d[0]), "+f"(d[1]), "+f"(d[2]), "+f"(d[3]), "+f"(d[4]), "+f"(d[5]), "+f"(d[6]), "+f"(d[7]), "+f"(d[8]), "+f"(d[9]), "+f"(d[10]), "+f"(d[11]),
      "+f"(d[12]), "+f"(d[13]), "+f"(d[14]), "+f"(d[15]), "+f"(d[16]), "+f"(d[17]), "+f"(d[18]), "+f"(d[19]), "+f"(d[20]), "+f"(d[21]), "+f"(d[22]),
      "+f"(d[23]), "+f"(d[24]), "+f"(d[25]), "+f"(d[26]), "+f"(d[27]), "+f"(d[28]), "+f"(d[29]), "+f"(d[30]), "+f"(d[31]), "+f"(d[32]), "+f"(d[33]),
      "+f"(d[34]), "+f"(d[35]), "+f"(d[36]), "+f"(d[37]), "+f"(d[38]), "+f"(d[39])
    : "r"(a[0]), "r"(a[1]), "r"(a[2]), "r"(a[3]), "l"(db), "r"(acc));
}
__device__ __forceinline__ void wgmma_rs192t(float* d, const uint32_t* a, uint64_t db, int acc) {
  asm volatile("{.reg .pred p; setp.ne.b32 p, %101, 0;\n"
    "wgmma.mma_async.sync.aligned.m64n192k16.f32.bf16.bf16 "
    "{%0,%1,%2,%3,%4,%5,%6,%7,%8,%9,%10,%11,%12,%13,%14,%15,%16,%17,%18,%19,%20,%21,%22,%23,%24,%25,%26,%27,%28,%29,%30,%31,%32,%33,%34,%35,%36,%37,%38,%39,%40,%41,%42,%43,%44,%45,%46,%47,%48,%49,%50,%51,%52,%53,%54,%55,%56,%57,%58,%59,%60,%61,%62,%63,%64,%65,%66,%67,%68,%69,%70,%71,%72,%73,%74,%75,%76,%77,%78,%79,%80,%81,%82,%83,%84,%85,%86,%87,%88,%89,%90,%91,%92,%93,%94,%95}, {%96,%97,%98,%99}, %100, p, 1, 1, 1;}"
    : "+f"(d[0]), "+f"(d[1]), "+f"(d[2]), "+f"(d[3]), "+f"(d[4]), "+f"(d[5]), "+f"(d[6]), "+f"(d[7]), "+f"(d[8]), "+f"(d[9]), "+f"(d[10]), "+f"(d[11]),
      "+f"(d[12]), "+f"(d[13]), "+f"(d[14]), "+f"(d[15]), "+f"(d[16]), "+f"(d[17]), "+f"(d[18]), "+f"(d[19]), "+f"(d[20]), "+f"(d[21]), "+f"(d[22]),
      "+f"(d[23]), "+f"(d[24]), "+f"(d[25]), "+f"(d[26]), "+f"(d[27]), "+f"(d[28]), "+f"(d[29]), "+f"(d[30]), "+f"(d[31]), "+f"(d[32]), "+f"(d[33]),
      "+f"(d[34]), "+f"(d[35]), "+f"(d[36]), "+f"(d[37]), "+f"(d[38]), "+f"(d[39]), "+f"(d[40]), "+f"(d[41]), "+f"(d[42]), "+f"(d[43]), "+f"(d[44]),
      "+f"(d[45]), "+f"(d[46]), "+f"(d[47]), "+f"(d[48]), "+f"(d[49]), "+f"(d[50]), "+f"(d[51]), "+f"(d[52]), "+f"(d[53]), "+f"(d[54]), "+f"(d[55]),
      "+f"(d[56]), "+f"(d[57]), "+f"(d[58]), "+f"(d[59]), "+f"(d[60]), "+f"(d[61]), "+f"(d[62]), "+f"(d[63]), "+f"(d[64]), "+f"(d[65]), "+f"(d[66]),
      "+f"(d[67]), "+f"(d[68]), "+f"(d[69]), "+f"(d[70]), "+f"(d[71]), "+f"(d[72]), "+f"(d[73]), "+f"(d[74]), "+f"(d[75]), "+f"(d[76]), "+f"(d[77]),
      "+f"(d[78]), "+f"(d[79]), "+f"(d[80]), "+f"(d[81]), "+f"(d[82]), "+f"(d[83]), "+f"(d[84]), "+f"(d[85]), "+f"(d[86]), "+f"(d[87]), "+f"(d[88]),
      "+f"(d[89]), "+f"(d[90]), "+f"(d[91]), "+f"(d[92]), "+f"(d[93]), "+f"(d[94]), "+f"(d[95])
    : "r"(a[0]), "r"(a[1]), "r"(a[2]), "r"(a[3]), "l"(db), "r"(acc));
}

constexpr int NPQ = 2;
#define NQ 12
#define NQ_WIN 8
#define NO_EARLY 6
#define NO_MID 9
#define NW1 16
#define NW1A 10
#define VLD 6
#define VB 0
#define XPF 3
#define WSPLIT 8
#define PEARLY 0
#define NQ_W1 8
#define B5LATE 0
#define WD 750
#define DFENCE 0
#define PDS 300
#define PDT 50
#define LDEP 2
#define LDT 6000
#define PD 900
constexpr int R_WQ = 0;
constexpr int R_WO = R_WQ + 8 * (20 - NPQ) * 512;
constexpr int R_XT = R_WO + 14 * 12 * 512;
constexpr int R_MEM = R_XT;
constexpr int R_QB = R_XT + 40960;
constexpr int R_QA = R_QB + 1024;
constexpr int R_O2 = R_QA + 1024;
constexpr int R_VS = R_O2 + 1024;
constexpr int R_KT = R_VS + 1024;
constexpr int R_VT = R_KT + 5120;
constexpr int R_V1 = R_VT + 5120;
constexpr int R_SX = R_V1 + 8192;
constexpr int R_VM = R_SX + 4608;
constexpr int R_BAR = R_VM + 2048;
constexpr int R_MI = R_BAR + 64;
constexpr int R_SMEM = R_MI + 64;
static_assert(NPQ == 2 && R_XT % 1024 == 0 && R_KT % 1024 == 0 && R_VT % 1024 == 0 && R_V1 % 1024 == 0 && R_WO % 1024 == 0, "align");
constexpr int R_SMEM_ALLOC = R_SMEM;
static_assert(R_SMEM_ALLOC <= 232448, "smem");

#define TR(i) do {} while (0)

__device__ __forceinline__ void red_pair(unsigned char* p, float lo, float hi) {
  const int b = __float2int_rn(lo), a = __float2int_rn(hi);
  asm volatile("{.reg .b64 t; mov.b64 t, {%1,%2}; red.relaxed.gpu.global.add.u64 [%0], t;}" ::"l"(p), "r"(b + ((1 << 29) + (1 << 23))), "r"(a * 8) : "memory");
}
__device__ __forceinline__ unsigned long long swap0(unsigned char* p) {
  unsigned long long r;
  asm volatile("atom.relaxed.gpu.global.exch.b64 %0, [%1], 0;" : "=l"(r) : "l"(p) : "memory");
  return r;
}
__device__ __forceinline__ uint32_t dec_pair(uint32_t lo, uint32_t hi, uint32_t bias) { return pack2((float)(int)(lo * 8u + bias), (float)(int)hi); }

__global__ void __cluster_dims__(3, 1, 1) __launch_bounds__(256, 1)
rec_kernel(const __grid_constant__ CUtensorMap tmX, const __grid_constant__ CUtensorMap tmK, const __grid_constant__ CUtensorMap tmV,
           const __grid_constant__ CUtensorMap tmWq, const __grid_constant__ CUtensorMap tmWq2, const __grid_constant__ CUtensorMap tmWk,
           const __grid_constant__ CUtensorMap tmWv, const __grid_constant__ CUtensorMap tmWo, const bf16* __restrict__ mem0,
           const bf16* __restrict__ Wq, const bf16* __restrict__ Wo, const bf16* __restrict__ x) {
  extern __shared__ __align__(1024) unsigned char smem[];
  const uint32_t sb = smem_u32(smem);
  const int tid = threadIdx.x, lane = tid & 31, wid = __shfl_sync(~0u, tid >> 5, 0), g = wid >> 2, w = wid & 3;
  const int cta = blockIdx.x, head = cta / 3, rank = cta % 3;
  const int D0 = head * DH + rank * 64;
  const int tile0 = rank == 0 ? 0 : (rank == 1 ? 14 : 26);
  const uint32_t XBAR = sb + R_BAR, SBAR = XBAR + 8, OBAR = XBAR + 16, VBAR = XBAR + 24, FBAR = XBAR + 32, WBAR = XBAR + 40;
  constexpr uint32_t ONES = 0x3F803F80u;
  if (LDEP == 0) asm volatile("griddepcontrol.launch_dependents;" ::: "memory");
  GTR(0);
  if (wid == 0) {
    if (lane == 0) {
      mbar_init(XBAR, 1); mbar_init(SBAR, 4); mbar_init(OBAR, 5); mbar_init(VBAR, 1); mbar_init(FBAR, 2);
      mbar_init(WBAR, 1); mbar_init(WBAR + 8, 1); mbar_init(WBAR + 16, 1);
      asm volatile("fence.mbarrier_init.release.cluster;" ::: "memory");
      mbar_expect(WBAR, 81920); mbar_expect(WBAR + 8, 81920 + 2 * NPQ * 2048); mbar_expect(XBAR, 40960);
      mbar_expect(SBAR, 3072); mbar_expect(OBAR, 2048); mbar_expect(VBAR, 8192);
      sts128(sb + R_MI + 48, 0, 0, 0, 0);
    }
    __syncwarp();
    if (lane < 5) tma_load2(sb + lane * 16384, &tmWk, D0, lane * 128, WBAR);
    if (lane == 5) tma_load3(sb + R_XT, &tmX, 0, 0, 0, XBAR);
    if (lane < 5) tma_load2(lane < 4 ? sb + 81920 + lane * 16384 : sb + R_QB, &tmWv, D0, lane * 128, WBAR + 8);
    if (lane < 2) tma_load2(sb + R_QB + 16384 + lane * 4096, &tmWq2, D0, lane * 320, WBAR + 8);
  }
  if (tid == 32) { prefetch_map(&tmWq); prefetch_map(&tmWo); prefetch_map(&tmK); prefetch_map(&tmV); }
  if (tid >= 64 && tid < 144) prefetch_l2(mem0 + (tid - 64) * 64);
  __syncthreads();
  GTR(1);
  if (LDEP == 1) asm volatile("griddepcontrol.launch_dependents;" ::: "memory");
  if (LDEP == 4 && wid == 7) { spin_until(clk32(), LDT); asm volatile("griddepcontrol.launch_dependents;" ::: "memory"); }
#pragma unroll
  for (int i = 0; i < 5; i++) { const int l = tid + i * 256; prefetch_l2((l < 640 ? Wq : Wo - 40960) + (size_t)cta * 40960 + l * 64); }
  uint32_t ww[40][4], wqp[NPQ][4];
  {
    uint32_t xm = 0;
#pragma unroll
    for (int i = 0; i < 7; i++) {
      const int v = tid + i * 256, gv = cta * 1707 + v;
      if (v < 1707 && gv < S_TOK * DM / 8) {
        const uint4 q = __ldg((const uint4*)x + gv);
        xm = hmaxabs2(hmaxabs2(xm, hmaxabs2(q.x, q.y)), hmaxabs2(q.z, q.w));
      }
    }
    xm = __reduce_max_sync(~0u, max((xm << 16) & 0x7fffffffu, xm & 0x7fff0000u));
    const uint32_t p = sb + (lane >> 4) * 1024 + (lane & 7) * 128 + (((2 * w + ((lane >> 3) & 1)) ^ (lane & 7)) << 4);
    if (LDEP == 2) asm volatile("griddepcontrol.launch_dependents;" ::: "memory");
    mbar_wait(WBAR + 8 * g, 0);
    GTR(2);
#pragma unroll
    for (int f = 0; f < 40; f++) ldsm4t(ww[f], (f >= 32 && g == 1) ? p + R_QB + (f - 32) * 2048 : p + g * 81920 + f * 2048);
    mbar_wait(WBAR + 8, 0);
    GTR(3);
#pragma unroll
    for (int f = 0; f < NPQ; f++) ldsm4t(wqp[f], p + R_QB + 16384 + g * 4096 + f * 2048);
    __syncthreads();
    asm volatile("barrier.cluster.arrive.relaxed.aligned;" ::: "memory");
    if (wid == 0) {
      if (lane == 0) mbar_expect(WBAR + 16, 18 * 4096 + 21 * 4096);
      __syncwarp();
      if (lane < 4) tma_load2(sb + R_WQ + lane * 18432, &tmWq, D0, (lane >> 1) * 320 + 32 + (lane & 1) * 144, WBAR + 16);
      else if (lane < 7) tma_load3(sb + R_WO + ((lane - 1 - rank) % 3) * 28672, &tmWo, 0, head * DH + (lane - 4) * 64, tile0 >> 1, WBAR + 16);
      __syncwarp();
    }
    float nv[4] = {0.f, 0.f, 0.f, 0.f};
#pragma unroll
    for (int f = 0; f < 40; f++) {
      const uint32_t a[4] = {ww[f][0] & 0x7fff7fffu, ww[f][1] & 0x7fff7fffu, ww[f][2] & 0x7fff7fffu, ww[f][3] & 0x7fff7fffu};
      mma16816(nv, a, ONES, ONES);
    }
    const uint32_t mv = __reduce_max_sync(~0u, __float_as_uint(fmaxf(nv[0], nv[2])));
    if (lane == 0) { if (g == 1) smax32(sb + R_MI + 48, mv); smax32(sb + R_MI + 52, xm); }
  }
  GTR(4);
  if (LDEP == 3) asm volatile("griddepcontrol.launch_dependents;" ::: "memory");

  const uint32_t rF_ = opaque(sb + lane * 16);
  const uint32_t rP_ = opaque(sb + (lane >> 4) * 1024 + (lane & 7) * 128 + (((2 * w + ((lane >> 3) & 1)) ^ (lane & 7)) << 4));
  const int tA = g == 1 ? 2 * w : (rank != 1 ? (w < 2 ? 8 + 2 * w : 10 + w) : 8 + w);
  const bool two = g == 1 || (w < 2 && rank != 1);
  const uint32_t r1 = rank == 2 ? 0 : rank + 1, r2 = rank == 0 ? 2 : rank - 1;
  const uint32_t rW_ = opaque(sb + R_WO + (tA >> 1) * 4096 + ((lane >> 4) * 8 + (lane & 7)) * 64 +
                             (((2 * (tA & 1) + ((lane >> 3) & 1)) ^ ((lane >> 1) & 3)) << 4));
  uint32_t wqt[NQ][4];
  float u = 1.f;
  uint32_t t0 = 0;
  int s = -1;

#define WOFF(ks) (((ks) >> 2) * 28672 + ((ks) & 3) * 1024)
#define XDESC(j) (((uint64_t)0x40000040 << 32) | (dlo + ((((j) >> 2) * 4096 + ((j) & 3) * 32) >> 4)))

  auto window = [&](auto G_, auto FIRST_) {
    constexpr int G = decltype(G_)::value;
    constexpr bool FIRST = decltype(FIRST_)::value;
    const uint32_t rF = pin(rF_), rP = pin(rP_);
    float d[16];
    const uint32_t dlo = pin(((sb + R_XT) >> 4) | 0x10000);
    const uint32_t wqS = rP + R_WQ + G * (20 - NPQ) * 2048;
    uint4 y[5];
    unsigned long long zr = 0;
    const uint32_t t = w * 32 + ((rF - sb) >> 4);
    if (G == 0) zr = swap0(g_red + (((s + 2) & 3) * RB_SIZE + ((cta % 20) * 8 + (t >> 4)) * RB_LINE + (t & 15) * 8));
    if (G == 0) {
      if (!FIRST && w == 3) {
        if (elect()) {
          mbar_expect(SBAR, 3072); mbar_expect(OBAR, 2048); mbar_expect(VBAR, 8192);
          asm volatile("mbarrier.arrive.relaxed.cluster.shared::cluster.b64 _, [%0];" ::"r"(mapa(FBAR, r1)) : "memory");
          asm volatile("mbarrier.arrive.relaxed.cluster.shared::cluster.b64 _, [%0];" ::"r"(mapa(FBAR, r2)) : "memory");
        }
        __syncwarp();
      }
    }
    const unsigned char* yp = g_red + ((s & 3) * RB_SIZE + (G * 80 + (t >> 3)) * RB_LINE + (t & 7) * 16);
    auto poll = [&]() {
      TR(10);
      spin_until(t0, PD);
#pragma unroll
      for (int q = 0; q < 5; q++) y[q] = ldg_rlx128(yp + q * 16 * RB_LINE);
      TR(9);
      sched_fence(sb);
    };
    constexpr int WS = FIRST || G == 1 ? 40 : WSPLIT;
    if (!FIRST && G == 0) {
#pragma unroll
      for (int f = 0; f < NQ_WIN; f++) ldsm4t(wqt[f], wqS + f * 2048);
      asm volatile("" : "+l"(yp));
      mbar_wait(XBAR, (s + 1) & 1);
      spin_until(t0, WD);
    } else {
      mbar_wait(XBAR, (s + 1) & 1);
    }
    TR(11);
    wg_fence();
    wgmma_rs32<0>(d, ww[0], XDESC(0));
#pragma unroll
    for (int j = 1; j < WS; j++) wgmma_rs32<1>(d, ww[j], XDESC(j));
    if (FIRST) {
      const unsigned short* m = (const unsigned short*)mem0 + (t & 1) * 4 * DM + G * 320 + (t >> 1);
#pragma unroll
      for (int q = 0; q < 5; q++) y[q] = make_uint4(m[q * 64], m[q * 64 + DM], m[q * 64 + 2 * DM], m[q * 64 + 3 * DM]);
    } else if (G == 0) {
      poll();
    }
#pragma unroll
    for (int j = WS; j < 40; j++) wgmma_rs32<1>(d, ww[j], XDESC(j));
    wg_commit();
    if (!FIRST && G == 1) {
      asm volatile("" : "+l"(yp));
      if (PEARLY) poll();
      mbar_wait(FBAR, s & 1);
#pragma unroll
      for (int f = 0; f < NQ_W1; f++) ldsm4t(wqt[f], wqS + f * 2048);
    }
    if (FIRST) asm volatile("barrier.cluster.wait.acquire.aligned;" ::: "memory");
    wg_wait0();
    fence_regs<16>(d);
    TR(13);
    bar_arrive(8 + G, 256);
    if (!FIRST && G == 1 && !PEARLY) poll();
    {
      uint32_t pk[8];
#pragma unroll
      for (int q = 0; q < 8; q++) pk[q] = pack2(d[2 * q], d[2 * q + 1]);
      stsm4t(rP + (G == 1 ? R_VT : R_KT) + 1024, pk[0], pk[1], pk[2], pk[3]);
      stsm4t(rP + (G == 1 ? R_VT : R_KT) + 3072, pk[4], pk[5], pk[6], pk[7]);
      if (G == 1) {
        const uint32_t e1 = mapa(rF + R_V1 + 4096 + w * 512, r1), e2 = mapa(rF + R_V1 + w * 512, r2), b1 = mapa(VBAR, r1), b2 = mapa(VBAR, r2);
        st_async4(e1, pk[0], pk[1], pk[2], pk[3], b1);
        st_async4(e2, pk[0], pk[1], pk[2], pk[3], b2);
        st_async4(e1 + 2048, pk[4], pk[5], pk[6], pk[7], b1);
        st_async4(e2 + 2048, pk[4], pk[5], pk[6], pk[7], b2);
      }
    }
    if (FIRST) {
      mbar_wait(WBAR + 16, 0);
      const uint32_t woA = rW_;
      float na[4] = {0.f, 0.f, 0.f, 0.f}, nb[4] = {0.f, 0.f, 0.f, 0.f};
#pragma unroll
      for (int ks = 0; ks < 12; ks++) {
        uint32_t a[4], b[4];
        ldsm4t(a, woA + WOFF(ks));
        ldsm4t(b, (two ? woA ^ 32 : woA) + WOFF(ks));
#pragma unroll
        for (int q = 0; q < 4; q++) { a[q] &= 0x7fff7fffu; b[q] &= 0x7fff7fffu; }
        mma16816(na, a, ONES, ONES);
        mma16816(nb, b, ONES, ONES);
      }
      const uint32_t mo = __reduce_max_sync(~0u, __float_as_uint(fmaxf(fmaxf(na[0], na[2]), fmaxf(nb[0], nb[2]))));
      if (rF == sb) smax32(sb + R_MI + 56, mo);
      __syncthreads();
      if (G == 1 && w == 2) {
        const uint4 r = lds128(sb + R_MI + 48);
        const uint32_t epoch = *(volatile uint32_t*)&g_epoch + 1;
        if (rF == sb) stg_rlx64(&g_rec[cta], (r.y & 0xffff0000u) | (epoch & 0xffffu), ((r.x + 0xffffu) & 0xffff0000u) | ((r.z + 0xffffu) >> 16));
      }
    }
#pragma unroll
    for (int f = FIRST ? 0 : (G == 1 ? NQ_W1 : NQ_WIN); f < NQ; f++) ldsm4t(wqt[f], wqS + f * 2048);
    if (FIRST || DFENCE) sched_fence(sb);
    TR(14);
    const uint32_t ma = sb + R_MEM + G * 5120 + t * 8;
    if (FIRST) {
      bar_sync(9 - G, 256);
#pragma unroll
      for (int j = 0; j < 5; j++) sts64(ma + j * 1024, y[j].x | (y[j].y << 16), y[j].z | (y[j].w << 16));
    } else {
      int n = 0;
#pragma unroll 1
      while (!__all_sync(~0u, (y[0].y & y[0].w & y[1].y) & (y[1].w & y[2].y & y[2].w) & (y[3].y & y[3].w & y[4].y) & (y[4].w & 4))) {
#pragma unroll
        for (int j = 0; j < 5; j++) if (!(y[j].y & y[j].w & 4)) y[j] = ldg_rlx128(yp + j * 16 * RB_LINE);
        if (++n > SPIN_MAX) { g_err = 5; break; }
      }
      const uint32_t bias = 0x80000000u + (sb >> 31);
      bar_sync(9 - G, 256);
#pragma unroll
      for (int j = 0; j < 5; j++) sts64(ma + j * 1024, dec_pair(y[j].x, y[j].y, bias), dec_pair(y[j].z, y[j].w, bias));
    }
    if (G == 0 && zr == ~0ull) g_err = 9;
    TR(0);
  };

  auto oproj = [&](auto TWO_, auto NPRE_, auto& wot, const uint32_t rF, const uint32_t woA, const uint32_t woB,
                   float sm0, float sm1, bool have_sums) {
    constexpr bool TWO = decltype(TWO_)::value;
    constexpr int NPRE = decltype(NPRE_)::value;
    float c[4][4];
#pragma unroll
    for (int q = 0; q < 4; q++) c[q][0] = c[q][1] = c[q][2] = c[q][3] = 0.f;
    unsigned char* sp = g_red + ((s & 3) * RB_SIZE + (4 * (tile0 + tA) + ((rF - sb) >> 8)) * RB_LINE + (((rF - sb) >> 1) & 120));
    bar_sync(3, 256);
    TR(8);
    uint4 ob[6];
    ob[0] = lds128(rF + R_QB); ob[1] = lds128(rF + R_QB + 512);
    const float2 su = lds64f(sb + R_MI + 48);
    if (!have_sums) { const float2 t = lds64f(sb + R_MI + 16 + (((rF - sb) >> 1) & 24)); sm0 = t.x; sm1 = t.y; }
#pragma unroll
    for (int p = 0; p < 6; p++) {
      if (p + 2 < 6) ob[p + 2] = lds128(rF + (p < 2 ? R_QA : R_O2) + (p & 1) * 512);
#pragma unroll
      for (int e = 0; e < 2; e++) {
        const int ks = 2 * p + e;
        const uint32_t b0 = e ? ob[p].z : ob[p].x, b1 = e ? ob[p].w : ob[p].y;
        if (TWO) {
          const int iA = 2 * ks, iB = iA + 1;
          mma16816(c[e], wot[iA % NPRE], b0, b1);
          if (iA + NPRE < 24) ldsm4t(wot[iA % NPRE], woA + WOFF((iA + NPRE) >> 1));
          mma16816(c[2 + e], wot[iB % NPRE], b0, b1);
          if (iB + NPRE < 24) ldsm4t(wot[iB % NPRE], woB + WOFF((iB + NPRE) >> 1));
        } else {
          mma16816(c[ks & 3], wot[ks], b0, b1);
        }
      }
    }
    const float f0 = su.x * rcp(sm0), f1 = su.x * rcp(sm1);
    t0 = clk32() + (TWO ? (have_sums ? -PDT : 0) : PDS);
    u = su.y;
    if (TWO) {
      red_pair(sp, (c[0][0] + c[1][0]) * f0, (c[0][1] + c[1][1]) * f1);
      red_pair(sp + 2 * RB_LINE, (c[0][2] + c[1][2]) * f0, (c[0][3] + c[1][3]) * f1);
      red_pair(sp + 4 * RB_LINE, (c[2][0] + c[3][0]) * f0, (c[2][1] + c[3][1]) * f1);
      red_pair(sp + 6 * RB_LINE, (c[2][2] + c[3][2]) * f0, (c[2][3] + c[3][3]) * f1);
    } else {
      red_pair(sp, ((c[0][0] + c[1][0]) + (c[2][0] + c[3][0])) * f0, ((c[0][1] + c[1][1]) + (c[2][1] + c[3][1])) * f1);
      red_pair(sp + 2 * RB_LINE, ((c[0][2] + c[1][2]) + (c[2][2] + c[3][2])) * f0, ((c[0][3] + c[1][3]) + (c[2][3] + c[3][3])) * f1);
    }
    TR(15);
  };

  auto step = [&](auto G_, auto LAST_) {
    constexpr int G = decltype(G_)::value;
    constexpr bool LAST = decltype(LAST_)::value;
    __syncthreads();
    const uint32_t rF = pin(rF_), rP = pin(rP_);
    TR(1);
    const uint32_t wqS = rP + R_WQ + G * (20 - NPQ) * 2048, rM = rF + R_MEM;
    const uint32_t l8 = sb + ((rF - sb) >> 1) + w * 256;
    const uint32_t woA = pin(rW_), woB = woA ^ 32;
    float aq[2][4] = {};
    const uint32_t ln = (rF - sb) >> 4;
    const uint32_t rS = sb + (ln & 7) * 128 + (ln < 16 ? R_QB + (ln & 8) * 128 + (((2 * w + G) ^ (ln & 7)) << 4) : R_KT + (((2 * w + ((ln >> 3) & 1)) ^ (ln & 7)) << 4));
    auto qmma = [&](int f, uint32_t b0, uint32_t b1) {
      if (f < NPQ) mma16816(aq[f & 1], wqp[f], b0, b1);
      else {
        const int slot = (f - NPQ) % NQ;
        mma16816(aq[f & 1], wqt[slot], b0, b1);
        if (f + NQ < 20) ldsm4t(wqt[slot], wqS + (f - NPQ + NQ) * 2048);
      }
    };
    if constexpr (G == 1) {
      uint32_t bb[20][4];
      if (!LAST) {
        ldsm4t(bb[10], rM + 5120);
        ldsm4t(bb[11], rM + 5632);
#pragma unroll
        for (int i = 10; i < 20; i++) {
          if (i + 2 < 20) ldsm4t(bb[i + 2], rM + (i + 2) * 512);
          qmma(2 * i - 20, bb[i][0], bb[i][1]);
          qmma(2 * i - 19, bb[i][2], bb[i][3]);
        }
        stsm2t(rS, pack2(aq[0][0] + aq[1][0], aq[0][1] + aq[1][1]), pack2(aq[0][2] + aq[1][2], aq[0][3] + aq[1][3]));
        bar_arrive(1, 256);
      }
      TR(2);
      float av[4][4] = {};
      uint32_t m0 = 0, m1 = 0;
      auto vmma = [&](auto MAX_) {
#pragma unroll
        for (int n = 0; n < 20; n++) {
          const int i = (n + 10) % 20;
          if (LAST && n < 8) ldsm4t(bb[(n + 10) % 20], rM + ((n + 10) % 20) * 512);
          if (LAST && n == 0) { ldsm4t(bb[18], rM + 18 * 512); ldsm4t(bb[19], rM + 19 * 512); }
          if (n == VB && !LAST) { bar_sync(5, 256); sched_fence(sb); }
          if (n == VLD) {
            if (VB != VLD && !LAST) sched_fence(sb);
#pragma unroll
            for (int q = 0; q < 10; q++) ldsm4t(bb[q], rM + q * 512);
            if (!LAST) sched_fence(sb);
          }
          mma16816(av[(2 * n) & 3], ww[2 * i], bb[i][0], bb[i][1]);
          mma16816(av[(2 * n + 1) & 3], ww[2 * i + 1], bb[i][2], bb[i][3]);
          if (decltype(MAX_)::value) { m0 = hmaxabs2(m0, hmaxabs2(bb[i][0], bb[i][1])); m1 = hmaxabs2(m1, hmaxabs2(bb[i][2], bb[i][3])); }
        }
      };
      auto vout = [&]() {
        const uint32_t vm0 = pack2(((av[0][0] + av[1][0]) + (av[2][0] + av[3][0])) * u, ((av[0][1] + av[1][1]) + (av[2][1] + av[3][1])) * u);
        const uint32_t vm1 = pack2(((av[0][2] + av[1][2]) + (av[2][2] + av[3][2])) * u, ((av[0][3] + av[1][3]) + (av[2][3] + av[3][3])) * u);
        if (!LAST) {
          st_async2(mapa(l8 + R_VM + 1024, r1), vm0, vm1, mapa(OBAR, r1));
          st_async2(mapa(l8 + R_VM, r2), vm0, vm1, mapa(OBAR, r2));
          sts64(l8 + R_VS, vm0, vm1);
          __syncwarp();
          if (rF == sb) mbar_arrive(OBAR);
        }
        stsm2t(rP + R_VT, vm0, vm1);
      };
      if (LAST) { vmma(std::false_type{}); vout(); return; }
      uint32_t wot[NW1][4];
      auto wpre = [&](int i0, int i1) {
#pragma unroll
        for (int i = i0; i < i1; i++) ldsm4t(wot[i], ((i & 1) ? woB : woA) + WOFF(i >> 1));
      };
      if (w != 1) {
        vmma(std::false_type{});
        bar_arrive(7, 128);
        vout();
        bar_arrive(2, 128);
        TR(5);
        wpre(0, NW1A);
      } else {
        vmma(std::true_type{});
        bar_sync(7, 128);
        if (elect()) { mbar_expect(XBAR, 40960); tma_load3(sb + R_XT, &tmX, 0, (s + 1) * SEG, 0, XBAR); }
        __syncwarp();
        vout();
        if (XPF && s + XPF < NSEG && rF - sb < 64 && cta < 80) prefetch_l2(x + (size_t)(s + XPF) * SEG * DM + cta * 256 + (rF - sb) * 4);
        TR(5);
        m0 = hmaxabs2(m0, m1);
        const uint32_t mx = __reduce_max_sync(~0u, max((m0 << 16) & 0x7fffffffu, m0 & 0x7fff0000u));
        const float2 mi = lds64f(sb + R_MI + 8);
        wpre(0, NW1A);
        bar_sync(2, 128);
        if (elect()) {
          fence_async_smem();
          if (s > 0) {
            bulk_wait0();
            asm volatile("red.relaxed.gpu.global.add.u32 [%0], 1;" ::"l"(&g_segcnt[s - 1]) : "memory");
            asm volatile("red.relaxed.gpu.global.add.u32 [%0], 1;" ::"l"(&g_prog) : "memory");
          }
          tma_store2(&tmK, sb + R_KT, D0, s * LK);
          tma_store2(&tmV, sb + R_VT, D0, s * LK);
          bulk_commit();
        }
        __syncwarp();
        float wb = mi.x, xm = mi.y;
        if (s == 0) {
          const uint32_t epoch = *(volatile uint32_t*)&g_epoch + 1;
          uint32_t av_ = 0, ao = 0, xi = 0;
#pragma unroll 1
          for (int j = 0; j < 3; j++) {
            uint2 r;
            int n = 0;
#pragma unroll 1
            while (true) {
              r = ldg_rlx64(&g_rec[j * 32 + ((rF - sb) >> 4)]);
              if (((r.x ^ epoch) & 0xffffu) == 0) break;
              if (++n > SPIN_MAX) { g_err = 6; break; }
            }
            av_ = max(av_, r.y & 0xffff0000u); ao = max(ao, r.y << 16); xi = max(xi, r.x & 0xffff0000u);
          }
          av_ = __reduce_max_sync(~0u, av_); ao = __reduce_max_sync(~0u, ao); xi = __reduce_max_sync(~0u, xi);
          wb = __uint_as_float(av_) * __uint_as_float(ao) * 33.f; xm = __uint_as_float(xi);
          if (rF == sb) sts64f(sb + R_MI + 8, wb, xm);
          __syncwarp();
        }
        const float hm = fmaxf(__uint_as_float(mx) * u, xm);
        const uint32_t eb = min(max(__float_as_uint(hm * wb) >> 23, 40u), 200u);
        if (rF == sb) sts64(sb + R_MI + 48, (280u - eb) << 23, (eb - 29u) << 23);
        if (elect()) bulk_wait_read0();
        __syncwarp();
      }
      if (NW1A < NW1) {
        bar_sync(4, 256);
        wpre(NW1A, NW1);
      }
      TR(6);
      oproj(std::true_type{}, std::integral_constant<int, NW1>{}, wot, rF, woA, woB, 0.f, 0.f, false);
    } else {
      {
        uint32_t bb[20][4];
        float ak[4][4] = {};
        ldsm4t(bb[0], rM);
        ldsm4t(bb[10], rM + 5120);
#pragma unroll
        for (int i = 0; i < 10; i++) {
          if (i + 1 < 10) { ldsm4t(bb[i + 1], rM + (i + 1) * 512); ldsm4t(bb[i + 11], rM + (i + 11) * 512); }
          mma16816(ak[0], ww[2 * i], bb[i][0], bb[i][1]);
          if (!LAST) qmma(2 * i, bb[i][0], bb[i][1]);
          mma16816(ak[1], ww[2 * i + 1], bb[i][2], bb[i][3]);
          if (!LAST) qmma(2 * i + 1, bb[i][2], bb[i][3]);
          mma16816(ak[2], ww[2 * i + 20], bb[i + 10][0], bb[i + 10][1]);
          mma16816(ak[3], ww[2 * i + 21], bb[i + 10][2], bb[i + 10][3]);
        }
#pragma unroll
        for (int q = 0; q < 4; q++) { ak[0][q] += ak[2][q]; ak[1][q] += ak[3][q]; }
        stsm4t(rS, pack2(aq[0][0] + aq[1][0], aq[0][1] + aq[1][1]), pack2(aq[0][2] + aq[1][2], aq[0][3] + aq[1][3]),
               pack2((ak[0][0] + ak[1][0]) * u, (ak[0][1] + ak[1][1]) * u), pack2((ak[0][2] + ak[1][2]) * u, (ak[0][3] + ak[1][3]) * u));
      }
      if (LAST) return;
      bar_sync(1, 256);
      if (!B5LATE) bar_arrive(5, 256);
      TR(2);
      if (w != 3) {
        uint32_t qa[4][4], kk[4][4];
        float x[4][4] = {};
#pragma unroll
        for (int i = 0; i < 4; i++) { ldsm4(qa[i], (rP ^ (i << 5)) + R_QB); ldsm4(kk[i], ((rP ^ (i << 5)) + w * 2048) + R_KT); }
        const uint32_t dst = rF + R_SX + rank * 1536 + w * 512;
        const uint32_t e1 = mapa(dst, r1), e2 = mapa(dst, r2), s1 = mapa(SBAR, r1), s2 = mapa(SBAR, r2);
#pragma unroll
        for (int i = 0; i < 4; i++) { mma16816(x[i & 1], qa[i], kk[i][0], kk[i][1]); mma16816(x[2 + (i & 1)], qa[i], kk[i][2], kk[i][3]); }
        const uint32_t u0 = __float_as_uint((x[0][0] + x[0][2]) + (x[1][0] + x[1][2])), u1 = __float_as_uint((x[0][1] + x[0][3]) + (x[1][1] + x[1][3]));
        const uint32_t u2 = __float_as_uint((x[2][0] + x[2][2]) + (x[3][0] + x[3][2])), u3 = __float_as_uint((x[2][1] + x[2][3]) + (x[3][1] + x[3][3]));
        st_async4(e1, u0, u1, u2, u3, s1);
        st_async4(e2, u0, u1, u2, u3, s2);
        sts128(dst, u0, u1, u2, u3);
        __syncwarp();
        if (rF == sb) mbar_arrive(SBAR);
      }
      if (B5LATE) bar_arrive(5, 256);
      TR(4);
      mbar_wait(VBAR, s & 1);
      uint32_t wot[12][4], va[3][8];
      ldsm4t(va[0], rP + R_VT + 1024); ldsm4t(va[0] + 4, rP + R_VT + 3072);
#pragma unroll
      for (int q = 0; q < 4; q++) {
        const uint4 t = lds128(rF + R_V1 + w * 512 + q * 2048);
        uint32_t* v = va[1 + (q >> 1)] + (q & 1) * 4;
        v[0] = t.x; v[1] = t.y; v[2] = t.z; v[3] = t.w;
      }
      auto wpre = [&](int i0, int i1) {
        if (two) {
#pragma unroll
          for (int i = i0; i < i1; i++) ldsm4t(wot[i], ((i & 1) ? woB : woA) + WOFF(i >> 1));
        } else {
#pragma unroll
          for (int i = i0; i < i1; i++) ldsm4t(wot[i], woA + WOFF(i));
        }
      };
      wpre(0, NO_EARLY);
      const uint32_t dst = rF + (w >> 1) * 512 + (w & 1) * 8;
      const float scl = u * (0.07216878364870322f * 1.4426950408889634f);
      mbar_wait(SBAR, s & 1);
      TR(6);
      float sc[10];
      {
        const float4 a0 = lds128f(rF + R_SX), b0 = lds128f(rF + R_SX + 1536), c0 = lds128f(rF + R_SX + 3072);
        const float4 a1 = lds128f(rF + R_SX + 512), b1 = lds128f(rF + R_SX + 2048), c1 = lds128f(rF + R_SX + 3584);
        const float2 a2 = lds64f(rF + R_SX + 1024), b2 = lds64f(rF + R_SX + 2560), c2 = lds64f(rF + R_SX + 4096);
        sc[8] = a0.x + b0.x + c0.x; sc[9] = a0.y + b0.y + c0.y; sc[0] = a0.z + b0.z + c0.z; sc[1] = a0.w + b0.w + c0.w;
        sc[2] = a1.x + b1.x + c1.x; sc[3] = a1.y + b1.y + c1.y; sc[4] = a1.z + b1.z + c1.z; sc[5] = a1.w + b1.w + c1.w;
        sc[6] = a2.x + b2.x + c2.x; sc[7] = a2.y + b2.y + c2.y;
      }
      float mx = fmaxf(fmaxf(fmaxf(sc[0], sc[1]), fmaxf(sc[2], sc[3])), fmaxf(fmaxf(sc[4], sc[5]), fmaxf(sc[6], sc[7])));
      mx = fmaxf(mx, fmaxf(sc[8], sc[9]));
      mx = fmaxf(mx, __shfl_xor_sync(~0u, mx, 1));
      const bool vok = mbar_test(OBAR, s & 1);
      mx = fmaxf(mx, __shfl_xor_sync(~0u, mx, 2));
      if (NW1A < NW1) bar_arrive(4, 256);
      const float mo = mx * scl;
      uint32_t pb[5];
#pragma unroll
      for (int j = 0; j < 5; j++) pb[j] = pack2(ex2(fmaf(sc[2 * j], scl, -mo)), ex2(fmaf(sc[2 * j + 1], scl, -mo)));
      if (!vok) mbar_wait(OBAR, s & 1);
      const uint2 m0 = lds64(l8 + R_VS), m1 = lds64(l8 + R_VM), m2 = lds64(l8 + R_VM + 1024);
      const uint32_t ones[4] = {ONES, ONES, ONES, ONES};
      float o[3][4], o2[3][4], sm[4] = {0.f, 0.f, 0.f, 0.f}, sn[4] = {0.f, 0.f, 0.f, 0.f}, so[4] = {0.f, 0.f, 0.f, 0.f};
#pragma unroll
      for (int b = 0; b < 3; b++) {
        o[b][0] = o[b][1] = o[b][2] = o[b][3] = o2[b][0] = o2[b][1] = o2[b][2] = o2[b][3] = 0.f;
        mma16816(o[b], va[b], pb[0], pb[1]);
      }
#pragma unroll
      for (int b = 0; b < 3; b++) mma16816(o2[b], va[b] + 4, pb[2], pb[3]);
      mma1688(o[0], m0.x, m0.y, pb[4]);
      mma1688(o[1], m1.x, m1.y, pb[4]);
      mma1688(o[2], m2.x, m2.y, pb[4]);
      mma16816(sm, ones, pb[0], pb[1]);
      mma16816(sn, ones, pb[2], pb[3]);
      mma1688(so, ONES, ONES, pb[4]);
      wpre(NO_EARLY, NO_MID);
#pragma unroll
      for (int b = 0; b < 3; b++)
        sts64(dst + (b == 0 ? R_QB : (b == 1 ? R_QA : R_O2)), movmat(pack2(o[b][0] + o2[b][0], o[b][1] + o2[b][1])),
              movmat(pack2(o[b][2] + o2[b][2], o[b][3] + o2[b][3])));
      sm[0] += sn[0] + so[0]; sm[1] += sn[1] + so[1];
      if (rF - sb < 64) sts64f(sb + R_MI + 16 + ((rF - sb) >> 1), sm[0], sm[1]);
      wpre(NO_MID, 12);
      TR(7);
      if (two) oproj(std::true_type{}, std::integral_constant<int, 12>{}, wot, rF, woA, woB, sm[0], sm[1], true);
      else oproj(std::false_type{}, std::integral_constant<int, 12>{}, wot, rF, woA, woB, sm[0], sm[1], true);
    }
  };

  GTR(5); GTR(6);
  if (g == 0) {
    window(std::integral_constant<int, 0>{}, std::true_type{});
    GTR(7);
#pragma unroll 1
    for (s = 0; s < NSEG - 1; s++) {
      step(std::integral_constant<int, 0>{}, std::false_type{});
      window(std::integral_constant<int, 0>{}, std::false_type{});
    }
    step(std::integral_constant<int, 0>{}, std::true_type{});
  } else {
    window(std::integral_constant<int, 1>{}, std::true_type{});
#pragma unroll 1
    for (s = 0; s < NSEG - 1; s++) {
      step(std::integral_constant<int, 1>{}, std::false_type{});
      window(std::integral_constant<int, 1>{}, std::false_type{});
    }
    step(std::integral_constant<int, 1>{}, std::true_type{});
  }
  __syncthreads();
  if (tid == 160) {
    fence_async_smem();
    tma_store2(&tmK, sb + R_KT, D0, (NSEG - 1) * LK);
    tma_store2(&tmV, sb + R_VT, D0, (NSEG - 1) * LK);
    bulk_commit();
    bulk_wait0();
    asm volatile("red.relaxed.gpu.global.add.u32 [%0], 1;" ::"l"(&g_segcnt[NSEG - 2]) : "memory");
    asm volatile("red.relaxed.gpu.global.add.u32 [%0], 1;" ::"l"(&g_segcnt[NSEG - 1]) : "memory");
    asm volatile("red.relaxed.gpu.global.add.u32 [%0], 2;" ::"l"(&g_prog) : "memory");
  }
  GTR(8);
  if (tid == 0) mbar_wait(VBAR, (NSEG - 1) & 1);
  GTR(9);
}

enum { IT_GATE = 0, IT_QKV = 1, IT_XATT = 2, IT_OUT = 3, IT_BATT = 4, IT_CVT = 5, IT_INIT = 6, IT_END = 7 };
constexpr int C_GATE = 0, C_QKV = 16, C_OB = 32, C_ACC = 48, C_O = 80;
constexpr uint32_t NONE = ~0u;
#define HP 0x1223346888888888ull
#define XD 0x4589aaaaaaaaaaaaull
#define KREQ 4
#define ADELAY 0
#define PP 3
__host__ __device__ constexpr uint32_t mk_item(int ty, int t, int a, int b = 0, int c = 0) { return ty | (t << 3) | (a << 8) | (b << 16) | (c << 24); }
struct ItemTab { uint32_t v[1280]; int n; };
constexpr ItemTab make_items() {
  ItemTab T{};
  int n = 0;
  for (int t = 0; t < 16; t++) T.v[n++] = mk_item(IT_GATE, t, 0);
  for (int t = 0; t < 16; t++) for (int a = 0; a < 5; a++) T.v[n++] = mk_item(IT_QKV, t, a);
  for (int t = 0; t < 32; t++) for (int a = 0; a < 4; a++) T.v[n++] = mk_item(IT_BATT, t, a);
  for (int t = 0; t < 16; t++) for (int a = 0; a < 2; a++) T.v[n++] = mk_item(IT_INIT, t, a);
  for (int t = 0; t < 16; t++) {
    const int hp = (HP >> 4 * t) & 15;
    for (int h = 0; h < 32; h += hp) for (int a = 0; a < 2; a++) T.v[n++] = mk_item(IT_OUT, t, a, h, h + hp < 32 ? h + hp : 32);
  }
  T.n = n;
  return T;
}
constexpr ItemTab k_items_host = make_items();
constexpr int NITEMS = k_items_host.n;
__constant__ ItemTab c_items = make_items();

constexpr int AUX_GRID = 132, NST = 7, STG = 32768;
constexpr int A_FULL = NST * STG, A_EMPTY = A_FULL + 64, A_ITEM = A_EMPTY + 64, A_QBAR = A_ITEM + 32, A_QENT = A_QBAR + 128, A_MISC = A_QENT + 256,
              A_SMEM = A_MISC + 64, A_REQ = A_FULL + 56, A_RSP = A_EMPTY + 56, A_MAIL = A_MISC + 48;
static_assert(A_SMEM <= 232448, "smem");
enum { OP_END = 0, OP_O = 1, OP_QKV = 2, OP_OB = 3, OP_SET = 4, OP_ADD = 5 };

struct AuxMaps { CUtensorMap xA, wq, wqkv, wo, wob, k, v, oA, oS, obA, obS, qkvS, qkvQ, qkvK, out; };

__device__ __forceinline__ void mbar_wait_long(uint32_t b, uint32_t par) {
  int n = 0;
#pragma unroll 1
  while (!mbar_try(b, par)) { if (++n > (SPIN_MAX << 4)) { g_err = 8; break; } }
}
__device__ __forceinline__ uint64_t mk_desc(uint32_t addr, uint32_t lbo, uint32_t sbo, uint32_t mode) {
  return (uint64_t)((addr & 0x3FFFF) >> 4) | ((uint64_t)(lbo >> 4) << 16) | ((uint64_t)(sbo >> 4) << 32) | ((uint64_t)mode << 62);
}

__global__ void __launch_bounds__(384, 1)
aux_kernel(const __grid_constant__ AuxMaps tm, const bf16* __restrict__ x, const bf16* __restrict__ gate_w) {
  extern __shared__ __align__(1024) unsigned char smem[];
  const uint32_t sb = smem_u32(smem);
  const int tid = threadIdx.x, lane = tid & 31, wid = __shfl_sync(~0u, tid >> 5, 0);
  uint32_t epoch = 0, j0 = 0;
  const uint32_t c0 = clk32();
  if (tid == 352) GTA(0);
  if (tid >= 256) epoch = *(volatile uint32_t*)&g_epoch + 1;
  if (tid == 352) j0 = atomicAdd(&g_queue[32], 1u);
  if (tid == 0) {
    mbar_init(sb + A_REQ, 1); mbar_init(sb + A_RSP, 1);
    for (int i = 0; i < NST; i++) { mbar_init(sb + A_FULL + i * 8, 1); mbar_init(sb + A_EMPTY + i * 8, 8); }
    for (int i = 0; i < 16; i++) mbar_init(sb + A_QBAR + i * 8, 4);
    asm volatile("fence.mbarrier_init.release.cluster;" ::: "memory");
  }
  if (tid < 15) prefetch_map(&tm.xA + tid);
  if (tid == 352) GTA(4);
  __syncthreads();
  if (tid == 352) GTA(5);
  uint32_t st = 0, ph = 0;
  auto advance = [&]() { if (++st == NST) { st = 0; ph ^= 1; } };

  if (wid >= 8) {
    asm volatile("setmaxnreg.dec.sync.aligned.u32 40;");
    if (tid == 352) GTA(6);
    auto cnt = [&](int c, uint32_t per) -> bool { return (int)(ldg_rlx32(&g_cnt[c * 8]) - epoch * per) >= 0; };
    auto ready = [&](uint32_t item) -> int {
      const int ty = item & 7, t = (item >> 3) & 31, b = (item >> 17) & 127, n = (((item >> 24) + 1) >> 1) - b;
      int r;
      if (ty == IT_OUT) {
        const int c = C_O + t * 16 + b;
        const bool r0 = cnt(c, 2), r1 = cnt(c + (n > 1), 2), r2 = cnt(c + (n > 2) * 2, 2), r3 = cnt(c + (n > 3) * 3, 2);
        r = r0 & cnt(C_ACC + t, 4) ? (r1 ? (r2 ? (r3 ? 4 : 3) : 2) : 1) : 0;
      } else if (ty == IT_XATT) {
        const uint4 v = ldg_rlx128(&g_segcnt[4 * t]);
        const uint32_t e = epoch * 96;
        r = ((int)(v.x - e) >= 0) & ((int)(v.y - e) >= 0) & ((int)(v.z - e) >= 0) & ((int)(v.w - e) >= 0);
      } else if (ty == IT_BATT) {
        r = cnt(C_GATE, 16) & cnt(C_QKV + (t >> 1), 10) & cnt(C_QKV + (max(t - 1, 0) >> 1), 10);
      } else {
        r = ty <= IT_QKV || cnt(C_OB + t, 8);
      }
      asm volatile("fence.acquire.gpu; fence.proxy.async.global;" ::: "memory");
      return r;
    };
    if (wid == 11 && lane == 0) {
      uint32_t pend = j0 < (uint32_t)NITEMS ? c_items.v[j0] : (uint32_t)IT_END;
      bool xleft = true;
      uint32_t nidx = 0, pidx = j0;
      GTA(1);
      if (j0 < 64) spin_until(c0, ADELAY);
      if (pend != 12345) GTA(2);
#pragma unroll 1
      for (uint32_t e = 0;; e++) {
        if (e) mbar_wait_long(sb + A_REQ, (e - 1) & 1);
        uint32_t item = NONE;
        int rdy = 0, spins = 0;
#pragma unroll 1
        while (true) {
          const bool fresh = pend == NONE;
          if (xleft) {
            const uint4 c = ldg_rlx128(&g_queue[0]);
            const uint32_t pr = ldg_rlx32(&g_prog) - (epoch - 1) * (96 * NSEG);
            const bool gates = cnt(C_GATE, 16);
            if (!fresh) rdy = ready(pend);
            auto full = [](uint32_t v) { v = (v | (v >> 2)) & 0x30303030u; return __popc((v | (v >> 1)) & 0x10101010u); };
            const int t = full(c.x) + full(c.y) + full(c.z) + full(c.w);
            xleft = t < 16;
            if (xleft && gates && (int)pr >= 96 * (4 * t - 8 + (int)((XD >> 4 * t) & 15))) {
              const uint32_t j = (atomicAdd(&g_queue[t >> 2], 1u << (t & 3) * 8) >> (t & 3) * 8) & 255;
              if (j < 16) { item = mk_item(IT_XATT, t, j); rdy = 0; nidx = NITEMS + 132 + t * 16 + j; }
            }
          } else if (!fresh) {
            rdy = ready(pend);
          }
          if (item == NONE) {
            if (fresh) {
              pidx = atomicAdd(&g_queue[32], 1u);
              pend = pidx < (uint32_t)NITEMS ? c_items.v[pidx] : (uint32_t)IT_END;
              rdy = ready(pend);
            }
            const int need = (pend & 7) == IT_OUT && xleft ? (((pend >> 24) + 1) >> 1) - ((pend >> 17) & 127) : 1;
            if (pend == IT_END ? !xleft : rdy >= need) { item = pend; pend = NONE; nidx = pidx; }
          }
          if (item != NONE) break;
          if (++spins > SPIN_MAX) { g_err = 10; item = IT_END; break; }
          __nanosleep(50);
        }
        if (e == 0) GTA(3);
        sts128(sb + A_MAIL, item, rdy, nidx, 0);
        mbar_arrive(sb + A_RSP);
        if (item == IT_END) break;
      }
      if (atomicAdd(&g_queue[64], 1u) == AUX_GRID - 1) { *(uint4*)g_queue = make_uint4(0, 0, 0, 0); g_queue[32] = 0; g_queue[64] = 0; g_epoch = epoch; }
      asm volatile("griddepcontrol.wait;" ::: "memory");
    } else if (wid == 8 && lane == 0) {
      uint32_t item = 0;
      auto slot = [&](uint32_t bytes) -> uint32_t {
        mbar_wait_long(sb + A_EMPTY + st * 8, ph ^ 1);
        sts32(sb + A_ITEM + st * 4, item);
        if (bytes) mbar_expect(sb + A_FULL + st * 8, bytes); else mbar_arrive(sb + A_FULL + st * 8);
        return sb + st * STG;
      };
#pragma unroll 1
      for (uint32_t e = 0;; e++) {
        mbar_wait_long(sb + A_RSP, e & 1);
        const uint4 mail = lds128(sb + A_MAIL);
        asm volatile("fence.proxy.async.global;" ::: "memory");
        item = mail.x;
        int rdy = mail.y;
        int k = (item & 7) == IT_OUT ? ((item >> 16) & 255) * 6 : 0;
        const int k1 = (item & 7) == IT_OUT ? (item >> 24) * 6 : (0x01140103001c1401ull >> ((item & 7) * 8)) & 255;
        const int kreq = max(k1 - KREQ, k);
#pragma unroll 1
        for (; k < k1; k++) {
          item = pin(item);
          const int ty = item & 7, t = (item >> 3) & 31, a = (item >> 8) & 255;
          const bool out_ = ty == IT_OUT, gemm1 = ty == IT_QKV || ty == IT_XATT;
          const int dep = out_ ? k / 12 - ((item >> 17) & 127) : (ty == IT_XATT ? (k >= 20) - 1 : -1);
          if (rdy <= dep || (k == 12 && ty == IT_XATT)) {
            int n = 0;
#pragma unroll 1
            while ((rdy = ready(pin(item))) <= dep) {
              if (++n > SPIN_MAX) { g_err = 7; break; }
              __nanosleep(20);
            }
          }
          const uint32_t fb = sb + A_FULL + st * 8;
          if (out_ || ty == IT_INIT) {
            const uint32_t d = slot(28672);
            tma_load2(d, out_ ? &tm.oA : &tm.obA, k * 32, t * 128, fb);
            tma_load3(d + 8192, out_ ? &tm.wo : &tm.wob, 0, k * 32, a * 5, fb);
          } else if (gemm1 && k < 20) {
            const uint32_t d = slot(32768);
            tma_load2(d, &tm.xA, k * 32, t * 128, fb);
            tma_load3(d + 8192, ty == IT_QKV ? &tm.wqkv : &tm.wq, 0, k * 32, a * 6, fb);
          } else if (gemm1) {
            const uint32_t d = slot(30720);
            tma_load3(d, k < 24 ? &tm.k : &tm.v, 0, (4 * t + (k & 2)) * LK, (2 * a + (k & 1)) * 3, fb);
          } else if (ty == IT_BATT) {
            const uint32_t d = slot(k ? 25600 : 20480);
            tma_load2(d, k ? &tm.qkvK : &tm.qkvQ, k * 640 + a * 160, t * 64 - (k ? 16 : 0), fb);
          } else {
            slot(0);
          }
          if (k == kreq) mbar_arrive(sb + A_REQ);
          advance();
        }
        if (item == IT_END) break;
        if ((0x4a >> (item & 7)) & 1) {
#pragma unroll 1
          for (k = 0; k < 4; k++) { slot(0); advance(); }
        }
      }
    } else if ((wid == 9 || wid == 10) && lane == 0) {
      const uint32_t qb = sb + A_QBAR + (wid - 9) * 64, qe = sb + A_QENT + (wid - 9) * 128;
      for (uint32_t e = 0;; e++) {
        mbar_wait_long(qb + (e & 7) * 8, (e >> 3) & 1);
        const uint4 en = lds128(qe + (e & 7) * 16);
        const int op = en.x & 15, sg = (en.x >> 4) & 15, rel = (en.x >> 8) & 15, nb = (en.x >> 12) & 15;
        if (op == OP_END) break;
        const uint32_t src = sb + sg * STG;
        if (op == OP_O) tma_store3(&tm.oS, src, 0, en.y, en.z);
        else if (op == OP_QKV) tma_store3(&tm.qkvS, src, 0, en.y, en.z);
        else if (op == OP_OB) tma_store2(&tm.obS, src, en.z, en.y);
        else if (op == OP_SET) { for (int i = 0; i < nb; i++) tma_store3(&tm.out, src + i * 8192, 0, en.y, en.z + i); }
        else { for (int i = 0; i < nb; i++) tma_red3(&tm.out, src + i * 8192, 0, en.y, en.z + i); }
        bulk_commit();
        bulk_wait_read0();
        asm volatile("mbarrier.arrive.shared::cta.b64 _, [%0], %1;" ::"r"(sb + A_EMPTY + sg * 8), "r"(rel) : "memory");
        if (en.w) {
          bulk_wait0();
          asm volatile("red.relaxed.gpu.global.add.u32 [%0], %1;" ::"l"(&g_cnt[(en.w - 1) * 8]), "r"(1) : "memory");
        }
      }
      bulk_wait0();
      if (wid == 10) GTA(7);
    }
  } else {
    asm volatile("setmaxnreg.inc.sync.aligned.u32 232;");
    const int g = wid >> 2, w = wid & 3;
    uint32_t qn = 0;
    auto wait_full = [&]() { mbar_wait_long(sb + A_FULL + st * 8, ph); };
    auto release = [&](uint32_t s_) { if (lane == 0) mbar_arrive(sb + A_EMPTY + s_ * 8); };
    auto take_pair = [&]() -> uint32_t {
      wait_full();
      const uint32_t s0 = st; advance();
      wait_full();
      const uint32_t s1 = st; advance();
      release(g ? s0 : s1);
      return g ? s1 : s0;
    };
    auto push = [&](uint32_t w0, uint32_t w1, uint32_t w2, uint32_t w3) {
      fence_async_smem();
      if (w == 0 && lane == 0) sts128(sb + A_QENT + g * 128 + (qn & 7) * 16, w0, w1, w2, w3);
      __syncwarp();
      if (lane == 0) mbar_arrive(sb + A_QBAR + g * 64 + (qn & 7) * 8);
      qn++;
    };
    const uint32_t stm = (16 * w + (lane & 7) + (lane & 8)) * 128, stx = lane & 7, sth = lane >> 4;
    auto stage_bf16 = [&](uint32_t dst, const float* d, float s0, float s1, int nks = 12) {
#pragma unroll
      for (int ks = 0; ks < nks; ks++)
        stsm4(dst + (ks >> 2) * 8192 + stm + (((2 * (ks & 3) + sth) ^ stx) << 4), pack2(d[8 * ks] * s0, d[8 * ks + 1] * s0), pack2(d[8 * ks + 2] * s1, d[8 * ks + 3] * s1),
              pack2(d[8 * ks + 4] * s0, d[8 * ks + 5] * s0), pack2(d[8 * ks + 6] * s1, d[8 * ks + 7] * s1));
    };
#pragma unroll 1
    while (true) {
      wait_full();
      const uint32_t item = lds32(sb + A_ITEM + st * 4);
      const int ty = item & 7, t = (item >> 3) & 31, a = (item >> 8) & 255;
      if (ty == IT_QKV || ty == IT_XATT) {
        float acc[192] = {};
        uint32_t prev = 0;
#pragma unroll 1
        for (int k = 0; k < 20; k++) {
          if (k) wait_full();
          const uint32_t s_ = sb + st * STG;
          const uint64_t da = mk_desc(s_, 16, 512, 2), db = mk_desc(s_ + 8192 + g * 12288, 4096, 1024, 1);
          wg_fence();
          wgmma_ss192t(acc, da, db, k);
          wgmma_ss192t(acc + 96, da + 256, db, k);
          wgmma_ss192t(acc, da + 2, db + 128, 1);
          wgmma_ss192t(acc + 96, da + 258, db + 128, 1);
          wg_commit();
          if (k) { wg_wait1(); release(prev); }
          prev = st; advance();
        }
        wg_wait0();
        fence_regs<192>(acc);
        release(prev);
        if (ty == IT_QKV) {
#pragma unroll
          for (int q = 0; q < 2; q++) {
            const uint32_t m = take_pair();
            stage_bf16(sb + m * STG, acc + q * 96, 1.f, 1.f);
            push(OP_QKV | (m << 4) | (4 << 8), t * 128 + q * 64, a * 6 + g * 3, q ? C_QKV + t + 1 : 0);
          }
        } else {
          uint32_t qf[24][4];
#pragma unroll
          for (int ks = 23; ks >= 0; ks--)
#pragma unroll
            for (int j = 0; j < 4; j++)
              asm volatile("cvt.rn.bf16x2.f32 %0, %1, %2;" : "=r"(qf[ks][j]) : "f"(acc[8 * ks + 2 * j + 1]), "f"(acc[8 * ks + 2 * j]));
          float sc[2][40] = {};
          uint32_t kst[2];
#pragma unroll
          for (int q = 0; q < 2; q++) {
            kst[q] = take_pair();
            const uint64_t db = mk_desc(sb + kst[q] * STG, 16, 1024, 1);
            wg_fence();
#pragma unroll
            for (int ks = 0; ks < 12; ks++) wgmma_rs80(sc[q], qf[q * 12 + ks], db + (((ks >> 2) * 10240 + (ks & 3) * 32) >> 4), ks);
            wg_commit();
          }
          const int tt = 16 * (w & 1) + (lane >> 2) - 2 * (lane & 3);
          const float* gp = g_gate + t * 128 + 16 * w + (lane >> 2);
          const float gt[4] = {__ldcg(gp), __ldcg(gp + 8), __ldcg(gp + 64), __ldcg(gp + 72)};
          uint32_t pf[2][5][4];
          float rs[2][2];
          auto softmax = [&](const float* s_, uint32_t (&p)[5][4], float* r) {
            constexpr float SCL = 0.07216878364870322f * 1.4426950408889634f;
            float v[20];
#pragma unroll
            for (int i = 0; i < 20; i++) {
              v[i] = w >= 2 ? s_[20 + i] : s_[i];
              if (i >= 4 && 8 * ((i >> 2) - 1) + (i & 1) > tt + ((i & 2) ? 8 : 0)) v[i] = -INFINITY;
            }
            uint32_t pt[5][2];
#pragma unroll
            for (int h = 0; h < 2; h++) {
              float mx = fmaxf(v[2 * h], v[2 * h + 1]);
#pragma unroll
              for (int j = 1; j < 5; j++) mx = fmaxf(mx, fmaxf(v[4 * j + 2 * h], v[4 * j + 2 * h + 1]));
              mx = fmaxf(mx, __shfl_xor_sync(~0u, mx, 1));
              mx = fmaxf(mx, __shfl_xor_sync(~0u, mx, 2));
              const float mo = mx * SCL;
              float sum = 0.f;
#pragma unroll
              for (int j = 0; j < 5; j++) {
                const float e0 = ex2(fmaf(v[4 * j + 2 * h], SCL, -mo)), e1 = ex2(fmaf(v[4 * j + 2 * h + 1], SCL, -mo));
                pt[j][h] = pack2(e0, e1);
                sum += bf_lo(pt[j][h]) + bf_hi(pt[j][h]);
              }
              sum += __shfl_xor_sync(~0u, sum, 1);
              sum += __shfl_xor_sync(~0u, sum, 2);
              r[h] = rcp(sum);
            }
#pragma unroll
            for (int J = 0; J < 10; J++)
#pragma unroll
              for (int h = 0; h < 2; h++) p[J >> 1][(J & 1) * 2 + h] = (J >= 5) == (w >= 2) ? pt[J % 5][h] : 0u;
          };
          wg_wait1();
          fence_regs<40>(sc[0]);
          release(kst[0]);
          softmax(sc[0], pf[0], rs[0]);
#pragma unroll
          for (int q = 0; q < 2; q++) {
            const uint32_t m = take_pair();
            const uint64_t db = mk_desc(sb + m * STG, 10240, 1024, 1);
            float o[96] = {};
            wg_fence();
#pragma unroll
            for (int ks = 0; ks < 5; ks++) wgmma_rs192t(o, pf[q][ks], db + ks * 128, ks);
            wg_commit();
            if (q == 0) {
              wg_wait1();
              fence_regs<40>(sc[1]);
              release(kst[1]);
              softmax(sc[1], pf[1], rs[1]);
            }
            wg_wait0();
            fence_regs<96>(o);
            bar_sync(1 + g, 128);
            stage_bf16(sb + m * STG, o, rs[q][0] * gt[2 * q], rs[q][1] * gt[2 * q + 1]);
            push(OP_O | (m << 4) | (4 << 8), t * 128 + q * 64, a * 6 + g * 3, q ? C_O + t * 16 + a + 1 : 0);
          }
        }
      } else if (ty == IT_OUT || ty == IT_INIT) {
        float acc[160] = {};
        const int hb = (item >> 16) & 255, nh = (item >> 24) - hb, nk = ty == IT_OUT ? nh * 6 : 20, jh = a & 1;
        const uint32_t ln = pin(lane), ao = (g * 64 + 16 * w + (ln & 15)) * 64 + (((ln >> 4) ^ ((ln >> 1) & 3)) << 4);
        if (PP && g == 1) bar_arrive(4, 256);
#pragma unroll 1
        for (int k = 0; k < nk; k += 2) {
          uint32_t af[4][4], sg[2];
#pragma unroll
          for (int e = 0; e < 2; e++) {
            if (k + e) wait_full();
            sg[e] = st;
            ldsm4(af[2 * e], sb + st * STG + ao);
            ldsm4(af[2 * e + 1], sb + st * STG + (ao ^ 32));
            advance();
          }
          if (PP) bar_sync(4 + g, 256);
          wg_fence();
#pragma unroll
          for (int e = 0; e < 4; e++) {
            const uint64_t db = mk_desc(sb + sg[e >> 1] * STG + 8192 + (e & 1) * 2048, 4096, 1024, 1);
            if (PP == 2 && e == 3 && (g == 0 || k + 2 < nk)) bar_arrive(5 - g, 256);
            wgmma_rs192t(acc, af[e], db, 1);
            if (PP == 3 && e == 3 && (g == 0 || k + 2 < nk)) bar_arrive(5 - g, 256);
            wgmma_rs128t(acc + 96, af[e], db + 768, 1);
          }
          wg_commit();
          if (PP == 1 && (g == 0 || k + 2 < nk)) bar_arrive(5 - g, 256);
          wg_wait0();
          release(sg[0]); release(sg[1]);
        }
        fence_regs<160>(acc);
        const uint32_t row = t * 128 + g * 64;
#pragma unroll
        for (int q = 0; q < 2; q++) {
          const uint32_t m = take_pair();
          stage_bf16(sb + m * STG, acc + q * 96, 1.f, 1.f, q ? 8 : 12);
          push((ty == IT_OUT ? OP_ADD : OP_SET) | (m << 4) | (4 << 8) | ((3 - q) << 12), row, jh * 5 + q * 3, q && ty == IT_INIT ? C_ACC + t + 1 : 0);
        }
      } else if (ty == IT_BATT) {
        const uint32_t sq = st; advance();
        wait_full();
        const uint32_t sk = st; advance();
        wait_full();
        const uint32_t sv = st; advance();
        const int h = tid & 7;
#pragma unroll 1
        for (int p = 0; p < 2; p++) {
          const int tok = (tid >> 3) + 32 * p, pos = t * 64 + tok;
          const uint32_t qa = sb + sq * STG + tok * 320 + h * 40, ka = sb + sk * STG + (tok + 16) * 320 + h * 40, va = sb + sv * STG + (tok + 16) * 320 + h * 40;
          const float gt = __ldcg(g_gate + 2048 + pos);
          float q[20], l[8];
#pragma unroll
          for (int i = 0; i < 5; i++) { const uint2 u = lds64(qa + i * 8); q[4 * i] = bf_lo(u.x); q[4 * i + 1] = bf_hi(u.x); q[4 * i + 2] = bf_lo(u.y); q[4 * i + 3] = bf_hi(u.y); }
          float mx = -INFINITY;
#pragma unroll
          for (int j = 0; j < 8; j++) {
            float s0 = 0.f, s1 = 0.f;
#pragma unroll
            for (int i = 0; i < 5; i++) {
              const uint2 u = lds64(ka - j * 640 + i * 8);
              s0 = fmaf(q[4 * i], bf_lo(u.x), s0); s1 = fmaf(q[4 * i + 1], bf_hi(u.x), s1);
              s0 = fmaf(q[4 * i + 2], bf_lo(u.y), s0); s1 = fmaf(q[4 * i + 3], bf_hi(u.y), s1);
            }
            l[j] = pos - 2 * j >= 0 ? s0 + s1 : -INFINITY;
            mx = fmaxf(mx, l[j]);
          }
          constexpr float SCL = 0.22360679774997896f * 1.4426950408889634f;
          const float mo = mx * SCL;
          float sum = 0.f;
#pragma unroll
          for (int j = 0; j < 8; j++) { l[j] = ex2(fmaf(l[j], SCL, -mo)); sum += l[j]; }
          const float r = gt * rcp(sum);
#pragma unroll
          for (int i = 0; i < 20; i++) q[i] = 0.f;
#pragma unroll
          for (int j = 0; j < 8; j++) {
#pragma unroll
            for (int i = 0; i < 5; i++) {
              const uint2 u = lds64(va - j * 640 + i * 8);
              q[4 * i] = fmaf(l[j], bf_lo(u.x), q[4 * i]); q[4 * i + 1] = fmaf(l[j], bf_hi(u.x), q[4 * i + 1]);
              q[4 * i + 2] = fmaf(l[j], bf_lo(u.y), q[4 * i + 2]); q[4 * i + 3] = fmaf(l[j], bf_hi(u.y), q[4 * i + 3]);
            }
          }
#pragma unroll
          for (int i = 0; i < 5; i++) sts64(qa + i * 8, pack2(q[4 * i] * r, q[4 * i + 1] * r), pack2(q[4 * i + 2] * r, q[4 * i + 3] * r));
        }
        __syncwarp();
        release(sk); release(sv);
        fence_async_smem();
        bar_sync(3, 256);
        if (g == 0) push(OP_OB | (sq << 4) | (8 << 8), t * 64, a * 160, C_OB + (t >> 1) + 1);
      } else if (ty == IT_GATE) {
        release(st); advance();
        uint4 gw[3];
#pragma unroll
        for (int i = 0; i < 3; i++) gw[i] = (i < 2 || lane < 16) ? __ldg((const uint4*)gate_w + lane + 32 * i) : make_uint4(0, 0, 0, 0);
        const uint4* xr = (const uint4*)(x + (size_t)(t * 128 + wid * 16) * DM) + lane;
        uint4 v[16][3];
#pragma unroll
        for (int r = 0; r < 16; r++)
#pragma unroll
          for (int i = 0; i < 3; i++) v[r][i] = (i < 2 || lane < 16) ? __ldg(xr + r * (DM / 8) + 32 * i) : make_uint4(0, 0, 0, 0);
        float z = 0.f;
#pragma unroll
        for (int r = 0; r < 16; r++) {
          float s_ = 0.f;
#pragma unroll
          for (int i = 0; i < 3; i++) {
            const uint32_t p0 = hmul2(v[r][i].x, gw[i].x), p1 = hmul2(v[r][i].y, gw[i].y), p2 = hmul2(v[r][i].z, gw[i].z), p3 = hmul2(v[r][i].w, gw[i].w);
            s_ += ((bf_lo(p0) + bf_hi(p0)) + (bf_lo(p1) + bf_hi(p1))) + ((bf_lo(p2) + bf_hi(p2)) + (bf_lo(p3) + bf_hi(p3)));
          }
#pragma unroll
          for (int o = 16; o; o >>= 1) s_ += __shfl_xor_sync(~0u, s_, o);
          if (lane == r) z = s_;
        }
        z = bf_lo(pack2(z, 0.f));
        const float gv = bf_lo(pack2(1.f / (1.f + __expf(-z)), 0.f));
        if (lane < 16) { g_gate[t * 128 + wid * 16 + lane] = gv; g_gate[2048 + t * 128 + wid * 16 + lane] = bf_lo(pack2(1.f - gv, 0.f)); }
        __threadfence();
        bar_sync(3, 256);
        if (tid == 0) asm volatile("red.release.gpu.global.add.u32 [%0], 1;" ::"l"(&g_cnt[C_GATE * 8]) : "memory");
      } else {
        release(st);
        push(OP_END, 0, 0, 0);
        break;
      }
    }
  }
}

typedef CUresult (*EncFn)(CUtensorMap*, CUtensorMapDataType, cuuint32_t, void*, const cuuint64_t*, const cuuint64_t*, const cuuint32_t*,
                          const cuuint32_t*, CUtensorMapInterleave, CUtensorMapSwizzle, CUtensorMapL2promotion, CUtensorMapFloatOOBfill);

#define PROMO CU_TENSOR_MAP_L2_PROMOTION_L2_128B
void make_map(EncFn enc, CUtensorMap* tm, const void* base, int rank, const cuuint64_t* dims, const cuuint64_t* strides, const cuuint32_t* box,
              CUtensorMapSwizzle sw = CU_TENSOR_MAP_SWIZZLE_128B, CUtensorMapDataType dt = CU_TENSOR_MAP_DATA_TYPE_BFLOAT16) {
  const cuuint32_t es[5] = {1, 1, 1, 1, 1};
  enc(tm, dt, rank, const_cast<void*>(base), dims, strides, box, es, CU_TENSOR_MAP_INTERLEAVE_NONE, sw, PROMO,
      CU_TENSOR_MAP_FLOAT_OOB_FILL_NONE);
}
void map_blk(EncFn enc, CUtensorMap* tm, const void* base, int rows, int cols, int brows, int bblk) {
  const cuuint64_t d[3] = {64, (cuuint64_t)rows, (cuuint64_t)cols / 64}, st[2] = {(cuuint64_t)cols * 2, 128};
  const cuuint32_t b[3] = {64, (cuuint32_t)brows, (cuuint32_t)bblk};
  make_map(enc, tm, base, 3, d, st, b);
}
void map_2d(EncFn enc, CUtensorMap* tm, const void* base, int rows, int cols, int brows, int bcols, CUtensorMapSwizzle sw) {
  const cuuint64_t d[2] = {(cuuint64_t)cols, (cuuint64_t)rows}, st[1] = {(cuuint64_t)cols * 2};
  const cuuint32_t b[2] = {(cuuint32_t)bcols, (cuuint32_t)brows};
  make_map(enc, tm, base, 2, d, st, b, sw);
}

}

extern "C" void kernel_launch(void* const* d_in, const int* in_sizes, int n_in, void* d_out, int out_size) {
  const bf16* x = (const bf16*)d_in[0];
  const bf16* mem0 = (const bf16*)d_in[1];
  const bf16* Wq = (const bf16*)d_in[2];
  const bf16* Wk = (const bf16*)d_in[3];
  const bf16* Wv = (const bf16*)d_in[4];
  const bf16* Wo = (const bf16*)d_in[5];
  const bf16* wqkv = (const bf16*)d_in[8];
  const bf16* wob = (const bf16*)d_in[9];
  const bf16* gate_w = (const bf16*)d_in[10];
  static EncFn enc = nullptr;
  static void *pK = nullptr, *pV = nullptr, *pO = nullptr, *pQ = nullptr, *pB = nullptr;
  if (!enc) {
    void* fn = nullptr;
    cudaDriverEntryPointQueryResult qr;
    cudaGetDriverEntryPoint("cuTensorMapEncodeTiled", &fn, cudaEnableDefault, &qr);
    enc = (EncFn)fn;
    cudaGetSymbolAddress(&pK, g_K);
    cudaGetSymbolAddress(&pV, g_V);
    cudaGetSymbolAddress(&pO, g_O);
    cudaGetSymbolAddress(&pQ, g_qkv);
    cudaGetSymbolAddress(&pB, g_Ob);
    cudaFuncSetAttribute(rec_kernel, cudaFuncAttributeMaxDynamicSharedMemorySize, R_SMEM_ALLOC);
    cudaFuncSetAttribute(aux_kernel, cudaFuncAttributeMaxDynamicSharedMemorySize, A_SMEM);
  }
  CUtensorMap tmX, tmK, tmV, tmWq, tmWq2, tmWk, tmWv, tmWo;
  map_2d(enc, &tmWq, Wq, DM, HD, 144, 64, CU_TENSOR_MAP_SWIZZLE_128B);
  map_2d(enc, &tmWq2, Wq, DM, HD, 32, 64, CU_TENSOR_MAP_SWIZZLE_128B);
  map_2d(enc, &tmWk, Wk, DM, HD, 128, 64, CU_TENSOR_MAP_SWIZZLE_128B);
  map_2d(enc, &tmWv, Wv, DM, HD, 128, 64, CU_TENSOR_MAP_SWIZZLE_128B);
  {
    const cuuint64_t d[3] = {32, HD, 20}, st[2] = {DM * 2, 64};
    const cuuint32_t b[3] = {32, 64, 7};
    make_map(enc, &tmWo, Wo, 3, d, st, b, CU_TENSOR_MAP_SWIZZLE_64B);
  }
  map_blk(enc, &tmX, x, S_TOK, DM, 32, 10);
  map_2d(enc, &tmK, pK, NSEG * LK, HD, LK, 64, CU_TENSOR_MAP_SWIZZLE_128B);
  map_2d(enc, &tmV, pV, NSEG * LK, HD, LK, 64, CU_TENSOR_MAP_SWIZZLE_128B);
  AuxMaps am;
  map_2d(enc, &am.xA, x, S_TOK, DM, 128, 32, CU_TENSOR_MAP_SWIZZLE_64B);
  map_blk(enc, &am.wq, Wq, DM, HD, 32, 6);
  map_blk(enc, &am.wqkv, wqkv, DM, 3 * DM, 32, 6);
  map_blk(enc, &am.wo, Wo, HD, DM, 32, 5);
  map_blk(enc, &am.wob, wob, DM, DM, 32, 5);
  map_blk(enc, &am.k, pK, NSEG * LK, HD, 80, 3);
  map_blk(enc, &am.v, pV, NSEG * LK, HD, 80, 3);
  map_2d(enc, &am.oA, pO, S_TOK, HD, 128, 32, CU_TENSOR_MAP_SWIZZLE_64B);
  map_blk(enc, &am.oS, pO, S_TOK, HD, 64, 3);
  map_2d(enc, &am.obA, pB, S_TOK, DM, 128, 32, CU_TENSOR_MAP_SWIZZLE_64B);
  map_2d(enc, &am.obS, pB, S_TOK, DM, 64, 160, CU_TENSOR_MAP_SWIZZLE_NONE);
  map_blk(enc, &am.qkvS, pQ, S_TOK, 3 * DM, 64, 3);
  map_2d(enc, &am.qkvQ, pQ, S_TOK, 3 * DM, 64, 160, CU_TENSOR_MAP_SWIZZLE_NONE);
  map_2d(enc, &am.qkvK, pQ, S_TOK, 3 * DM, 80, 160, CU_TENSOR_MAP_SWIZZLE_NONE);
  map_blk(enc, &am.out, d_out, S_TOK, DM, 64, 1);
  rec_kernel<<<96, 256, R_SMEM_ALLOC, cudaStreamPerThread>>>(tmX, tmK, tmV, tmWq, tmWq2, tmWk, tmWv, tmWo, mem0, Wq, Wo, x);
  cudaLaunchConfig_t cfg = {};
  cfg.gridDim = dim3(AUX_GRID); cfg.blockDim = dim3(384); cfg.dynamicSmemBytes = A_SMEM; cfg.stream = cudaStreamPerThread;
  cudaLaunchAttribute at[1];
  at[0].id = cudaLaunchAttributeProgrammaticStreamSerialization;
  at[0].val.programmaticStreamSerializationAllowed = 1;
  cfg.attrs = at;
  cfg.numAttrs = 1;
  cudaLaunchKernelEx(&cfg, aux_kernel, am, x, gate_w);
}
```

```cpp
#include <cuda_runtime.h>
#include <cuda_bf16.h>
#include <cuda.h>
#include <stdint.h>
#include <type_traits>

typedef __nv_bfloat16 bf16;

namespace {

constexpr int S_TOK = 2048, DM = 640, NH = 32, DH = 192, HD = NH * DH, SEG = 32, NSEG = 64, MT = 8, LK = 40;
constexpr int SPIN_MAX = 1 << 20;

__device__ __align__(4096) unsigned char g_red[(2 << 20) + (640 << 10)];
__host__ __device__ constexpr uint32_t rb_q(int q) { return (q < 5 ? q : q - 5) * 131072 + (uint32_t)((0x3122120330ull >> 4 * q) & 15) * 2048; }
__host__ __device__ constexpr uint32_t rb_j(int j) { return (j & 1) * 256 + (j & 2) * 512 + (j & 12) * 2048; }
__host__ __device__ constexpr uint32_t rb_b(int b) { return (b & 1) * 128 + (b & 2) * 256; }
__device__ unsigned long long g_rec[96];
__device__ uint32_t g_epoch;
__device__ uint32_t g_err;
__device__ __align__(16) uint32_t g_segcnt[NSEG];
__device__ __align__(1024) bf16 g_K[NSEG * LK * HD];
__device__ __align__(1024) bf16 g_V[NSEG * LK * HD];
__device__ __align__(1024) bf16 g_O[S_TOK * HD];
__device__ __align__(1024) bf16 g_qkv[S_TOK * 3 * DM];
__device__ __align__(1024) bf16 g_Ob[S_TOK * DM];
__device__ float g_gate[2 * S_TOK];
__device__ uint32_t g_cnt[512 * 8];
__device__ __align__(128) uint32_t g_queue[3 * 32];
__device__ uint32_t g_prog;
#define GTR(i) do {} while (0)
#define GTA(i) do {} while (0)

__device__ __forceinline__ uint32_t smem_u32(const void* p) { return (uint32_t)__cvta_generic_to_shared(p); }
__device__ __forceinline__ uint32_t clk32() { uint32_t t; asm volatile("mov.u32 %0, %%clock;" : "=r"(t)::"memory"); return t; }
__device__ __forceinline__ uint32_t mapa(uint32_t a, uint32_t r) { uint32_t o; asm("mapa.shared::cluster.u32 %0, %1, %2;" : "=r"(o) : "r"(a), "r"(r)); return o; }
__device__ __forceinline__ void mbar_init(uint32_t b, uint32_t c) { asm volatile("mbarrier.init.shared::cta.b64 [%0], %1;" ::"r"(b), "r"(c) : "memory"); }
__device__ __forceinline__ void mbar_expect(uint32_t b, uint32_t bytes) { asm volatile("mbarrier.arrive.expect_tx.shared::cta.b64 _, [%0], %1;" ::"r"(b), "r"(bytes) : "memory"); }
__device__ __forceinline__ void mbar_arrive(uint32_t b) { asm volatile("mbarrier.arrive.shared::cta.b64 _, [%0];" ::"r"(b) : "memory"); }
__device__ __forceinline__ bool mbar_try(uint32_t b, uint32_t par) {
  uint32_t p;
  asm volatile("{.reg .pred p; mbarrier.try_wait.parity.shared::cta.b64 p, [%1], %2; selp.u32 %0,1,0,p;}" : "=r"(p) : "r"(b), "r"(par) : "memory");
  return p;
}
__device__ __forceinline__ bool mbar_test(uint32_t b, uint32_t par) {
  uint32_t p;
  asm volatile("{.reg .pred p; mbarrier.test_wait.parity.shared::cta.b64 p, [%1], %2; selp.u32 %0,1,0,p;}" : "=r"(p) : "r"(b), "r"(par) : "memory");
  return p;
}
__device__ __forceinline__ bool mbar_try_cl(uint32_t b, uint32_t par) {
  uint32_t p;
  asm volatile("{.reg .pred p; mbarrier.try_wait.parity.acquire.cluster.shared::cta.b64 p, [%1], %2; selp.u32 %0,1,0,p;}" : "=r"(p) : "r"(b), "r"(par) : "memory");
  return p;
}
__device__ __forceinline__ void mbar_wait(uint32_t b, uint32_t par) {
  int n = 0;
#pragma unroll 1
  while (!mbar_try(b, par)) { if (++n > SPIN_MAX) { g_err = 1; break; } }
}
__device__ __forceinline__ void mbar_wait_cl(uint32_t b, uint32_t par) {
  int n = 0;
#pragma unroll 1
  while (!mbar_try_cl(b, par)) { if (++n > SPIN_MAX) { g_err = 2; break; } }
}
__device__ __forceinline__ void cluster_sync() { asm volatile("barrier.cluster.arrive.release.aligned; barrier.cluster.wait.acquire.aligned;" ::: "memory"); }
__device__ __forceinline__ void bar_sync(int id, int n) { asm volatile("bar.sync %0, %1;" ::"r"(id), "r"(n) : "memory"); }
__device__ __forceinline__ void bar_arrive(int id, int n) { asm volatile("bar.arrive %0, %1;" ::"r"(id), "r"(n) : "memory"); }
__device__ __forceinline__ void fence_async_smem() { asm volatile("fence.proxy.async.shared::cta;" ::: "memory"); }
__device__ __forceinline__ void ldsm4(uint32_t* r, uint32_t a) {
  asm volatile("ldmatrix.sync.aligned.m8n8.x4.shared.b16 {%0,%1,%2,%3}, [%4];" : "=r"(r[0]), "=r"(r[1]), "=r"(r[2]), "=r"(r[3]) : "r"(a) : "memory");
}
__device__ __forceinline__ void ldsm4t(uint32_t* r, uint32_t a) {
  asm volatile("ldmatrix.sync.aligned.m8n8.x4.trans.shared.b16 {%0,%1,%2,%3}, [%4];" : "=r"(r[0]), "=r"(r[1]), "=r"(r[2]), "=r"(r[3]) : "r"(a) : "memory");
}
__device__ __forceinline__ void ldsm2t(uint32_t* r, uint32_t a) {
  asm volatile("ldmatrix.sync.aligned.m8n8.x2.trans.shared.b16 {%0,%1}, [%2];" : "=r"(r[0]), "=r"(r[1]) : "r"(a) : "memory");
}
__device__ __forceinline__ void stsm4t(uint32_t a, uint32_t r0, uint32_t r1, uint32_t r2, uint32_t r3) {
  asm volatile("stmatrix.sync.aligned.m8n8.x4.trans.shared.b16 [%0], {%1,%2,%3,%4};" ::"r"(a), "r"(r0), "r"(r1), "r"(r2), "r"(r3) : "memory");
}
__device__ __forceinline__ void stsm2t(uint32_t a, uint32_t r0, uint32_t r1) {
  asm volatile("stmatrix.sync.aligned.m8n8.x2.trans.shared.b16 [%0], {%1,%2};" ::"r"(a), "r"(r0), "r"(r1) : "memory");
}
__device__ __forceinline__ uint32_t movmat(uint32_t a) { uint32_t d; asm volatile("movmatrix.sync.aligned.m8n8.trans.b16 %0, %1;" : "=r"(d) : "r"(a)); return d; }
__device__ __forceinline__ void mma16816(float* d, const uint32_t* a, uint32_t b0, uint32_t b1) {
  asm volatile("mma.sync.aligned.m16n8k16.row.col.f32.bf16.bf16.f32 {%0,%1,%2,%3}, {%4,%5,%6,%7}, {%8,%9}, {%0,%1,%2,%3};"
               : "+f"(d[0]), "+f"(d[1]), "+f"(d[2]), "+f"(d[3]) : "r"(a[0]), "r"(a[1]), "r"(a[2]), "r"(a[3]), "r"(b0), "r"(b1));
}
__device__ __forceinline__ void mma1688(float* d, uint32_t a0, uint32_t a1, uint32_t b0) {
  asm volatile("mma.sync.aligned.m16n8k8.row.col.f32.bf16.bf16.f32 {%0,%1,%2,%3}, {%4,%5}, {%6}, {%0,%1,%2,%3};"
               : "+f"(d[0]), "+f"(d[1]), "+f"(d[2]), "+f"(d[3]) : "r"(a0), "r"(a1), "r"(b0));
}
__device__ __forceinline__ uint32_t pack2(float lo, float hi) { uint32_t r; asm("cvt.rn.bf16x2.f32 %0, %1, %2;" : "=r"(r) : "f"(hi), "f"(lo)); return r; }
__device__ __forceinline__ float bf_lo(uint32_t w) { return __uint_as_float(w << 16); }
__device__ __forceinline__ float bf_hi(uint32_t w) { return __uint_as_float(w & 0xffff0000u); }
__device__ __forceinline__ float ex2(float x) { float y; asm("ex2.approx.ftz.f32 %0, %1;" : "=f"(y) : "f"(x)); return y; }
__device__ __forceinline__ void sts128(uint32_t a, uint32_t x, uint32_t y, uint32_t z, uint32_t w) { asm volatile("st.shared.v4.b32 [%0], {%1,%2,%3,%4};" ::"r"(a), "r"(x), "r"(y), "r"(z), "r"(w) : "memory"); }
__device__ __forceinline__ void sts128f(uint32_t a, float x, float y, float z, float w) { asm volatile("st.shared.v4.f32 [%0], {%1,%2,%3,%4};" ::"r"(a), "f"(x), "f"(y), "f"(z), "f"(w) : "memory"); }
__device__ __forceinline__ void sts64f(uint32_t a, float x, float y) { asm volatile("st.shared.v2.f32 [%0], {%1,%2};" ::"r"(a), "f"(x), "f"(y) : "memory"); }
__device__ __forceinline__ void sts32(uint32_t a, uint32_t x) { asm volatile("st.shared.b32 [%0], %1;" ::"r"(a), "r"(x) : "memory"); }
__device__ __forceinline__ void smax32(uint32_t a, uint32_t x) { asm volatile("red.shared.max.u32 [%0], %1;" ::"r"(a), "r"(x) : "memory"); }
__device__ __forceinline__ uint32_t lds32(uint32_t a) { uint32_t v; asm volatile("ld.shared.b32 %0, [%1];" : "=r"(v) : "r"(a) : "memory"); return v; }
__device__ __forceinline__ float4 lds128f(uint32_t a) { float4 v; asm volatile("ld.shared.v4.f32 {%0,%1,%2,%3}, [%4];" : "=f"(v.x), "=f"(v.y), "=f"(v.z), "=f"(v.w) : "r"(a) : "memory"); return v; }
__device__ __forceinline__ uint4 lds128(uint32_t a) { uint4 v; asm volatile("ld.shared.v4.b32 {%0,%1,%2,%3}, [%4];" : "=r"(v.x), "=r"(v.y), "=r"(v.z), "=r"(v.w) : "r"(a) : "memory"); return v; }
__device__ __forceinline__ float2 lds64f(uint32_t a) { float2 v; asm volatile("ld.shared.v2.f32 {%0,%1}, [%2];" : "=f"(v.x), "=f"(v.y) : "r"(a) : "memory"); return v; }
__device__ __forceinline__ void st_async2(uint32_t a, uint32_t x, uint32_t y, uint32_t bar) {
  asm volatile("st.async.weak.shared::cluster.mbarrier::complete_tx::bytes.v2.b32 [%0], {%1,%2}, [%3];" ::"r"(a), "r"(x), "r"(y), "r"(bar) : "memory");
}
__device__ __forceinline__ void st_async4(uint32_t a, uint32_t x, uint32_t y, uint32_t z, uint32_t w, uint32_t bar) {
  asm volatile("st.async.weak.shared::cluster.mbarrier::complete_tx::bytes.v4.b32 [%0], {%1,%2,%3,%4}, [%5];" ::"r"(a), "r"(x), "r"(y), "r"(z), "r"(w), "r"(bar) : "memory");
}
__device__ __forceinline__ void sts64(uint32_t a, uint32_t x, uint32_t y) { asm volatile("st.shared.v2.b32 [%0], {%1,%2};" ::"r"(a), "r"(x), "r"(y) : "memory"); }
__device__ __forceinline__ bool bar_red_or(int id, int n, bool q) {
  uint32_t r;
  asm volatile("{.reg .pred p, q; setp.ne.u32 q, %3, 0; barrier.cta.red.or.aligned.pred p, %1, %2, q; selp.u32 %0,1,0,p;}" : "=r"(r) : "r"(id), "r"(n), "r"((uint32_t)q) : "memory");
  return r;
}
__device__ __forceinline__ float rcp(float x) { float y; asm("rcp.approx.ftz.f32 %0, %1;" : "=f"(y) : "f"(x)); return y; }
__device__ __forceinline__ uint32_t hadd2(uint32_t a, uint32_t b) { uint32_t r; asm("add.rn.bf16x2 %0, %1, %2;" : "=r"(r) : "r"(a), "r"(b)); return r; }
__device__ __forceinline__ uint32_t pin(uint32_t v) { asm volatile("" : "+r"(v)); return v; }
template <int ID> __device__ __forceinline__ void sched_fence_(uint32_t a) {
  asm volatile("{.reg .pred p;\nsetp.eq.u32 p, %0, %1;\nSF: @p pmevent 0;\n@p bra.uni SF;}" ::"r"(a), "n"(0x40000000 + ID) : "memory");
}
#define sched_fence(a) sched_fence_<__LINE__>(a)
__device__ __forceinline__ bool elect() {
  uint32_t p;
  asm volatile("{.reg .pred p; elect.sync _|p, 0xffffffff; selp.u32 %0,1,0,p;}" : "=r"(p));
  return p;
}
__device__ __forceinline__ uint32_t opaque(uint32_t v) { return __shfl_sync(~0u, v, threadIdx.x & 31); }
__device__ __forceinline__ uint4 ldg_rlx128(const void* p) {
  uint4 v; asm volatile("ld.relaxed.gpu.global.v4.b32 {%0,%1,%2,%3}, [%4];" : "=r"(v.x), "=r"(v.y), "=r"(v.z), "=r"(v.w) : "l"(p) : "memory"); return v;
}
__device__ __forceinline__ uint2 ldg_rlx64(const void* p) {
  uint2 v; asm volatile("{.reg .b64 t; ld.relaxed.gpu.global.b64 t, [%2]; mov.b64 {%0,%1}, t;}" : "=r"(v.x), "=r"(v.y) : "l"(p) : "memory"); return v;
}
__device__ __forceinline__ uint32_t hmaxabs2(uint32_t a, uint32_t b) { uint32_t r; asm("max.xorsign.abs.bf16x2 %0, %1, %2;" : "=r"(r) : "r"(a), "r"(b)); return r; }
__device__ __forceinline__ uint32_t ldg_rlx32(const void* p) {
  uint32_t v; asm volatile("ld.relaxed.gpu.global.b32 %0, [%1];" : "=r"(v) : "l"(p) : "memory"); return v;
}
__device__ __forceinline__ void spin_until(uint32_t t0, int d) {
#pragma unroll 1
  while ((int)(clk32() - t0) < d) {}
}
__device__ __forceinline__ void stg_rlx64(void* p, uint32_t a, uint32_t b) {
  asm volatile("{.reg .b64 t; mov.b64 t, {%1,%2}; st.relaxed.gpu.global.b64 [%0], t;}" ::"l"(p), "r"(a), "r"(b) : "memory");
}
__device__ __forceinline__ uint32_t ldg_acq32(const void* p) { uint32_t v; asm volatile("ld.acquire.gpu.global.b32 %0, [%1];" : "=r"(v) : "l"(p) : "memory"); return v; }
__device__ __forceinline__ void stg_rel32(void* p, uint32_t v) { asm volatile("st.release.gpu.global.b32 [%0], %1;" ::"l"(p), "r"(v) : "memory"); }
__device__ __forceinline__ void cp_async16(uint32_t dst, const void* src) { asm volatile("cp.async.cg.shared.global [%0], [%1], 16;" ::"r"(dst), "l"(src) : "memory"); }
__device__ __forceinline__ void cp_async_wait_all() { asm volatile("cp.async.wait_all;" ::: "memory"); }
__device__ __forceinline__ void prefetch_l2(const void* p) { asm volatile("prefetch.global.L2 [%0];" ::"l"(p)); }
__device__ __forceinline__ void tma_load3(uint32_t dst, const CUtensorMap* tm, int c0, int c1, int c2, uint32_t bar) {
  asm volatile("cp.async.bulk.tensor.3d.shared::cluster.global.mbarrier::complete_tx::bytes [%0], [%1, {%3,%4,%5}], [%2];"
               ::"r"(dst), "l"(tm), "r"(bar), "r"(c0), "r"(c1), "r"(c2) : "memory");
}
__device__ __forceinline__ void tma_load2(uint32_t dst, const CUtensorMap* tm, int c0, int c1, uint32_t bar) {
  asm volatile("cp.async.bulk.tensor.2d.shared::cluster.global.mbarrier::complete_tx::bytes [%0], [%1, {%3,%4}], [%2];"
               ::"r"(dst), "l"(tm), "r"(bar), "r"(c0), "r"(c1) : "memory");
}
__device__ __forceinline__ void bulk_load(uint32_t dst, const void* src, uint32_t bytes, uint32_t bar) {
  asm volatile("cp.async.bulk.shared::cluster.global.mbarrier::complete_tx::bytes [%0], [%1], %2, [%3];" ::"r"(dst), "l"(src), "r"(bytes), "r"(bar) : "memory");
}
__device__ __forceinline__ void bulk_s2s(uint32_t dst, uint32_t src, uint32_t bytes, uint32_t bar) {
  asm volatile("cp.async.bulk.shared::cluster.shared::cta.mbarrier::complete_tx::bytes [%0], [%1], %2, [%3];" ::"r"(dst), "r"(src), "r"(bytes), "r"(bar) : "memory");
}
__device__ __forceinline__ void prefetch_map(const CUtensorMap* tm) { asm volatile("prefetch.tensormap [%0];" ::"l"(tm) : "memory"); }
__device__ __forceinline__ void tma_store2(const CUtensorMap* tm, uint32_t src, int c0, int c1) {
  asm volatile("cp.async.bulk.tensor.2d.global.shared::cta.bulk_group [%0, {%2,%3}], [%1];" ::"l"(tm), "r"(src), "r"(c0), "r"(c1) : "memory");
}
__device__ __forceinline__ void bulk_commit() { asm volatile("cp.async.bulk.commit_group;" ::: "memory"); }
__device__ __forceinline__ void bulk_wait0() { asm volatile("cp.async.bulk.wait_group 0;" ::: "memory"); }
__device__ __forceinline__ void bulk_wait_read0() { asm volatile("cp.async.bulk.wait_group.read 0;" ::: "memory"); }
__device__ __forceinline__ void wg_fence() { asm volatile("wgmma.fence.sync.aligned;" ::: "memory"); }
__device__ __forceinline__ void wg_commit() { asm volatile("wgmma.commit_group.sync.aligned;" ::: "memory"); }
__device__ __forceinline__ void wg_wait0() { asm volatile("wgmma.wait_group.sync.aligned 0;" ::: "memory"); }
__device__ __forceinline__ uint64_t desc_sw128(uint32_t addr) {
  return (uint64_t)((addr & 0x3FFFF) >> 4) | ((uint64_t)1 << 16) | ((uint64_t)64 << 32) | ((uint64_t)1 << 62);
}
template <int ACC>
__device__ __forceinline__ void wgmma_rs32(float* d, const uint32_t* a, uint64_t db) {
  asm volatile("{.reg .pred p; setp.ne.b32 p, %21, 0;\n"
               "wgmma.mma_async.sync.aligned.m64n32k16.f32.bf16.bf16 {%0,%1,%2,%3,%4,%5,%6,%7,%8,%9,%10,%11,%12,%13,%14,%15}, {%16,%17,%18,%19}, %20, p, 1, 1, 0;}"
               : "+f"(d[0]), "+f"(d[1]), "+f"(d[2]), "+f"(d[3]), "+f"(d[4]), "+f"(d[5]), "+f"(d[6]), "+f"(d[7]), "+f"(d[8]), "+f"(d[9]),
                 "+f"(d[10]), "+f"(d[11]), "+f"(d[12]), "+f"(d[13]), "+f"(d[14]), "+f"(d[15])
               : "r"(a[0]), "r"(a[1]), "r"(a[2]), "r"(a[3]), "l"(db), "n"(ACC));
}

template <int N> __device__ __forceinline__ void fence_regs(float* d) {
#pragma unroll
  for (int i = 0; i < N; i++) asm volatile("" : "+f"(d[i])::"memory");
}
__device__ __forceinline__ void wg_wait1() { asm volatile("wgmma.wait_group.sync.aligned 1;" ::: "memory"); }
__device__ __forceinline__ void tma_store3(const CUtensorMap* tm, uint32_t src, int c0, int c1, int c2) {
  asm volatile("cp.async.bulk.tensor.3d.global.shared::cta.bulk_group [%0, {%2,%3,%4}], [%1];" ::"l"(tm), "r"(src), "r"(c0), "r"(c1), "r"(c2) : "memory");
}
__device__ __forceinline__ void tma_red3(const CUtensorMap* tm, uint32_t src, int c0, int c1, int c2) {
  asm volatile("cp.reduce.async.bulk.tensor.3d.global.shared::cta.add.bulk_group [%0, {%2,%3,%4}], [%1];" ::"l"(tm), "r"(src), "r"(c0), "r"(c1), "r"(c2) : "memory");
}
__device__ __forceinline__ void stsm4(uint32_t a, uint32_t r0, uint32_t r1, uint32_t r2, uint32_t r3) {
  asm volatile("stmatrix.sync.aligned.m8n8.x4.shared.b16 [%0], {%1,%2,%3,%4};" ::"r"(a), "r"(r0), "r"(r1), "r"(r2), "r"(r3) : "memory");
}
__device__ __forceinline__ uint2 lds64(uint32_t a) { uint2 v; asm volatile("ld.shared.v2.b32 {%0,%1}, [%2];" : "=r"(v.x), "=r"(v.y) : "r"(a) : "memory"); return v; }
__device__ __forceinline__ uint32_t hmul2(uint32_t a, uint32_t b) { uint32_t r; asm("mul.rn.bf16x2 %0, %1, %2;" : "=r"(r) : "r"(a), "r"(b)); return r; }
__device__ __forceinline__ void wgmma_ss192t(float* d, uint64_t da, uint64_t db, int acc) {
  asm volatile("{.reg .pred p; setp.ne.b32 p, %98, 0;\n"
    "wgmma.mma_async.sync.aligned.m64n192k16.f32.bf16.bf16 "
    "{%0,%1,%2,%3,%4,%5,%6,%7,%8,%9,%10,%11,%12,%13,%14,%15,%16,%17,%18,%19,%20,%21,%22,%23,%24,%25,%26,%27,%28,%29,%30,%31,%32,%33,%34,%35,%36,%37,%38,%39,%40,%41,%42,%43,%44,%45,%46,%47,%48,%49,%50,%51,%52,%53,%54,%55,%56,%57,%58,%59,%60,%61,%62,%63,%64,%65,%66,%67,%68,%69,%70,%71,%72,%73,%74,%75,%76,%77,%78,%79,%80,%81,%82,%83,%84,%85,%86,%87,%88,%89,%90,%91,%92,%93,%94,%95}, %96, %97, p, 1, 1, 0, 1;}"
    : "+f"(d[0]), "+f"(d[1]), "+f"(d[2]), "+f"(d[3]), "+f"(d[4]), "+f"(d[5]), "+f"(d[6]), "+f"(d[7]), "+f"(d[8]), "+f"(d[9]), "+f"(d[10]), "+f"(d[11]),
      "+f"(d[12]), "+f"(d[13]), "+f"(d[14]), "+f"(d[15]), "+f"(d[16]), "+f"(d[17]), "+f"(d[18]), "+f"(d[19]), "+f"(d[20]), "+f"(d[21]), "+f"(d[22]),
      "+f"(d[23]), "+f"(d[24]), "+f"(d[25]), "+f"(d[26]), "+f"(d[27]), "+f"(d[28]), "+f"(d[29]), "+f"(d[30]), "+f"(d[31]), "+f"(d[32]), "+f"(d[33]),
      "+f"(d[34]), "+f"(d[35]), "+f"(d[36]), "+f"(d[37]), "+f"(d[38]), "+f"(d[39]), "+f"(d[40]), "+f"(d[41]), "+f"(d[42]), "+f"(d[43]), "+f"(d[44]),
      "+f"(d[45]), "+f"(d[46]), "+f"(d[47]), "+f"(d[48]), "+f"(d[49]), "+f"(d[50]), "+f"(d[51]), "+f"(d[52]), "+f"(d[53]), "+f"(d[54]), "+f"(d[55]),
      "+f"(d[56]), "+f"(d[57]), "+f"(d[58]), "+f"(d[59]), "+f"(d[60]), "+f"(d[61]), "+f"(d[62]), "+f"(d[63]), "+f"(d[64]), "+f"(d[65]), "+f"(d[66]),
      "+f"(d[67]), "+f"(d[68]), "+f"(d[69]), "+f"(d[70]), "+f"(d[71]), "+f"(d[72]), "+f"(d[73]), "+f"(d[74]), "+f"(d[75]), "+f"(d[76]), "+f"(d[77]),
      "+f"(d[78]), "+f"(d[79]), "+f"(d[80]), "+f"(d[81]), "+f"(d[82]), "+f"(d[83]), "+f"(d[84]), "+f"(d[85]), "+f"(d[86]), "+f"(d[87]), "+f"(d[88]),
      "+f"(d[89]), "+f"(d[90]), "+f"(d[91]), "+f"(d[92]), "+f"(d[93]), "+f"(d[94]), "+f"(d[95])
    : "l"(da), "l"(db), "r"(acc));
}
__device__ __forceinline__ void wgmma_rs128t(float* d, const uint32_t* a, uint64_t db, int acc) {
  asm volatile("{.reg .pred p; setp.ne.b32 p, %69, 0;\n"
    "wgmma.mma_async.sync.aligned.m64n128k16.f32.bf16.bf16 "
    "{%0,%1,%2,%3,%4,%5,%6,%7,%8,%9,%10,%11,%12,%13,%14,%15,%16,%17,%18,%19,%20,%21,%22,%23,%24,%25,%26,%27,%28,%29,%30,%31,%32,%33,%34,%35,%36,%37,%38,%39,%40,%41,%42,%43,%44,%45,%46,%47,%48,%49,%50,%51,%52,%53,%54,%55,%56,%57,%58,%59,%60,%61,%62,%63}, {%64,%65,%66,%67}, %68, p, 1, 1, 1;}"
    : "+f"(d[0]), "+f"(d[1]), "+f"(d[2]), "+f"(d[3]), "+f"(d[4]), "+f"(d[5]), "+f"(d[6]), "+f"(d[7]), "+f"(d[8]), "+f"(d[9]), "+f"(d[10]), "+f"(d[11]),
      "+f"(d[12]), "+f"(d[13]), "+f"(d[14]), "+f"(d[15]), "+f"(d[16]), "+f"(d[17]), "+f"(d[18]), "+f"(d[19]), "+f"(d[20]), "+f"(d[21]), "+f"(d[22]),
      "+f"(d[23]), "+f"(d[24]), "+f"(d[25]), "+f"(d[26]), "+f"(d[27]), "+f"(d[28]), "+f"(d[29]), "+f"(d[30]), "+f"(d[31]), "+f"(d[32]), "+f"(d[33]),
      "+f"(d[34]), "+f"(d[35]), "+f"(d[36]), "+f"(d[37]), "+f"(d[38]), "+f"(d[39]), "+f"(d[40]), "+f"(d[41]), "+f"(d[42]), "+f"(d[43]), "+f"(d[44]),
      "+f"(d[45]), "+f"(d[46]), "+f"(d[47]), "+f"(d[48]), "+f"(d[49]), "+f"(d[50]), "+f"(d[51]), "+f"(d[52]), "+f"(d[53]), "+f"(d[54]), "+f"(d[55]),
      "+f"(d[56]), "+f"(d[57]), "+f"(d[58]), "+f"(d[59]), "+f"(d[60]), "+f"(d[61]), "+f"(d[62]), "+f"(d[63])
    : "r"(a[0]), "r"(a[1]), "r"(a[2]), "r"(a[3]), "l"(db), "r"(acc));
}
__device__ __forceinline__ void wgmma_rs80(float* d, const uint32_t* a, uint64_t db, int acc) {
  asm volatile("{.reg .pred p; setp.ne.b32 p, %45, 0;\n"
    "wgmma.mma_async.sync.aligned.m64n80k16.f32.bf16.bf16 "
    "{%0,%1,%2,%3,%4,%5,%6,%7,%8,%9,%10,%11,%12,%13,%14,%15,%16,%17,%18,%19,%20,%21,%22,%23,%24,%25,%26,%27,%28,%29,%30,%31,%32,%33,%34,%35,%36,%37,%38,%39}, {%40,%41,%42,%43}, %44, p, 1, 1, 0;}"
    : "+f"(d[0]), "+f"(d[1]), "+f"(d[2]), "+f"(d[3]), "+f"(d[4]), "+f"(d[5]), "+f"(d[6]), "+f"(d[7]), "+f"(d[8]), "+f"(d[9]), "+f"(d[10]), "+f"(d[11]),
      "+f"(d[12]), "+f"(d[13]), "+f"(d[14]), "+f"(d[15]), "+f"(d[16]), "+f"(d[17]), "+f"(d[18]), "+f"(d[19]), "+f"(d[20]), "+f"(d[21]), "+f"(d[22]),
      "+f"(d[23]), "+f"(d[24]), "+f"(d[25]), "+f"(d[26]), "+f"(d[27]), "+f"(d[28]), "+f"(d[29]), "+f"(d[30]), "+f"(d[31]), "+f"(d[32]), "+f"(d[33]),
      "+f"(d[34]), "+f"(d[35]), "+f"(d[36]), "+f"(d[37]), "+f"(d[38]), "+f"(d[39])
    : "r"(a[0]), "r"(a[1]), "r"(a[2]), "r"(a[3]), "l"(db), "r"(acc));
}
__device__ __forceinline__ void wgmma_rs192t(float* d, const uint32_t* a, uint64_t db, int acc) {
  asm volatile("{.reg .pred p; setp.ne.b32 p, %101, 0;\n"
    "wgmma.mma_async.sync.aligned.m64n192k16.f32.bf16.bf16 "
    "{%0,%1,%2,%3,%4,%5,%6,%7,%8,%9,%10,%11,%12,%13,%14,%15,%16,%17,%18,%19,%20,%21,%22,%23,%24,%25,%26,%27,%28,%29,%30,%31,%32,%33,%34,%35,%36,%37,%38,%39,%40,%41,%42,%43,%44,%45,%46,%47,%48,%49,%50,%51,%52,%53,%54,%55,%56,%57,%58,%59,%60,%61,%62,%63,%64,%65,%66,%67,%68,%69,%70,%71,%72,%73,%74,%75,%76,%77,%78,%79,%80,%81,%82,%83,%84,%85,%86,%87,%88,%89,%90,%91,%92,%93,%94,%95}, {%96,%97,%98,%99}, %100, p, 1, 1, 1;}"
    : "+f"(d[0]), "+f"(d[1]), "+f"(d[2]), "+f"(d[3]), "+f"(d[4]), "+f"(d[5]), "+f"(d[6]), "+f"(d[7]), "+f"(d[8]), "+f"(d[9]), "+f"(d[10]), "+f"(d[11]),
      "+f"(d[12]), "+f"(d[13]), "+f"(d[14]), "+f"(d[15]), "+f"(d[16]), "+f"(d[17]), "+f"(d[18]), "+f"(d[19]), "+f"(d[20]), "+f"(d[21]), "+f"(d[22]),
      "+f"(d[23]), "+f"(d[24]), "+f"(d[25]), "+f"(d[26]), "+f"(d[27]), "+f"(d[28]), "+f"(d[29]), "+f"(d[30]), "+f"(d[31]), "+f"(d[32]), "+f"(d[33]),
      "+f"(d[34]), "+f"(d[35]), "+f"(d[36]), "+f"(d[37]), "+f"(d[38]), "+f"(d[39]), "+f"(d[40]), "+f"(d[41]), "+f"(d[42]), "+f"(d[43]), "+f"(d[44]),
      "+f"(d[45]), "+f"(d[46]), "+f"(d[47]), "+f"(d[48]), "+f"(d[49]), "+f"(d[50]), "+f"(d[51]), "+f"(d[52]), "+f"(d[53]), "+f"(d[54]), "+f"(d[55]),
      "+f"(d[56]), "+f"(d[57]), "+f"(d[58]), "+f"(d[59]), "+f"(d[60]), "+f"(d[61]), "+f"(d[62]), "+f"(d[63]), "+f"(d[64]), "+f"(d[65]), "+f"(d[66]),
      "+f"(d[67]), "+f"(d[68]), "+f"(d[69]), "+f"(d[70]), "+f"(d[71]), "+f"(d[72]), "+f"(d[73]), "+f"(d[74]), "+f"(d[75]), "+f"(d[76]), "+f"(d[77]),
      "+f"(d[78]), "+f"(d[79]), "+f"(d[80]), "+f"(d[81]), "+f"(d[82]), "+f"(d[83]), "+f"(d[84]), "+f"(d[85]), "+f"(d[86]), "+f"(d[87]), "+f"(d[88]),
      "+f"(d[89]), "+f"(d[90]), "+f"(d[91]), "+f"(d[92]), "+f"(d[93]), "+f"(d[94]), "+f"(d[95])
    : "r"(a[0]), "r"(a[1]), "r"(a[2]), "r"(a[3]), "l"(db), "r"(acc));
}

constexpr int NPQ = 2;
#define NQ 12
#define NQ_WIN 8
#define NO_EARLY 6
#define NO_MID 9
#define NW1 16
#define NW1A 10
#define VLD 6
#define VB 0
#define XPF 3
#define WSPLIT 8
#define PEARLY 0
#define NQ_W1 8
#define B5LATE 0
#define WD 650
#define DFENCE 0
#define PDS 300
#define PDT 50
#define LDEP 2
#define LDT 6000
#define VBULK 1
#define VBW 3
#define PD 780
constexpr int R_WQ = 0;
constexpr int R_WO = R_WQ + 8 * (20 - NPQ) * 512;
constexpr int R_XT = R_WO + 14 * 12 * 512;
constexpr int R_MEM = R_XT;
constexpr int R_QB = R_XT + 40960;
constexpr int R_QA = R_QB + 1024;
constexpr int R_O2 = R_QA + 1024;
constexpr int R_VS = R_O2 + 1024;
constexpr int R_KT = R_VS + 1024;
constexpr int R_VT = R_KT + 5120;
constexpr int R_V1 = R_VT + 5120;
constexpr int R_SX = R_V1 + 8192;
constexpr int R_VM = R_SX + 4608;
constexpr int R_BAR = R_VM + 2048;
constexpr int R_MI = R_BAR + 64;
constexpr int R_SMEM = R_MI + 64;
static_assert(NPQ == 2 && R_XT % 1024 == 0 && R_KT % 1024 == 0 && R_VT % 1024 == 0 && R_V1 % 1024 == 0 && R_WO % 1024 == 0, "align");
constexpr int R_SMEM_ALLOC = R_SMEM;
static_assert(R_SMEM_ALLOC <= 232448, "smem");

#define TR(i) do {} while (0)

__device__ __forceinline__ void red_pair(unsigned char* p, float lo, float hi) {
  const int b = __float2int_rn(lo), a = __float2int_rn(hi);
  asm volatile("{.reg .b64 t; mov.b64 t, {%1,%2}; red.relaxed.gpu.global.add.u64 [%0], t;}" ::"l"(p), "r"(b + ((1 << 29) + (1 << 23))), "r"(a * 8) : "memory");
}
__device__ __forceinline__ unsigned long long swap0(unsigned char* p) {
  unsigned long long r;
  asm volatile("atom.relaxed.gpu.global.exch.b64 %0, [%1], 0;" : "=l"(r) : "l"(p) : "memory");
  return r;
}
__device__ __forceinline__ uint32_t dec_pair(uint32_t lo, uint32_t hi, uint32_t bias) { return pack2((float)(int)(lo * 8u + bias), (float)(int)hi); }

__global__ void __cluster_dims__(3, 1, 1) __launch_bounds__(256, 1)
rec_kernel(const __grid_constant__ CUtensorMap tmX, const __grid_constant__ CUtensorMap tmK, const __grid_constant__ CUtensorMap tmV,
           const __grid_constant__ CUtensorMap tmWq, const __grid_constant__ CUtensorMap tmWq2, const __grid_constant__ CUtensorMap tmWk,
           const __grid_constant__ CUtensorMap tmWv, const __grid_constant__ CUtensorMap tmWo, const bf16* __restrict__ mem0,
           const bf16* __restrict__ Wq, const bf16* __restrict__ Wo, const bf16* __restrict__ x, unsigned char* __restrict__ red) {
  extern __shared__ __align__(1024) unsigned char smem[];
  const uint32_t sb = smem_u32(smem);
  const int tid = threadIdx.x, lane = tid & 31, wid = __shfl_sync(~0u, tid >> 5, 0), g = wid >> 2, w = wid & 3;
  const int cta = blockIdx.x, head = cta / 3, rank = cta % 3;
  const int D0 = head * DH + rank * 64;
  const int tile0 = rank == 0 ? 0 : (rank == 1 ? 14 : 26);
  const uint32_t XBAR = sb + R_BAR, SBAR = XBAR + 8, OBAR = XBAR + 16, VBAR = XBAR + 24, FBAR = XBAR + 32, WBAR = XBAR + 40;
  constexpr uint32_t ONES = 0x3F803F80u;
  if (LDEP == 0) asm volatile("griddepcontrol.launch_dependents;" ::: "memory");
  GTR(0);
  if (wid == 0) {
    if (lane == 0) {
      mbar_init(XBAR, 1); mbar_init(SBAR, 4); mbar_init(OBAR, 5); mbar_init(VBAR, 1); mbar_init(FBAR, 2);
      mbar_init(WBAR, 1); mbar_init(WBAR + 8, 1); mbar_init(WBAR + 16, 1);
      asm volatile("fence.mbarrier_init.release.cluster;" ::: "memory");
      mbar_expect(WBAR, 81920); mbar_expect(WBAR + 8, 81920 + 2 * NPQ * 2048); mbar_expect(XBAR, 40960);
      mbar_expect(SBAR, 3072); mbar_expect(OBAR, 2048); mbar_expect(VBAR, 8192);
      sts128(sb + R_MI + 48, 0, 0, 0, 0);
    }
    __syncwarp();
    if (lane < 5) tma_load2(sb + lane * 16384, &tmWk, D0, lane * 128, WBAR);
    if (lane == 5) tma_load3(sb + R_XT, &tmX, 0, 0, 0, XBAR);
    if (lane < 5) tma_load2(lane < 4 ? sb + 81920 + lane * 16384 : sb + R_QB, &tmWv, D0, lane * 128, WBAR + 8);
    if (lane < 2) tma_load2(sb + R_QB + 16384 + lane * 4096, &tmWq2, D0, lane * 320, WBAR + 8);
  }
  if (tid == 32) { prefetch_map(&tmWq); prefetch_map(&tmWo); prefetch_map(&tmK); prefetch_map(&tmV); }
  if (tid >= 64 && tid < 144) prefetch_l2(mem0 + (tid - 64) * 64);
  __syncthreads();
  GTR(1);
  if (LDEP == 1) asm volatile("griddepcontrol.launch_dependents;" ::: "memory");
  if (LDEP == 4 && wid == 7) { spin_until(clk32(), LDT); asm volatile("griddepcontrol.launch_dependents;" ::: "memory"); }
#pragma unroll
  for (int i = 0; i < 5; i++) { const int l = tid + i * 256; prefetch_l2((l < 640 ? Wq : Wo - 40960) + (size_t)cta * 40960 + l * 64); }
  uint32_t ww[40][4], wqp[NPQ][4];
  {
    uint32_t xm = 0;
#pragma unroll
    for (int i = 0; i < 7; i++) {
      const int v = tid + i * 256, gv = cta * 1707 + v;
      if (v < 1707 && gv < S_TOK * DM / 8) {
        const uint4 q = __ldg((const uint4*)x + gv);
        xm = hmaxabs2(hmaxabs2(xm, hmaxabs2(q.x, q.y)), hmaxabs2(q.z, q.w));
      }
    }
    xm = __reduce_max_sync(~0u, max((xm << 16) & 0x7fffffffu, xm & 0x7fff0000u));
    const uint32_t p = sb + (lane >> 4) * 1024 + (lane & 7) * 128 + (((2 * w + ((lane >> 3) & 1)) ^ (lane & 7)) << 4);
    if (LDEP == 2) asm volatile("griddepcontrol.launch_dependents;" ::: "memory");
    mbar_wait(WBAR + 8 * g, 0);
    GTR(2);
#pragma unroll
    for (int f = 0; f < 40; f++) ldsm4t(ww[f], (f >= 32 && g == 1) ? p + R_QB + (f - 32) * 2048 : p + g * 81920 + f * 2048);
    mbar_wait(WBAR + 8, 0);
    GTR(3);
#pragma unroll
    for (int f = 0; f < NPQ; f++) ldsm4t(wqp[f], p + R_QB + 16384 + g * 4096 + f * 2048);
    __syncthreads();
    asm volatile("barrier.cluster.arrive.relaxed.aligned;" ::: "memory");
    if (wid == 0) {
      if (lane == 0) mbar_expect(WBAR + 16, 18 * 4096 + 21 * 4096);
      __syncwarp();
      if (lane < 4) tma_load2(sb + R_WQ + lane * 18432, &tmWq, D0, (lane >> 1) * 320 + 32 + (lane & 1) * 144, WBAR + 16);
      else if (lane < 7) tma_load3(sb + R_WO + ((lane - 1 - rank) % 3) * 28672, &tmWo, 0, head * DH + (lane - 4) * 64, tile0 >> 1, WBAR + 16);
      __syncwarp();
    }
    float nv[4] = {0.f, 0.f, 0.f, 0.f};
#pragma unroll
    for (int f = 0; f < 40; f++) {
      const uint32_t a[4] = {ww[f][0] & 0x7fff7fffu, ww[f][1] & 0x7fff7fffu, ww[f][2] & 0x7fff7fffu, ww[f][3] & 0x7fff7fffu};
      mma16816(nv, a, ONES, ONES);
    }
    const uint32_t mv = __reduce_max_sync(~0u, __float_as_uint(fmaxf(nv[0], nv[2])));
    if (lane == 0) { if (g == 1) smax32(sb + R_MI + 48, mv); smax32(sb + R_MI + 52, xm); }
  }
  GTR(4);
  if (LDEP == 3) asm volatile("griddepcontrol.launch_dependents;" ::: "memory");

  const uint32_t rF_ = opaque(sb + lane * 16);
  const uint32_t rP_ = opaque(sb + (lane >> 4) * 1024 + (lane & 7) * 128 + (((2 * w + ((lane >> 3) & 1)) ^ (lane & 7)) << 4));
  const int tA = g == 1 ? 2 * w : (rank != 1 ? (w < 2 ? 8 + 2 * w : 10 + w) : 8 + w);
  const bool two = g == 1 || (w < 2 && rank != 1);
  const uint32_t r1 = rank == 2 ? 0 : rank + 1, r2 = rank == 0 ? 2 : rank - 1;
  const uint32_t rW_ = opaque(sb + R_WO + (tA >> 1) * 4096 + ((lane >> 4) * 8 + (lane & 7)) * 64 +
                             (((2 * (tA & 1) + ((lane >> 3) & 1)) ^ ((lane >> 1) & 3)) << 4));
  const uint32_t toff = rb_q((tile0 + tA) >> 2) + rb_j(4 * (tile0 + tA)), zoff = rb_q((cta % 20) >> 1) + rb_j((cta % 20) * 8);
  uint32_t wqt[NQ][4];
  float u = 1.f;
  uint32_t t0 = 0;
  int s = -1;

#define WOFF(ks) (((ks) >> 2) * 28672 + ((ks) & 3) * 1024)
#define XDESC(j) (((uint64_t)0x40000040 << 32) | (dlo + ((((j) >> 2) * 4096 + ((j) & 3) * 32) >> 4)))

  auto vsend = [&]() {
    if (elect()) {
      if (VBULK != 1) fence_async_smem();
      bulk_s2s(mapa(sb + R_V1 + 4096, r1), sb + R_VT + 1024, 4096, mapa(VBAR, r1));
      bulk_s2s(mapa(sb + R_V1, r2), sb + R_VT + 1024, 4096, mapa(VBAR, r2));
    }
    __syncwarp();
  };
  auto window = [&](auto G_, auto FIRST_) {
    constexpr int G = decltype(G_)::value;
    constexpr bool FIRST = decltype(FIRST_)::value;
    const uint32_t rF = pin(rF_), rP = pin(rP_);
    float d[16];
    const uint32_t dlo = pin(((sb + R_XT) >> 4) | 0x10000);
    const uint32_t wqS = rP + R_WQ + G * (20 - NPQ) * 2048;
    uint4 y[5];
    unsigned long long zr = 0;
    const uint32_t t = w * 32 + ((rF - sb) >> 4);
    if (G == 0) zr = swap0(red + (rb_b(s + 2) + zoff + rb_j(t >> 4) + (t & 15) * 8));
    if (G == 0) {
      if (!FIRST && w == 3) {
        if (elect()) {
          mbar_expect(SBAR, 3072); mbar_expect(OBAR, 2048); mbar_expect(VBAR, 8192);
          asm volatile("mbarrier.arrive.relaxed.cluster.shared::cluster.b64 _, [%0];" ::"r"(mapa(FBAR, r1)) : "memory");
          asm volatile("mbarrier.arrive.relaxed.cluster.shared::cluster.b64 _, [%0];" ::"r"(mapa(FBAR, r2)) : "memory");
        }
        __syncwarp();
      }
    }
    const unsigned char* yp = red + (rb_b(s) + rb_j(t >> 3) + (t & 7) * 16);
    auto poll = [&]() {
      TR(10);
      spin_until(t0, PD);
#pragma unroll
      for (int q = 0; q < 5; q++) y[q] = ldg_rlx128(yp + rb_q(G * 5 + q));
      TR(9);
      sched_fence(sb);
    };
    constexpr int WS = FIRST || G == 1 ? 40 : WSPLIT;
    if (!FIRST && G == 0) {
#pragma unroll
      for (int f = 0; f < NQ_WIN; f++) ldsm4t(wqt[f], wqS + f * 2048);
      asm volatile("" : "+l"(yp));
      mbar_wait(XBAR, (s + 1) & 1);
      if (WS) spin_until(t0, WD);
    } else {
      mbar_wait(XBAR, (s + 1) & 1);
    }
    TR(11);
    if (WS == 0) { poll(); spin_until(t0, WD); }
    wg_fence();
    wgmma_rs32<0>(d, ww[0], XDESC(0));
#pragma unroll
    for (int j = 1; j < WS; j++) wgmma_rs32<1>(d, ww[j], XDESC(j));
    if (FIRST) {
      const unsigned short* m = (const unsigned short*)mem0 + (t & 1) * 4 * DM + G * 320 + (t >> 1);
#pragma unroll
      for (int q = 0; q < 5; q++) y[q] = make_uint4(m[q * 64], m[q * 64 + DM], m[q * 64 + 2 * DM], m[q * 64 + 3 * DM]);
    } else if (G == 0 && WS) {
      poll();
    }
#pragma unroll
    for (int j = WS ? WS : 1; j < 40; j++) wgmma_rs32<1>(d, ww[j], XDESC(j));
    wg_commit();
    if (!FIRST && G == 1) {
      asm volatile("" : "+l"(yp));
      if (PEARLY && (VBULK != 4 || w != VBW)) poll();
      mbar_wait(FBAR, s & 1);
#pragma unroll
      for (int f = 0; f < NQ_W1; f++) ldsm4t(wqt[f], wqS + f * 2048);
    }
    if (FIRST) asm volatile("barrier.cluster.wait.acquire.aligned;" ::: "memory");
    wg_wait0();
    fence_regs<16>(d);
    TR(13);
    bar_arrive(8 + G, 256);
    if (!FIRST && G == 1 && !PEARLY && (VBULK != 4 || w != VBW)) poll();
    {
      uint32_t pk[8];
#pragma unroll
      for (int q = 0; q < 8; q++) pk[q] = pack2(d[2 * q], d[2 * q + 1]);
      stsm4t(rP + (G == 1 ? R_VT : R_KT) + 1024, pk[0], pk[1], pk[2], pk[3]);
      stsm4t(rP + (G == 1 ? R_VT : R_KT) + 3072, pk[4], pk[5], pk[6], pk[7]);
      if (G == 1 && VBULK) {
        if (VBULK == 1) fence_async_smem();
        if (VBULK == 1 || VBULK == 4) {
          if (w != VBW) bar_arrive(6, 128);
          else {
            bar_sync(6, 128);
            vsend();
            if (VBULK == 4 && !FIRST) poll();
          }
        }
      } else if (G == 1) {
        const uint32_t e1 = mapa(rF + R_V1 + 4096 + w * 512, r1), e2 = mapa(rF + R_V1 + w * 512, r2), b1 = mapa(VBAR, r1), b2 = mapa(VBAR, r2);
        st_async4(e1, pk[0], pk[1], pk[2], pk[3], b1);
        st_async4(e2, pk[0], pk[1], pk[2], pk[3], b2);
        st_async4(e1 + 2048, pk[4], pk[5], pk[6], pk[7], b1);
        st_async4(e2 + 2048, pk[4], pk[5], pk[6], pk[7], b2);
      }
    }
    if (FIRST) {
      mbar_wait(WBAR + 16, 0);
      const uint32_t woA = rW_;
      float na[4] = {0.f, 0.f, 0.f, 0.f}, nb[4] = {0.f, 0.f, 0.f, 0.f};
#pragma unroll
      for (int ks = 0; ks < 12; ks++) {
        uint32_t a[4], b[4];
        ldsm4t(a, woA + WOFF(ks));
        ldsm4t(b, (two ? woA ^ 32 : woA) + WOFF(ks));
#pragma unroll
        for (int q = 0; q < 4; q++) { a[q] &= 0x7fff7fffu; b[q] &= 0x7fff7fffu; }
        mma16816(na, a, ONES, ONES);
        mma16816(nb, b, ONES, ONES);
      }
      const uint32_t mo = __reduce_max_sync(~0u, __float_as_uint(fmaxf(fmaxf(na[0], na[2]), fmaxf(nb[0], nb[2]))));
      if (rF == sb) smax32(sb + R_MI + 56, mo);
      __syncthreads();
      if (G == 1 && w == 2) {
        const uint4 r = lds128(sb + R_MI + 48);
        const uint32_t epoch = *(volatile uint32_t*)&g_epoch + 1;
        if (rF == sb) stg_rlx64(&g_rec[cta], (r.y & 0xffff0000u) | (epoch & 0xffffu), ((r.x + 0xffffu) & 0xffff0000u) | ((r.z + 0xffffu) >> 16));
      }
    }
#pragma unroll
    for (int f = FIRST ? 0 : (G == 1 ? NQ_W1 : NQ_WIN); f < NQ; f++) ldsm4t(wqt[f], wqS + f * 2048);
    if (FIRST || DFENCE) sched_fence(sb);
    TR(14);
    const uint32_t ma = sb + R_MEM + G * 5120 + t * 8;
    if (FIRST) {
      bar_sync(9 - G, 256);
#pragma unroll
      for (int j = 0; j < 5; j++) sts64(ma + j * 1024, y[j].x | (y[j].y << 16), y[j].z | (y[j].w << 16));
    } else {
      int n = 0;
#pragma unroll 1
      while (!__all_sync(~0u, (y[0].y & y[0].w & y[1].y) & (y[1].w & y[2].y & y[2].w) & (y[3].y & y[3].w & y[4].y) & (y[4].w & 4))) {
#pragma unroll
        for (int j = 0; j < 5; j++) if (!(y[j].y & y[j].w & 4)) y[j] = ldg_rlx128(yp + rb_q(G * 5 + j));
        if (++n > SPIN_MAX) { g_err = 5; break; }
      }
      const uint32_t bias = 0x80000000u + (sb >> 31);
      bar_sync(9 - G, 256);
#pragma unroll
      for (int j = 0; j < 5; j++) sts64(ma + j * 1024, dec_pair(y[j].x, y[j].y, bias), dec_pair(y[j].z, y[j].w, bias));
    }
    if (G == 0 && zr == ~0ull) g_err = 9;
    TR(0);
  };

  auto oproj = [&](auto TWO_, auto NPRE_, auto& wot, const uint32_t rF, const uint32_t woA, const uint32_t woB,
                   float sm0, float sm1, bool have_sums) {
    constexpr bool TWO = decltype(TWO_)::value;
    constexpr int NPRE = decltype(NPRE_)::value;
    float c[4][4];
#pragma unroll
    for (int q = 0; q < 4; q++) c[q][0] = c[q][1] = c[q][2] = c[q][3] = 0.f;
    unsigned char* sp = red + (rb_b(s) + toff + ((rF - sb) & 256) + (((rF - sb) >> 1) & 120));
    bar_sync(3, 256);
    TR(8);
    uint4 ob[6];
    ob[0] = lds128(rF + R_QB); ob[1] = lds128(rF + R_QB + 512);
    const float2 su = lds64f(sb + R_MI + 48);
    if (!have_sums) { const float2 t = lds64f(sb + R_MI + 16 + (((rF - sb) >> 1) & 24)); sm0 = t.x; sm1 = t.y; }
#pragma unroll
    for (int p = 0; p < 6; p++) {
      if (p + 2 < 6) ob[p + 2] = lds128(rF + (p < 2 ? R_QA : R_O2) + (p & 1) * 512);
#pragma unroll
      for (int e = 0; e < 2; e++) {
        const int ks = 2 * p + e;
        const uint32_t b0 = e ? ob[p].z : ob[p].x, b1 = e ? ob[p].w : ob[p].y;
        if (TWO) {
          const int iA = 2 * ks, iB = iA + 1;
          mma16816(c[e], wot[iA % NPRE], b0, b1);
          if (iA + NPRE < 24) ldsm4t(wot[iA % NPRE], woA + WOFF((iA + NPRE) >> 1));
          mma16816(c[2 + e], wot[iB % NPRE], b0, b1);
          if (iB + NPRE < 24) ldsm4t(wot[iB % NPRE], woB + WOFF((iB + NPRE) >> 1));
        } else {
          mma16816(c[ks & 3], wot[ks], b0, b1);
        }
      }
    }
    const float f0 = su.x * rcp(sm0), f1 = su.x * rcp(sm1);
    t0 = clk32() + (TWO ? (have_sums ? -PDT : 0) : PDS);
    u = su.y;
    if (TWO) {
      red_pair(sp, (c[0][0] + c[1][0]) * f0, (c[0][1] + c[1][1]) * f1);
      red_pair(sp + rb_j(2), (c[0][2] + c[1][2]) * f0, (c[0][3] + c[1][3]) * f1);
      red_pair(sp + rb_j(4), (c[2][0] + c[3][0]) * f0, (c[2][1] + c[3][1]) * f1);
      red_pair(sp + rb_j(6), (c[2][2] + c[3][2]) * f0, (c[2][3] + c[3][3]) * f1);
    } else {
      red_pair(sp, ((c[0][0] + c[1][0]) + (c[2][0] + c[3][0])) * f0, ((c[0][1] + c[1][1]) + (c[2][1] + c[3][1])) * f1);
      red_pair(sp + rb_j(2), ((c[0][2] + c[1][2]) + (c[2][2] + c[3][2])) * f0, ((c[0][3] + c[1][3]) + (c[2][3] + c[3][3])) * f1);
    }
    TR(15);
  };

  auto step = [&](auto G_, auto LAST_) {
    constexpr int G = decltype(G_)::value;
    constexpr bool LAST = decltype(LAST_)::value;
    __syncthreads();
    const uint32_t rF = pin(rF_), rP = pin(rP_);
    TR(1);
    const uint32_t wqS = rP + R_WQ + G * (20 - NPQ) * 2048, rM = rF + R_MEM;
    const uint32_t l8 = sb + ((rF - sb) >> 1) + w * 256;
    const uint32_t woA = pin(rW_), woB = woA ^ 32;
    float aq[2][4] = {};
    const uint32_t ln = (rF - sb) >> 4;
    const uint32_t rS = sb + (ln & 7) * 128 + (ln < 16 ? R_QB + (ln & 8) * 128 + (((2 * w + G) ^ (ln & 7)) << 4) : R_KT + (((2 * w + ((ln >> 3) & 1)) ^ (ln & 7)) << 4));
    auto qmma = [&](int f, uint32_t b0, uint32_t b1) {
      if (f < NPQ) mma16816(aq[f & 1], wqp[f], b0, b1);
      else {
        const int slot = (f - NPQ) % NQ;
        mma16816(aq[f & 1], wqt[slot], b0, b1);
        if (f + NQ < 20) ldsm4t(wqt[slot], wqS + (f - NPQ + NQ) * 2048);
      }
    };
    if constexpr (G == 1) {
      uint32_t bb[20][4];
      if (!LAST) {
        if (VBULK == 2 && w == VBW) vsend();
        ldsm4t(bb[10], rM + 5120);
        ldsm4t(bb[11], rM + 5632);
#pragma unroll
        for (int i = 10; i < 20; i++) {
          if (i + 2 < 20) ldsm4t(bb[i + 2], rM + (i + 2) * 512);
          qmma(2 * i - 20, bb[i][0], bb[i][1]);
          qmma(2 * i - 19, bb[i][2], bb[i][3]);
        }
        stsm2t(rS, pack2(aq[0][0] + aq[1][0], aq[0][1] + aq[1][1]), pack2(aq[0][2] + aq[1][2], aq[0][3] + aq[1][3]));
        bar_arrive(1, 256);
        if (VBULK == 3 && w == VBW) vsend();
      }
      TR(2);
      float av[4][4] = {};
      uint32_t m0 = 0, m1 = 0;
      auto vmma = [&](auto MAX_) {
#pragma unroll
        for (int n = 0; n < 20; n++) {
          const int i = (n + 10) % 20;
          if (LAST && n < 8) ldsm4t(bb[(n + 10) % 20], rM + ((n + 10) % 20) * 512);
          if (LAST && n == 0) { ldsm4t(bb[18], rM + 18 * 512); ldsm4t(bb[19], rM + 19 * 512); }
          if (n == VB && !LAST) { bar_sync(5, 256); sched_fence(sb); }
          if (n == VLD) {
            if (VB != VLD && !LAST) sched_fence(sb);
#pragma unroll
            for (int q = 0; q < 10; q++) ldsm4t(bb[q], rM + q * 512);
            if (!LAST) sched_fence(sb);
          }
          mma16816(av[(2 * n) & 3], ww[2 * i], bb[i][0], bb[i][1]);
          mma16816(av[(2 * n + 1) & 3], ww[2 * i + 1], bb[i][2], bb[i][3]);
          if (decltype(MAX_)::value) { m0 = hmaxabs2(m0, hmaxabs2(bb[i][0], bb[i][1])); m1 = hmaxabs2(m1, hmaxabs2(bb[i][2], bb[i][3])); }
        }
      };
      auto vout = [&]() {
        const uint32_t vm0 = pack2(((av[0][0] + av[1][0]) + (av[2][0] + av[3][0])) * u, ((av[0][1] + av[1][1]) + (av[2][1] + av[3][1])) * u);
        const uint32_t vm1 = pack2(((av[0][2] + av[1][2]) + (av[2][2] + av[3][2])) * u, ((av[0][3] + av[1][3]) + (av[2][3] + av[3][3])) * u);
        if (!LAST) {
          st_async2(mapa(l8 + R_VM + 1024, r1), vm0, vm1, mapa(OBAR, r1));
          st_async2(mapa(l8 + R_VM, r2), vm0, vm1, mapa(OBAR, r2));
          sts64(l8 + R_VS, vm0, vm1);
          __syncwarp();
          if (rF == sb) mbar_arrive(OBAR);
        }
        stsm2t(rP + R_VT, vm0, vm1);
      };
      if (LAST) { vmma(std::false_type{}); vout(); return; }
      uint32_t wot[NW1][4];
      auto wpre = [&](int i0, int i1) {
#pragma unroll
        for (int i = i0; i < i1; i++) ldsm4t(wot[i], ((i & 1) ? woB : woA) + WOFF(i >> 1));
      };
      if (w != 1) {
        vmma(std::false_type{});
        bar_arrive(7, 128);
        vout();
        bar_arrive(2, 128);
        TR(5);
        wpre(0, NW1A);
      } else {
        vmma(std::true_type{});
        bar_sync(7, 128);
        if (elect()) { mbar_expect(XBAR, 40960); tma_load3(sb + R_XT, &tmX, 0, (s + 1) * SEG, 0, XBAR); }
        __syncwarp();
        vout();
        if (XPF && s + XPF < NSEG && rF - sb < 64 && cta < 80) prefetch_l2(x + (size_t)(s + XPF) * SEG * DM + cta * 256 + (rF - sb) * 4);
        TR(5);
        m0 = hmaxabs2(m0, m1);
        const uint32_t mx = __reduce_max_sync(~0u, max((m0 << 16) & 0x7fffffffu, m0 & 0x7fff0000u));
        const float2 mi = lds64f(sb + R_MI + 8);
        wpre(0, NW1A);
        bar_sync(2, 128);
        if (elect()) {
          fence_async_smem();
          if (s > 0) {
            bulk_wait0();
            asm volatile("red.relaxed.gpu.global.add.u32 [%0], 1;" ::"l"(&g_segcnt[s - 1]) : "memory");
            asm volatile("red.relaxed.gpu.global.add.u32 [%0], 1;" ::"l"(&g_prog) : "memory");
          }
          tma_store2(&tmK, sb + R_KT, D0, s * LK);
          tma_store2(&tmV, sb + R_VT, D0, s * LK);
          bulk_commit();
        }
        __syncwarp();
        float wb = mi.x, xm = mi.y;
        if (s == 0) {
          const uint32_t epoch = *(volatile uint32_t*)&g_epoch + 1;
          uint32_t av_ = 0, ao = 0, xi = 0;
#pragma unroll 1
          for (int j = 0; j < 3; j++) {
            uint2 r;
            int n = 0;
#pragma unroll 1
            while (true) {
              r = ldg_rlx64(&g_rec[j * 32 + ((rF - sb) >> 4)]);
              if (((r.x ^ epoch) & 0xffffu) == 0) break;
              if (++n > SPIN_MAX) { g_err = 6; break; }
            }
            av_ = max(av_, r.y & 0xffff0000u); ao = max(ao, r.y << 16); xi = max(xi, r.x & 0xffff0000u);
          }
          av_ = __reduce_max_sync(~0u, av_); ao = __reduce_max_sync(~0u, ao); xi = __reduce_max_sync(~0u, xi);
          wb = __uint_as_float(av_) * __uint_as_float(ao) * 33.f; xm = __uint_as_float(xi);
          if (rF == sb) sts64f(sb + R_MI + 8, wb, xm);
          __syncwarp();
        }
        const float hm = fmaxf(__uint_as_float(mx) * u, xm);
        const uint32_t eb = min(max(__float_as_uint(hm * wb) >> 23, 40u), 200u);
        if (rF == sb) sts64(sb + R_MI + 48, (280u - eb) << 23, (eb - 29u) << 23);
        if (elect()) bulk_wait_read0();
        __syncwarp();
      }
      if (NW1A < NW1) {
        bar_sync(4, 256);
        wpre(NW1A, NW1);
      }
      TR(6);
      oproj(std::true_type{}, std::integral_constant<int, NW1>{}, wot, rF, woA, woB, 0.f, 0.f, false);
    } else {
      {
        uint32_t bb[20][4];
        float ak[4][4] = {};
        ldsm4t(bb[0], rM);
        ldsm4t(bb[10], rM + 5120);
#pragma unroll
        for (int i = 0; i < 10; i++) {
          if (i + 1 < 10) { ldsm4t(bb[i + 1], rM + (i + 1) * 512); ldsm4t(bb[i + 11], rM + (i + 11) * 512); }
          mma16816(ak[0], ww[2 * i], bb[i][0], bb[i][1]);
          if (!LAST) qmma(2 * i, bb[i][0], bb[i][1]);
          mma16816(ak[1], ww[2 * i + 1], bb[i][2], bb[i][3]);
          if (!LAST) qmma(2 * i + 1, bb[i][2], bb[i][3]);
          mma16816(ak[2], ww[2 * i + 20], bb[i + 10][0], bb[i + 10][1]);
          mma16816(ak[3], ww[2 * i + 21], bb[i + 10][2], bb[i + 10][3]);
        }
#pragma unroll
        for (int q = 0; q < 4; q++) { ak[0][q] += ak[2][q]; ak[1][q] += ak[3][q]; }
        stsm4t(rS, pack2(aq[0][0] + aq[1][0], aq[0][1] + aq[1][1]), pack2(aq[0][2] + aq[1][2], aq[0][3] + aq[1][3]),
               pack2((ak[0][0] + ak[1][0]) * u, (ak[0][1] + ak[1][1]) * u), pack2((ak[0][2] + ak[1][2]) * u, (ak[0][3] + ak[1][3]) * u));
      }
      if (LAST) return;
      bar_sync(1, 256);
      if (!B5LATE) bar_arrive(5, 256);
      TR(2);
      if (w != 3) {
        uint32_t qa[4][4], kk[4][4];
        float x[4][4] = {};
#pragma unroll
        for (int i = 0; i < 4; i++) { ldsm4(qa[i], (rP ^ (i << 5)) + R_QB); ldsm4(kk[i], ((rP ^ (i << 5)) + w * 2048) + R_KT); }
        const uint32_t dst = rF + R_SX + rank * 1536 + w * 512;
        const uint32_t e1 = mapa(dst, r1), e2 = mapa(dst, r2), s1 = mapa(SBAR, r1), s2 = mapa(SBAR, r2);
#pragma unroll
        for (int i = 0; i < 4; i++) { mma16816(x[i & 1], qa[i], kk[i][0], kk[i][1]); mma16816(x[2 + (i & 1)], qa[i], kk[i][2], kk[i][3]); }
        const uint32_t u0 = __float_as_uint((x[0][0] + x[0][2]) + (x[1][0] + x[1][2])), u1 = __float_as_uint((x[0][1] + x[0][3]) + (x[1][1] + x[1][3]));
        const uint32_t u2 = __float_as_uint((x[2][0] + x[2][2]) + (x[3][0] + x[3][2])), u3 = __float_as_uint((x[2][1] + x[2][3]) + (x[3][1] + x[3][3]));
        st_async4(e1, u0, u1, u2, u3, s1);
        st_async4(e2, u0, u1, u2, u3, s2);
        sts128(dst, u0, u1, u2, u3);
        __syncwarp();
        if (rF == sb) mbar_arrive(SBAR);
      }
      if (B5LATE) bar_arrive(5, 256);
      TR(4);
      mbar_wait(VBAR, s & 1);
      uint32_t wot[12][4], va[3][8];
      ldsm4t(va[0], rP + R_VT + 1024); ldsm4t(va[0] + 4, rP + R_VT + 3072);
#pragma unroll
      for (int q = 0; q < 4; q++) {
        if (VBULK) { ldsm4t(va[1 + (q >> 1)] + (q & 1) * 4, rP + R_V1 + q * 2048); continue; }
        const uint4 t = lds128(rF + R_V1 + w * 512 + q * 2048);
        uint32_t* v = va[1 + (q >> 1)] + (q & 1) * 4;
        v[0] = t.x; v[1] = t.y; v[2] = t.z; v[3] = t.w;
      }
      auto wpre = [&](int i0, int i1) {
        if (two) {
#pragma unroll
          for (int i = i0; i < i1; i++) ldsm4t(wot[i], ((i & 1) ? woB : woA) + WOFF(i >> 1));
        } else {
#pragma unroll
          for (int i = i0; i < i1; i++) ldsm4t(wot[i], woA + WOFF(i));
        }
      };
      wpre(0, NO_EARLY);
      const uint32_t dst = rF + (w >> 1) * 512 + (w & 1) * 8;
      const float scl = u * (0.07216878364870322f * 1.4426950408889634f);
      mbar_wait(SBAR, s & 1);
      TR(6);
      float sc[10];
      {
        const float4 a0 = lds128f(rF + R_SX), b0 = lds128f(rF + R_SX + 1536), c0 = lds128f(rF + R_SX + 3072);
        const float4 a1 = lds128f(rF + R_SX + 512), b1 = lds128f(rF + R_SX + 2048), c1 = lds128f(rF + R_SX + 3584);
        const float2 a2 = lds64f(rF + R_SX + 1024), b2 = lds64f(rF + R_SX + 2560), c2 = lds64f(rF + R_SX + 4096);
        sc[8] = a0.x + b0.x + c0.x; sc[9] = a0.y + b0.y + c0.y; sc[0] = a0.z + b0.z + c0.z; sc[1] = a0.w + b0.w + c0.w;
        sc[2] = a1.x + b1.x + c1.x; sc[3] = a1.y + b1.y + c1.y; sc[4] = a1.z + b1.z + c1.z; sc[5] = a1.w + b1.w + c1.w;
        sc[6] = a2.x + b2.x + c2.x; sc[7] = a2.y + b2.y + c2.y;
      }
      float mx = fmaxf(fmaxf(fmaxf(sc[0], sc[1]), fmaxf(sc[2], sc[3])), fmaxf(fmaxf(sc[4], sc[5]), fmaxf(sc[6], sc[7])));
      mx = fmaxf(mx, fmaxf(sc[8], sc[9]));
      mx = fmaxf(mx, __shfl_xor_sync(~0u, mx, 1));
      const bool vok = mbar_test(OBAR, s & 1);
      mx = fmaxf(mx, __shfl_xor_sync(~0u, mx, 2));
      if (NW1A < NW1) bar_arrive(4, 256);
      const float mo = mx * scl;
      uint32_t pb[5];
#pragma unroll
      for (int j = 0; j < 5; j++) pb[j] = pack2(ex2(fmaf(sc[2 * j], scl, -mo)), ex2(fmaf(sc[2 * j + 1], scl, -mo)));
      if (!vok) mbar_wait(OBAR, s & 1);
      const uint2 m0 = lds64(l8 + R_VS), m1 = lds64(l8 + R_VM), m2 = lds64(l8 + R_VM + 1024);
      const uint32_t ones[4] = {ONES, ONES, ONES, ONES};
      float o[3][4], o2[3][4], sm[4] = {0.f, 0.f, 0.f, 0.f}, sn[4] = {0.f, 0.f, 0.f, 0.f}, so[4] = {0.f, 0.f, 0.f, 0.f};
#pragma unroll
      for (int b = 0; b < 3; b++) {
        o[b][0] = o[b][1] = o[b][2] = o[b][3] = o2[b][0] = o2[b][1] = o2[b][2] = o2[b][3] = 0.f;
        mma16816(o[b], va[b], pb[0], pb[1]);
      }
#pragma unroll
      for (int b = 0; b < 3; b++) mma16816(o2[b], va[b] + 4, pb[2], pb[3]);
      mma1688(o[0], m0.x, m0.y, pb[4]);
      mma1688(o[1], m1.x, m1.y, pb[4]);
      mma1688(o[2], m2.x, m2.y, pb[4]);
      mma16816(sm, ones, pb[0], pb[1]);
      mma16816(sn, ones, pb[2], pb[3]);
      mma1688(so, ONES, ONES, pb[4]);
      wpre(NO_EARLY, NO_MID);
#pragma unroll
      for (int b = 0; b < 3; b++)
        sts64(dst + (b == 0 ? R_QB : (b == 1 ? R_QA : R_O2)), movmat(pack2(o[b][0] + o2[b][0], o[b][1] + o2[b][1])),
              movmat(pack2(o[b][2] + o2[b][2], o[b][3] + o2[b][3])));
      sm[0] += sn[0] + so[0]; sm[1] += sn[1] + so[1];
      if (rF - sb < 64) sts64f(sb + R_MI + 16 + ((rF - sb) >> 1), sm[0], sm[1]);
      wpre(NO_MID, 12);
      TR(7);
      if (two) oproj(std::true_type{}, std::integral_constant<int, 12>{}, wot, rF, woA, woB, sm[0], sm[1], true);
      else oproj(std::false_type{}, std::integral_constant<int, 12>{}, wot, rF, woA, woB, sm[0], sm[1], true);
    }
  };

  GTR(5); GTR(6);
  if (g == 0) {
    window(std::integral_constant<int, 0>{}, std::true_type{});
    GTR(7);
#pragma unroll 1
    for (s = 0; s < NSEG - 1; s++) {
      step(std::integral_constant<int, 0>{}, std::false_type{});
      window(std::integral_constant<int, 0>{}, std::false_type{});
    }
    step(std::integral_constant<int, 0>{}, std::true_type{});
  } else {
    window(std::integral_constant<int, 1>{}, std::true_type{});
#pragma unroll 1
    for (s = 0; s < NSEG - 1; s++) {
      step(std::integral_constant<int, 1>{}, std::false_type{});
      window(std::integral_constant<int, 1>{}, std::false_type{});
    }
    step(std::integral_constant<int, 1>{}, std::true_type{});
  }
  __syncthreads();
  if (tid == 160) {
    fence_async_smem();
    tma_store2(&tmK, sb + R_KT, D0, (NSEG - 1) * LK);
    tma_store2(&tmV, sb + R_VT, D0, (NSEG - 1) * LK);
    bulk_commit();
    bulk_wait0();
    asm volatile("red.relaxed.gpu.global.add.u32 [%0], 1;" ::"l"(&g_segcnt[NSEG - 2]) : "memory");
    asm volatile("red.relaxed.gpu.global.add.u32 [%0], 1;" ::"l"(&g_segcnt[NSEG - 1]) : "memory");
    asm volatile("red.relaxed.gpu.global.add.u32 [%0], 2;" ::"l"(&g_prog) : "memory");
  }
  GTR(8);
  if (tid == 0 && VBULK != 2 && VBULK != 3) mbar_wait(VBAR, (NSEG - 1) & 1);
  GTR(9);
}

enum { IT_GATE = 0, IT_QKV = 1, IT_XATT = 2, IT_OUT = 3, IT_BATT = 4, IT_CVT = 5, IT_INIT = 6, IT_END = 7 };
constexpr int C_GATE = 0, C_QKV = 16, C_OB = 32, C_ACC = 48, C_O = 80;
constexpr uint32_t NONE = ~0u;
#define HP 0x1223346888888888ull
#define XD 0x4589aaaaaaaaaaaaull
#define KREQ 4
#define ADELAY 0
#define PP 3
__host__ __device__ constexpr uint32_t mk_item(int ty, int t, int a, int b = 0, int c = 0) { return ty | (t << 3) | (a << 8) | (b << 16) | (c << 24); }
struct ItemTab { uint32_t v[1280]; int n; };
constexpr ItemTab make_items() {
  ItemTab T{};
  int n = 0;
  for (int t = 0; t < 16; t++) T.v[n++] = mk_item(IT_GATE, t, 0);
  for (int t = 0; t < 16; t++) for (int a = 0; a < 5; a++) T.v[n++] = mk_item(IT_QKV, t, a);
  for (int t = 0; t < 32; t++) for (int a = 0; a < 4; a++) T.v[n++] = mk_item(IT_BATT, t, a);
  for (int t = 0; t < 16; t++) for (int a = 0; a < 2; a++) T.v[n++] = mk_item(IT_INIT, t, a);
  for (int t = 0; t < 16; t++) {
    const int hp = (HP >> 4 * t) & 15;
    for (int h = 0; h < 32; h += hp) for (int a = 0; a < 2; a++) T.v[n++] = mk_item(IT_OUT, t, a, h, h + hp < 32 ? h + hp : 32);
  }
  T.n = n;
  return T;
}
constexpr ItemTab k_items_host = make_items();
constexpr int NITEMS = k_items_host.n;
__constant__ ItemTab c_items = make_items();

constexpr int AUX_GRID = 132, NST = 7, STG = 32768;
constexpr int A_FULL = NST * STG, A_EMPTY = A_FULL + 64, A_ITEM = A_EMPTY + 64, A_QBAR = A_ITEM + 32, A_QENT = A_QBAR + 128, A_MISC = A_QENT + 256,
              A_SMEM = A_MISC + 64, A_REQ = A_FULL + 56, A_RSP = A_EMPTY + 56, A_MAIL = A_MISC + 48;
static_assert(A_SMEM <= 232448, "smem");
enum { OP_END = 0, OP_O = 1, OP_QKV = 2, OP_OB = 3, OP_SET = 4, OP_ADD = 5 };

struct AuxMaps { CUtensorMap xA, wq, wqkv, wo, wob, k, v, oA, oS, obA, obS, qkvS, qkvQ, qkvK, out; };

__device__ __forceinline__ void mbar_wait_long(uint32_t b, uint32_t par) {
  int n = 0;
#pragma unroll 1
  while (!mbar_try(b, par)) { if (++n > (SPIN_MAX << 4)) { g_err = 8; break; } }
}
__device__ __forceinline__ uint64_t mk_desc(uint32_t addr, uint32_t lbo, uint32_t sbo, uint32_t mode) {
  return (uint64_t)((addr & 0x3FFFF) >> 4) | ((uint64_t)(lbo >> 4) << 16) | ((uint64_t)(sbo >> 4) << 32) | ((uint64_t)mode << 62);
}

__global__ void __launch_bounds__(384, 1)
aux_kernel(const __grid_constant__ AuxMaps tm, const bf16* __restrict__ x, const bf16* __restrict__ gate_w) {
  extern __shared__ __align__(1024) unsigned char smem[];
  const uint32_t sb = smem_u32(smem);
  const int tid = threadIdx.x, lane = tid & 31, wid = __shfl_sync(~0u, tid >> 5, 0);
  uint32_t epoch = 0, j0 = 0;
  const uint32_t c0 = clk32();
  if (tid == 352) GTA(0);
  if (tid >= 256) epoch = *(volatile uint32_t*)&g_epoch + 1;
  if (tid == 352) j0 = atomicAdd(&g_queue[32], 1u);
  if (tid == 0) {
    mbar_init(sb + A_REQ, 1); mbar_init(sb + A_RSP, 1);
    for (int i = 0; i < NST; i++) { mbar_init(sb + A_FULL + i * 8, 1); mbar_init(sb + A_EMPTY + i * 8, 8); }
    for (int i = 0; i < 16; i++) mbar_init(sb + A_QBAR + i * 8, 4);
    asm volatile("fence.mbarrier_init.release.cluster;" ::: "memory");
  }
  if (tid < 15) prefetch_map(&tm.xA + tid);
  if (tid == 352) GTA(4);
  __syncthreads();
  if (tid == 352) GTA(5);
  uint32_t st = 0, ph = 0;
  auto advance = [&]() { if (++st == NST) { st = 0; ph ^= 1; } };

  if (wid >= 8) {
    asm volatile("setmaxnreg.dec.sync.aligned.u32 40;");
    if (tid == 352) GTA(6);
    auto cnt = [&](int c, uint32_t per) -> bool { return (int)(ldg_rlx32(&g_cnt[c * 8]) - epoch * per) >= 0; };
    auto ready = [&](uint32_t item) -> int {
      const int ty = item & 7, t = (item >> 3) & 31, b = (item >> 17) & 127, n = (((item >> 24) + 1) >> 1) - b;
      int r;
      if (ty == IT_OUT) {
        const int c = C_O + t * 16 + b;
        const bool r0 = cnt(c, 2), r1 = cnt(c + (n > 1), 2), r2 = cnt(c + (n > 2) * 2, 2), r3 = cnt(c + (n > 3) * 3, 2);
        r = r0 & cnt(C_ACC + t, 4) ? (r1 ? (r2 ? (r3 ? 4 : 3) : 2) : 1) : 0;
      } else if (ty == IT_XATT) {
        const uint4 v = ldg_rlx128(&g_segcnt[4 * t]);
        const uint32_t e = epoch * 96;
        r = ((int)(v.x - e) >= 0) & ((int)(v.y - e) >= 0) & ((int)(v.z - e) >= 0) & ((int)(v.w - e) >= 0);
      } else if (ty == IT_BATT) {
        r = cnt(C_GATE, 16) & cnt(C_QKV + (t >> 1), 10) & cnt(C_QKV + (max(t - 1, 0) >> 1), 10);
      } else {
        r = ty <= IT_QKV || cnt(C_OB + t, 8);
      }
      asm volatile("fence.acquire.gpu; fence.proxy.async.global;" ::: "memory");
      return r;
    };
    if (wid == 11 && lane == 0) {
      uint32_t pend = j0 < (uint32_t)NITEMS ? c_items.v[j0] : (uint32_t)IT_END;
      bool xleft = true;
      uint32_t nidx = 0, pidx = j0;
      GTA(1);
      if (j0 < 64) spin_until(c0, ADELAY);
      if (pend != 12345) GTA(2);
#pragma unroll 1
      for (uint32_t e = 0;; e++) {
        if (e) mbar_wait_long(sb + A_REQ, (e - 1) & 1);
        uint32_t item = NONE;
        int rdy = 0, spins = 0;
#pragma unroll 1
        while (true) {
          const bool fresh = pend == NONE;
          if (xleft) {
            const uint4 c = ldg_rlx128(&g_queue[0]);
            const uint32_t pr = ldg_rlx32(&g_prog) - (epoch - 1) * (96 * NSEG);
            const bool gates = cnt(C_GATE, 16);
            if (!fresh) rdy = ready(pend);
            auto full = [](uint32_t v) { v = (v | (v >> 2)) & 0x30303030u; return __popc((v | (v >> 1)) & 0x10101010u); };
            const int t = full(c.x) + full(c.y) + full(c.z) + full(c.w);
            xleft = t < 16;
            if (xleft && gates && (int)pr >= 96 * (4 * t - 8 + (int)((XD >> 4 * t) & 15))) {
              const uint32_t j = (atomicAdd(&g_queue[t >> 2], 1u << (t & 3) * 8) >> (t & 3) * 8) & 255;
              if (j < 16) { item = mk_item(IT_XATT, t, j); rdy = 0; nidx = NITEMS + 132 + t * 16 + j; }
            }
          } else if (!fresh) {
            rdy = ready(pend);
          }
          if (item == NONE) {
            if (fresh) {
              pidx = atomicAdd(&g_queue[32], 1u);
              pend = pidx < (uint32_t)NITEMS ? c_items.v[pidx] : (uint32_t)IT_END;
              rdy = ready(pend);
            }
            const int need = (pend & 7) == IT_OUT && xleft ? (((pend >> 24) + 1) >> 1) - ((pend >> 17) & 127) : 1;
            if (pend == IT_END ? !xleft : rdy >= need) { item = pend; pend = NONE; nidx = pidx; }
          }
          if (item != NONE) break;
          if (++spins > SPIN_MAX) { g_err = 10; item = IT_END; break; }
          __nanosleep(50);
        }
        if (e == 0) GTA(3);
        sts128(sb + A_MAIL, item, rdy, nidx, 0);
        mbar_arrive(sb + A_RSP);
        if (item == IT_END) break;
      }
      if (atomicAdd(&g_queue[64], 1u) == AUX_GRID - 1) { *(uint4*)g_queue = make_uint4(0, 0, 0, 0); g_queue[32] = 0; g_queue[64] = 0; g_epoch = epoch; }
      asm volatile("griddepcontrol.wait;" ::: "memory");
    } else if (wid == 8 && lane == 0) {
      uint32_t item = 0;
      auto slot = [&](uint32_t bytes) -> uint32_t {
        mbar_wait_long(sb + A_EMPTY + st * 8, ph ^ 1);
        sts32(sb + A_ITEM + st * 4, item);
        if (bytes) mbar_expect(sb + A_FULL + st * 8, bytes); else mbar_arrive(sb + A_FULL + st * 8);
        return sb + st * STG;
      };
#pragma unroll 1
      for (uint32_t e = 0;; e++) {
        mbar_wait_long(sb + A_RSP, e & 1);
        const uint4 mail = lds128(sb + A_MAIL);
        asm volatile("fence.proxy.async.global;" ::: "memory");
        item = mail.x;
        int rdy = mail.y;
        int k = (item & 7) == IT_OUT ? ((item >> 16) & 255) * 6 : 0;
        const int k1 = (item & 7) == IT_OUT ? (item >> 24) * 6 : (0x01140103001c1401ull >> ((item & 7) * 8)) & 255;
        const int kreq = max(k1 - KREQ, k);
#pragma unroll 1
        for (; k < k1; k++) {
          item = pin(item);
          const int ty = item & 7, t = (item >> 3) & 31, a = (item >> 8) & 255;
          const bool out_ = ty == IT_OUT, gemm1 = ty == IT_QKV || ty == IT_XATT;
          const int dep = out_ ? k / 12 - ((item >> 17) & 127) : (ty == IT_XATT ? (k >= 20) - 1 : -1);
          if (rdy <= dep || (k == 12 && ty == IT_XATT)) {
            int n = 0;
#pragma unroll 1
            while ((rdy = ready(pin(item))) <= dep) {
              if (++n > SPIN_MAX) { g_err = 7; break; }
              __nanosleep(20);
            }
          }
          const uint32_t fb = sb + A_FULL + st * 8;
          if (out_ || ty == IT_INIT) {
            const uint32_t d = slot(28672);
            tma_load2(d, out_ ? &tm.oA : &tm.obA, k * 32, t * 128, fb);
            tma_load3(d + 8192, out_ ? &tm.wo : &tm.wob, 0, k * 32, a * 5, fb);
          } else if (gemm1 && k < 20) {
            const uint32_t d = slot(32768);
            tma_load2(d, &tm.xA, k * 32, t * 128, fb);
            tma_load3(d + 8192, ty == IT_QKV ? &tm.wqkv : &tm.wq, 0, k * 32, a * 6, fb);
          } else if (gemm1) {
            const uint32_t d = slot(30720);
            tma_load3(d, k < 24 ? &tm.k : &tm.v, 0, (4 * t + (k & 2)) * LK, (2 * a + (k & 1)) * 3, fb);
          } else if (ty == IT_BATT) {
            const uint32_t d = slot(k ? 25600 : 20480);
            tma_load2(d, k ? &tm.qkvK : &tm.qkvQ, k * 640 + a * 160, t * 64 - (k ? 16 : 0), fb);
          } else {
            slot(0);
          }
          if (k == kreq) mbar_arrive(sb + A_REQ);
          advance();
        }
        if (item == IT_END) break;
        if ((0x4a >> (item & 7)) & 1) {
#pragma unroll 1
          for (k = 0; k < 4; k++) { slot(0); advance(); }
        }
      }
    } else if ((wid == 9 || wid == 10) && lane == 0) {
      const uint32_t qb = sb + A_QBAR + (wid - 9) * 64, qe = sb + A_QENT + (wid - 9) * 128;
      for (uint32_t e = 0;; e++) {
        mbar_wait_long(qb + (e & 7) * 8, (e >> 3) & 1);
        const uint4 en = lds128(qe + (e & 7) * 16);
        const int op = en.x & 15, sg = (en.x >> 4) & 15, rel = (en.x >> 8) & 15, nb = (en.x >> 12) & 15;
        if (op == OP_END) break;
        const uint32_t src = sb + sg * STG;
        if (op == OP_O) tma_store3(&tm.oS, src, 0, en.y, en.z);
        else if (op == OP_QKV) tma_store3(&tm.qkvS, src, 0, en.y, en.z);
        else if (op == OP_OB) tma_store2(&tm.obS, src, en.z, en.y);
        else if (op == OP_SET) { for (int i = 0; i < nb; i++) tma_store3(&tm.out, src + i * 8192, 0, en.y, en.z + i); }
        else { for (int i = 0; i < nb; i++) tma_red3(&tm.out, src + i * 8192, 0, en.y, en.z + i); }
        bulk_commit();
        bulk_wait_read0();
        asm volatile("mbarrier.arrive.shared::cta.b64 _, [%0], %1;" ::"r"(sb + A_EMPTY + sg * 8), "r"(rel) : "memory");
        if (en.w) {
          bulk_wait0();
          asm volatile("red.relaxed.gpu.global.add.u32 [%0], %1;" ::"l"(&g_cnt[(en.w - 1) * 8]), "r"(1) : "memory");
        }
      }
      bulk_wait0();
      if (wid == 10) GTA(7);
    }
  } else {
    asm volatile("setmaxnreg.inc.sync.aligned.u32 232;");
    const int g = wid >> 2, w = wid & 3;
    uint32_t qn = 0;
    auto wait_full = [&]() { mbar_wait_long(sb + A_FULL + st * 8, ph); };
    auto release = [&](uint32_t s_) { if (lane == 0) mbar_arrive(sb + A_EMPTY + s_ * 8); };
    auto take_pair = [&]() -> uint32_t {
      wait_full();
      const uint32_t s0 = st; advance();
      wait_full();
      const uint32_t s1 = st; advance();
      release(g ? s0 : s1);
      return g ? s1 : s0;
    };
    auto push = [&](uint32_t w0, uint32_t w1, uint32_t w2, uint32_t w3) {
      fence_async_smem();
      if (w == 0 && lane == 0) sts128(sb + A_QENT + g * 128 + (qn & 7) * 16, w0, w1, w2, w3);
      __syncwarp();
      if (lane == 0) mbar_arrive(sb + A_QBAR + g * 64 + (qn & 7) * 8);
      qn++;
    };
    const uint32_t stm = (16 * w + (lane & 7) + (lane & 8)) * 128, stx = lane & 7, sth = lane >> 4;
    auto stage_bf16 = [&](uint32_t dst, const float* d, float s0, float s1, int nks = 12) {
#pragma unroll
      for (int ks = 0; ks < nks; ks++)
        stsm4(dst + (ks >> 2) * 8192 + stm + (((2 * (ks & 3) + sth) ^ stx) << 4), pack2(d[8 * ks] * s0, d[8 * ks + 1] * s0), pack2(d[8 * ks + 2] * s1, d[8 * ks + 3] * s1),
              pack2(d[8 * ks + 4] * s0, d[8 * ks + 5] * s0), pack2(d[8 * ks + 6] * s1, d[8 * ks + 7] * s1));
    };
#pragma unroll 1
    while (true) {
      wait_full();
      const uint32_t item = lds32(sb + A_ITEM + st * 4);
      const int ty = item & 7, t = (item >> 3) & 31, a = (item >> 8) & 255;
      if (ty == IT_QKV || ty == IT_XATT) {
        float acc[192] = {};
        uint32_t prev = 0;
#pragma unroll 1
        for (int k = 0; k < 20; k++) {
          if (k) wait_full();
          const uint32_t s_ = sb + st * STG;
          const uint64_t da = mk_desc(s_, 16, 512, 2), db = mk_desc(s_ + 8192 + g * 12288, 4096, 1024, 1);
          wg_fence();
          wgmma_ss192t(acc, da, db, k);
          wgmma_ss192t(acc + 96, da + 256, db, k);
          wgmma_ss192t(acc, da + 2, db + 128, 1);
          wgmma_ss192t(acc + 96, da + 258, db + 128, 1);
          wg_commit();
          if (k) { wg_wait1(); release(prev); }
          prev = st; advance();
        }
        wg_wait0();
        fence_regs<192>(acc);
        release(prev);
        if (ty == IT_QKV) {
#pragma unroll
          for (int q = 0; q < 2; q++) {
            const uint32_t m = take_pair();
            stage_bf16(sb + m * STG, acc + q * 96, 1.f, 1.f);
            push(OP_QKV | (m << 4) | (4 << 8), t * 128 + q * 64, a * 6 + g * 3, q ? C_QKV + t + 1 : 0);
          }
        } else {
          uint32_t qf[24][4];
#pragma unroll
          for (int ks = 23; ks >= 0; ks--)
#pragma unroll
            for (int j = 0; j < 4; j++)
              asm volatile("cvt.rn.bf16x2.f32 %0, %1, %2;" : "=r"(qf[ks][j]) : "f"(acc[8 * ks + 2 * j + 1]), "f"(acc[8 * ks + 2 * j]));
          float sc[2][40] = {};
          uint32_t kst[2];
#pragma unroll
          for (int q = 0; q < 2; q++) {
            kst[q] = take_pair();
            const uint64_t db = mk_desc(sb + kst[q] * STG, 16, 1024, 1);
            wg_fence();
#pragma unroll
            for (int ks = 0; ks < 12; ks++) wgmma_rs80(sc[q], qf[q * 12 + ks], db + (((ks >> 2) * 10240 + (ks & 3) * 32) >> 4), ks);
            wg_commit();
          }
          const int tt = 16 * (w & 1) + (lane >> 2) - 2 * (lane & 3);
          const float* gp = g_gate + t * 128 + 16 * w + (lane >> 2);
          const float gt[4] = {__ldcg(gp), __ldcg(gp + 8), __ldcg(gp + 64), __ldcg(gp + 72)};
          uint32_t pf[2][5][4];
          float rs[2][2];
          auto softmax = [&](const float* s_, uint32_t (&p)[5][4], float* r) {
            constexpr float SCL = 0.07216878364870322f * 1.4426950408889634f;
            float v[20];
#pragma unroll
            for (int i = 0; i < 20; i++) {
              v[i] = w >= 2 ? s_[20 + i] : s_[i];
              if (i >= 4 && 8 * ((i >> 2) - 1) + (i & 1) > tt + ((i & 2) ? 8 : 0)) v[i] = -INFINITY;
            }
            uint32_t pt[5][2];
#pragma unroll
            for (int h = 0; h < 2; h++) {
              float mx = fmaxf(v[2 * h], v[2 * h + 1]);
#pragma unroll
              for (int j = 1; j < 5; j++) mx = fmaxf(mx, fmaxf(v[4 * j + 2 * h], v[4 * j + 2 * h + 1]));
              mx = fmaxf(mx, __shfl_xor_sync(~0u, mx, 1));
              mx = fmaxf(mx, __shfl_xor_sync(~0u, mx, 2));
              const float mo = mx * SCL;
              float sum = 0.f;
#pragma unroll
              for (int j = 0; j < 5; j++) {
                const float e0 = ex2(fmaf(v[4 * j + 2 * h], SCL, -mo)), e1 = ex2(fmaf(v[4 * j + 2 * h + 1], SCL, -mo));
                pt[j][h] = pack2(e0, e1);
                sum += bf_lo(pt[j][h]) + bf_hi(pt[j][h]);
              }
              sum += __shfl_xor_sync(~0u, sum, 1);
              sum += __shfl_xor_sync(~0u, sum, 2);
              r[h] = rcp(sum);
            }
#pragma unroll
            for (int J = 0; J < 10; J++)
#pragma unroll
              for (int h = 0; h < 2; h++) p[J >> 1][(J & 1) * 2 + h] = (J >= 5) == (w >= 2) ? pt[J % 5][h] : 0u;
          };
          wg_wait1();
          fence_regs<40>(sc[0]);
          release(kst[0]);
          softmax(sc[0], pf[0], rs[0]);
#pragma unroll
          for (int q = 0; q < 2; q++) {
            const uint32_t m = take_pair();
            const uint64_t db = mk_desc(sb + m * STG, 10240, 1024, 1);
            float o[96] = {};
            wg_fence();
#pragma unroll
            for (int ks = 0; ks < 5; ks++) wgmma_rs192t(o, pf[q][ks], db + ks * 128, ks);
            wg_commit();
            if (q == 0) {
              wg_wait1();
              fence_regs<40>(sc[1]);
              release(kst[1]);
              softmax(sc[1], pf[1], rs[1]);
            }
            wg_wait0();
            fence_regs<96>(o);
            bar_sync(1 + g, 128);
            stage_bf16(sb + m * STG, o, rs[q][0] * gt[2 * q], rs[q][1] * gt[2 * q + 1]);
            push(OP_O | (m << 4) | (4 << 8), t * 128 + q * 64, a * 6 + g * 3, q ? C_O + t * 16 + a + 1 : 0);
          }
        }
      } else if (ty == IT_OUT || ty == IT_INIT) {
        float acc[160] = {};
        const int hb = (item >> 16) & 255, nh = (item >> 24) - hb, nk = ty == IT_OUT ? nh * 6 : 20, jh = a & 1;
        const uint32_t ln = pin(lane), ao = (g * 64 + 16 * w + (ln & 15)) * 64 + (((ln >> 4) ^ ((ln >> 1) & 3)) << 4);
        if (PP && g == 1) bar_arrive(4, 256);
#pragma unroll 1
        for (int k = 0; k < nk; k += 2) {
          uint32_t af[4][4], sg[2];
#pragma unroll
          for (int e = 0; e < 2; e++) {
            if (k + e) wait_full();
            sg[e] = st;
            ldsm4(af[2 * e], sb + st * STG + ao);
            ldsm4(af[2 * e + 1], sb + st * STG + (ao ^ 32));
            advance();
          }
          if (PP) bar_sync(4 + g, 256);
          wg_fence();
#pragma unroll
          for (int e = 0; e < 4; e++) {
            const uint64_t db = mk_desc(sb + sg[e >> 1] * STG + 8192 + (e & 1) * 2048, 4096, 1024, 1);
            if (PP == 2 && e == 3 && (g == 0 || k + 2 < nk)) bar_arrive(5 - g, 256);
            wgmma_rs192t(acc, af[e], db, 1);
            if (PP == 3 && e == 3 && (g == 0 || k + 2 < nk)) bar_arrive(5 - g, 256);
            wgmma_rs128t(acc + 96, af[e], db + 768, 1);
          }
          wg_commit();
          if (PP == 1 && (g == 0 || k + 2 < nk)) bar_arrive(5 - g, 256);
          wg_wait0();
          release(sg[0]); release(sg[1]);
        }
        fence_regs<160>(acc);
        const uint32_t row = t * 128 + g * 64;
#pragma unroll
        for (int q = 0; q < 2; q++) {
          const uint32_t m = take_pair();
          stage_bf16(sb + m * STG, acc + q * 96, 1.f, 1.f, q ? 8 : 12);
          push((ty == IT_OUT ? OP_ADD : OP_SET) | (m << 4) | (4 << 8) | ((3 - q) << 12), row, jh * 5 + q * 3, q && ty == IT_INIT ? C_ACC + t + 1 : 0);
        }
      } else if (ty == IT_BATT) {
        const uint32_t sq = st; advance();
        wait_full();
        const uint32_t sk = st; advance();
        wait_full();
        const uint32_t sv = st; advance();
        const int h = tid & 7;
#pragma unroll 1
        for (int p = 0; p < 2; p++) {
          const int tok = (tid >> 3) + 32 * p, pos = t * 64 + tok;
          const uint32_t qa = sb + sq * STG + tok * 320 + h * 40, ka = sb + sk * STG + (tok + 16) * 320 + h * 40, va = sb + sv * STG + (tok + 16) * 320 + h * 40;
          const float gt = __ldcg(g_gate + 2048 + pos);
          float q[20], l[8];
#pragma unroll
          for (int i = 0; i < 5; i++) { const uint2 u = lds64(qa + i * 8); q[4 * i] = bf_lo(u.x); q[4 * i + 1] = bf_hi(u.x); q[4 * i + 2] = bf_lo(u.y); q[4 * i + 3] = bf_hi(u.y); }
          float mx = -INFINITY;
#pragma unroll
          for (int j = 0; j < 8; j++) {
            float s0 = 0.f, s1 = 0.f;
#pragma unroll
            for (int i = 0; i < 5; i++) {
              const uint2 u = lds64(ka - j * 640 + i * 8);
              s0 = fmaf(q[4 * i], bf_lo(u.x), s0); s1 = fmaf(q[4 * i + 1], bf_hi(u.x), s1);
              s0 = fmaf(q[4 * i + 2], bf_lo(u.y), s0); s1 = fmaf(q[4 * i + 3], bf_hi(u.y), s1);
            }
            l[j] = pos - 2 * j >= 0 ? s0 + s1 : -INFINITY;
            mx = fmaxf(mx, l[j]);
          }
          constexpr float SCL = 0.22360679774997896f * 1.4426950408889634f;
          const float mo = mx * SCL;
          float sum = 0.f;
#pragma unroll
          for (int j = 0; j < 8; j++) { l[j] = ex2(fmaf(l[j], SCL, -mo)); sum += l[j]; }
          const float r = gt * rcp(sum);
#pragma unroll
          for (int i = 0; i < 20; i++) q[i] = 0.f;
#pragma unroll
          for (int j = 0; j < 8; j++) {
#pragma unroll
            for (int i = 0; i < 5; i++) {
              const uint2 u = lds64(va - j * 640 + i * 8);
              q[4 * i] = fmaf(l[j], bf_lo(u.x), q[4 * i]); q[4 * i + 1] = fmaf(l[j], bf_hi(u.x), q[4 * i + 1]);
              q[4 * i + 2] = fmaf(l[j], bf_lo(u.y), q[4 * i + 2]); q[4 * i + 3] = fmaf(l[j], bf_hi(u.y), q[4 * i + 3]);
            }
          }
#pragma unroll
          for (int i = 0; i < 5; i++) sts64(qa + i * 8, pack2(q[4 * i] * r, q[4 * i + 1] * r), pack2(q[4 * i + 2] * r, q[4 * i + 3] * r));
        }
        __syncwarp();
        release(sk); release(sv);
        fence_async_smem();
        bar_sync(3, 256);
        if (g == 0) push(OP_OB | (sq << 4) | (8 << 8), t * 64, a * 160, C_OB + (t >> 1) + 1);
      } else if (ty == IT_GATE) {
        release(st); advance();
        uint4 gw[3];
#pragma unroll
        for (int i = 0; i < 3; i++) gw[i] = (i < 2 || lane < 16) ? __ldg((const uint4*)gate_w + lane + 32 * i) : make_uint4(0, 0, 0, 0);
        const uint4* xr = (const uint4*)(x + (size_t)(t * 128 + wid * 16) * DM) + lane;
        uint4 v[16][3];
#pragma unroll
        for (int r = 0; r < 16; r++)
#pragma unroll
          for (int i = 0; i < 3; i++) v[r][i] = (i < 2 || lane < 16) ? __ldg(xr + r * (DM / 8) + 32 * i) : make_uint4(0, 0, 0, 0);
        float z = 0.f;
#pragma unroll
        for (int r = 0; r < 16; r++) {
          float s_ = 0.f;
#pragma unroll
          for (int i = 0; i < 3; i++) {
            const uint32_t p0 = hmul2(v[r][i].x, gw[i].x), p1 = hmul2(v[r][i].y, gw[i].y), p2 = hmul2(v[r][i].z, gw[i].z), p3 = hmul2(v[r][i].w, gw[i].w);
            s_ += ((bf_lo(p0) + bf_hi(p0)) + (bf_lo(p1) + bf_hi(p1))) + ((bf_lo(p2) + bf_hi(p2)) + (bf_lo(p3) + bf_hi(p3)));
          }
#pragma unroll
          for (int o = 16; o; o >>= 1) s_ += __shfl_xor_sync(~0u, s_, o);
          if (lane == r) z = s_;
        }
        z = bf_lo(pack2(z, 0.f));
        const float gv = bf_lo(pack2(1.f / (1.f + __expf(-z)), 0.f));
        if (lane < 16) { g_gate[t * 128 + wid * 16 + lane] = gv; g_gate[2048 + t * 128 + wid * 16 + lane] = bf_lo(pack2(1.f - gv, 0.f)); }
        __threadfence();
        bar_sync(3, 256);
        if (tid == 0) asm volatile("red.release.gpu.global.add.u32 [%0], 1;" ::"l"(&g_cnt[C_GATE * 8]) : "memory");
      } else {
        release(st);
        push(OP_END, 0, 0, 0);
        break;
      }
    }
  }
}

typedef CUresult (*EncFn)(CUtensorMap*, CUtensorMapDataType, cuuint32_t, void*, const cuuint64_t*, const cuuint64_t*, const cuuint32_t*,
                          const cuuint32_t*, CUtensorMapInterleave, CUtensorMapSwizzle, CUtensorMapL2promotion, CUtensorMapFloatOOBfill);

#define PROMO CU_TENSOR_MAP_L2_PROMOTION_L2_128B
void make_map(EncFn enc, CUtensorMap* tm, const void* base, int rank, const cuuint64_t* dims, const cuuint64_t* strides, const cuuint32_t* box,
              CUtensorMapSwizzle sw = CU_TENSOR_MAP_SWIZZLE_128B, CUtensorMapDataType dt = CU_TENSOR_MAP_DATA_TYPE_BFLOAT16) {
  const cuuint32_t es[5] = {1, 1, 1, 1, 1};
  enc(tm, dt, rank, const_cast<void*>(base), dims, strides, box, es, CU_TENSOR_MAP_INTERLEAVE_NONE, sw, PROMO,
      CU_TENSOR_MAP_FLOAT_OOB_FILL_NONE);
}
void map_blk(EncFn enc, CUtensorMap* tm, const void* base, int rows, int cols, int brows, int bblk) {
  const cuuint64_t d[3] = {64, (cuuint64_t)rows, (cuuint64_t)cols / 64}, st[2] = {(cuuint64_t)cols * 2, 128};
  const cuuint32_t b[3] = {64, (cuuint32_t)brows, (cuuint32_t)bblk};
  make_map(enc, tm, base, 3, d, st, b);
}
void map_2d(EncFn enc, CUtensorMap* tm, const void* base, int rows, int cols, int brows, int bcols, CUtensorMapSwizzle sw) {
  const cuuint64_t d[2] = {(cuuint64_t)cols, (cuuint64_t)rows}, st[1] = {(cuuint64_t)cols * 2};
  const cuuint32_t b[2] = {(cuuint32_t)bcols, (cuuint32_t)brows};
  make_map(enc, tm, base, 2, d, st, b, sw);
}

}

extern "C" void kernel_launch(void* const* d_in, const int* in_sizes, int n_in, void* d_out, int out_size) {
  const bf16* x = (const bf16*)d_in[0];
  const bf16* mem0 = (const bf16*)d_in[1];
  const bf16* Wq = (const bf16*)d_in[2];
  const bf16* Wk = (const bf16*)d_in[3];
  const bf16* Wv = (const bf16*)d_in[4];
  const bf16* Wo = (const bf16*)d_in[5];
  const bf16* wqkv = (const bf16*)d_in[8];
  const bf16* wob = (const bf16*)d_in[9];
  const bf16* gate_w = (const bf16*)d_in[10];
  static EncFn enc = nullptr;
  static void *pR = nullptr, *pK = nullptr, *pV = nullptr, *pO = nullptr, *pQ = nullptr, *pB = nullptr;
  if (!enc) {
    void* fn = nullptr;
    cudaDriverEntryPointQueryResult qr;
    cudaGetDriverEntryPoint("cuTensorMapEncodeTiled", &fn, cudaEnableDefault, &qr);
    enc = (EncFn)fn;
    cudaGetSymbolAddress(&pR, g_red);
    cudaGetSymbolAddress(&pK, g_K);
    cudaGetSymbolAddress(&pV, g_V);
    cudaGetSymbolAddress(&pO, g_O);
    cudaGetSymbolAddress(&pQ, g_qkv);
    cudaGetSymbolAddress(&pB, g_Ob);
    cudaFuncSetAttribute(rec_kernel, cudaFuncAttributeMaxDynamicSharedMemorySize, R_SMEM_ALLOC);
    cudaFuncSetAttribute(aux_kernel, cudaFuncAttributeMaxDynamicSharedMemorySize, A_SMEM);
  }
  CUtensorMap tmX, tmK, tmV, tmWq, tmWq2, tmWk, tmWv, tmWo;
  map_2d(enc, &tmWq, Wq, DM, HD, 144, 64, CU_TENSOR_MAP_SWIZZLE_128B);
  map_2d(enc, &tmWq2, Wq, DM, HD, 32, 64, CU_TENSOR_MAP_SWIZZLE_128B);
  map_2d(enc, &tmWk, Wk, DM, HD, 128, 64, CU_TENSOR_MAP_SWIZZLE_128B);
  map_2d(enc, &tmWv, Wv, DM, HD, 128, 64, CU_TENSOR_MAP_SWIZZLE_128B);
  {
    const cuuint64_t d[3] = {32, HD, 20}, st[2] = {DM * 2, 64};
    const cuuint32_t b[3] = {32, 64, 7};
    make_map(enc, &tmWo, Wo, 3, d, st, b, CU_TENSOR_MAP_SWIZZLE_64B);
  }
  map_blk(enc, &tmX, x, S_TOK, DM, 32, 10);
  map_2d(enc, &tmK, pK, NSEG * LK, HD, LK, 64, CU_TENSOR_MAP_SWIZZLE_128B);
  map_2d(enc, &tmV, pV, NSEG * LK, HD, LK, 64, CU_TENSOR_MAP_SWIZZLE_128B);
  AuxMaps am;
  map_2d(enc, &am.xA, x, S_TOK, DM, 128, 32, CU_TENSOR_MAP_SWIZZLE_64B);
  map_blk(enc, &am.wq, Wq, DM, HD, 32, 6);
  map_blk(enc, &am.wqkv, wqkv, DM, 3 * DM, 32, 6);
  map_blk(enc, &am.wo, Wo, HD, DM, 32, 5);
  map_blk(enc, &am.wob, wob, DM, DM, 32, 5);
  map_blk(enc, &am.k, pK, NSEG * LK, HD, 80, 3);
  map_blk(enc, &am.v, pV, NSEG * LK, HD, 80, 3);
  map_2d(enc, &am.oA, pO, S_TOK, HD, 128, 32, CU_TENSOR_MAP_SWIZZLE_64B);
  map_blk(enc, &am.oS, pO, S_TOK, HD, 64, 3);
  map_2d(enc, &am.obA, pB, S_TOK, DM, 128, 32, CU_TENSOR_MAP_SWIZZLE_64B);
  map_2d(enc, &am.obS, pB, S_TOK, DM, 64, 160, CU_TENSOR_MAP_SWIZZLE_NONE);
  map_blk(enc, &am.qkvS, pQ, S_TOK, 3 * DM, 64, 3);
  map_2d(enc, &am.qkvQ, pQ, S_TOK, 3 * DM, 64, 160, CU_TENSOR_MAP_SWIZZLE_NONE);
  map_2d(enc, &am.qkvK, pQ, S_TOK, 3 * DM, 80, 160, CU_TENSOR_MAP_SWIZZLE_NONE);
  map_blk(enc, &am.out, d_out, S_TOK, DM, 64, 1);
  rec_kernel<<<96, 256, R_SMEM_ALLOC, cudaStreamPerThread>>>(tmX, tmK, tmV, tmWq, tmWq2, tmWk, tmWv, tmWo, mem0, Wq, Wo, x,
                                                               (unsigned char*)(((uintptr_t)pR + 0x1fffff) & ~(uintptr_t)0x1fffff));
  cudaLaunchConfig_t cfg = {};
  cfg.gridDim = dim3(AUX_GRID); cfg.blockDim = dim3(384); cfg.dynamicSmemBytes = A_SMEM; cfg.stream = cudaStreamPerThread;
  cudaLaunchAttribute at[1];
  at[0].id = cudaLaunchAttributeProgrammaticStreamSerialization;
  at[0].val.programmaticStreamSerializationAllowed = 1;
  cfg.attrs = at;
  cfg.numAttrs = 1;
  cudaLaunchKernelEx(&cfg, aux_kernel, am, x, gate_w);
}
```

```cpp
#include <cuda_runtime.h>
#include <cuda_bf16.h>
#include <cuda.h>
#include <stdint.h>
#include <type_traits>

typedef __nv_bfloat16 bf16;

namespace {

constexpr int S_TOK = 2048, DM = 640, NH = 32, DH = 192, HD = NH * DH, SEG = 32, NSEG = 64, MT = 8, LK = 40;
constexpr int SPIN_MAX = 1 << 20;

__device__ __align__(4096) unsigned char g_red[(2 << 20) + (640 << 10)];
__host__ __device__ constexpr uint32_t rb_q(int q) { return (q < 5 ? q : q - 5) * 131072 + (uint32_t)((0x3122120330ull >> 4 * q) & 15) * 2048; }
__host__ __device__ constexpr uint32_t rb_j(int j) { return (j & 1) * 256 + (j & 2) * 512 + (j & 12) * 2048; }
__host__ __device__ constexpr uint32_t rb_b(int b) { return (b & 1) * 128 + (b & 2) * 256; }
__device__ unsigned long long g_rec[96];
__device__ uint32_t g_epoch;
__device__ uint32_t g_err;
__device__ __align__(16) uint32_t g_segcnt[NSEG];
__device__ __align__(1024) bf16 g_K[NSEG * LK * HD];
__device__ __align__(1024) bf16 g_V[NSEG * LK * HD];
__device__ __align__(1024) bf16 g_O[S_TOK * HD];
__device__ __align__(1024) bf16 g_qkv[S_TOK * 3 * DM];
__device__ __align__(1024) bf16 g_Ob[S_TOK * DM];
__device__ float g_gate[2 * S_TOK];
__device__ uint32_t g_cnt[512 * 8];
__device__ __align__(128) uint32_t g_queue[3 * 32];
__device__ uint32_t g_prog;
#define GTR(i) do {} while (0)
#define GTA(i) do {} while (0)
#define PTR(c, r, k) do {} while (0)

__device__ __forceinline__ uint32_t smem_u32(const void* p) { return (uint32_t)__cvta_generic_to_shared(p); }
__device__ __forceinline__ uint32_t clk32() { uint32_t t; asm volatile("mov.u32 %0, %%clock;" : "=r"(t)::"memory"); return t; }
__device__ __forceinline__ uint32_t mapa(uint32_t a, uint32_t r) { uint32_t o; asm("mapa.shared::cluster.u32 %0, %1, %2;" : "=r"(o) : "r"(a), "r"(r)); return o; }
__device__ __forceinline__ void mbar_init(uint32_t b, uint32_t c) { asm volatile("mbarrier.init.shared::cta.b64 [%0], %1;" ::"r"(b), "r"(c) : "memory"); }
__device__ __forceinline__ void mbar_expect(uint32_t b, uint32_t bytes) { asm volatile("mbarrier.arrive.expect_tx.shared::cta.b64 _, [%0], %1;" ::"r"(b), "r"(bytes) : "memory"); }
__device__ __forceinline__ void mbar_arrive(uint32_t b) { asm volatile("mbarrier.arrive.shared::cta.b64 _, [%0];" ::"r"(b) : "memory"); }
__device__ __forceinline__ bool mbar_try(uint32_t b, uint32_t par) {
  uint32_t p;
  asm volatile("{.reg .pred p; mbarrier.try_wait.parity.shared::cta.b64 p, [%1], %2; selp.u32 %0,1,0,p;}" : "=r"(p) : "r"(b), "r"(par) : "memory");
  return p;
}
__device__ __forceinline__ bool mbar_test(uint32_t b, uint32_t par) {
  uint32_t p;
  asm volatile("{.reg .pred p; mbarrier.test_wait.parity.shared::cta.b64 p, [%1], %2; selp.u32 %0,1,0,p;}" : "=r"(p) : "r"(b), "r"(par) : "memory");
  return p;
}
__device__ __forceinline__ bool mbar_try_cl(uint32_t b, uint32_t par) {
  uint32_t p;
  asm volatile("{.reg .pred p; mbarrier.try_wait.parity.acquire.cluster.shared::cta.b64 p, [%1], %2; selp.u32 %0,1,0,p;}" : "=r"(p) : "r"(b), "r"(par) : "memory");
  return p;
}
__device__ __forceinline__ void mbar_wait(uint32_t b, uint32_t par) {
  int n = 0;
#pragma unroll 1
  while (!mbar_try(b, par)) { if (++n > SPIN_MAX) { g_err = 1; break; } }
}
__device__ __forceinline__ void mbar_wait_cl(uint32_t b, uint32_t par) {
  int n = 0;
#pragma unroll 1
  while (!mbar_try_cl(b, par)) { if (++n > SPIN_MAX) { g_err = 2; break; } }
}
__device__ __forceinline__ void cluster_sync() { asm volatile("barrier.cluster.arrive.release.aligned; barrier.cluster.wait.acquire.aligned;" ::: "memory"); }
__device__ __forceinline__ void bar_sync(int id, int n) { asm volatile("bar.sync %0, %1;" ::"r"(id), "r"(n) : "memory"); }
__device__ __forceinline__ void bar_arrive(int id, int n) { asm volatile("bar.arrive %0, %1;" ::"r"(id), "r"(n) : "memory"); }
__device__ __forceinline__ void fence_async_smem() { asm volatile("fence.proxy.async.shared::cta;" ::: "memory"); }
__device__ __forceinline__ void ldsm4(uint32_t* r, uint32_t a) {
  asm volatile("ldmatrix.sync.aligned.m8n8.x4.shared.b16 {%0,%1,%2,%3}, [%4];" : "=r"(r[0]), "=r"(r[1]), "=r"(r[2]), "=r"(r[3]) : "r"(a) : "memory");
}
__device__ __forceinline__ void ldsm4t(uint32_t* r, uint32_t a) {
  asm volatile("ldmatrix.sync.aligned.m8n8.x4.trans.shared.b16 {%0,%1,%2,%3}, [%4];" : "=r"(r[0]), "=r"(r[1]), "=r"(r[2]), "=r"(r[3]) : "r"(a) : "memory");
}
__device__ __forceinline__ void ldsm2t(uint32_t* r, uint32_t a) {
  asm volatile("ldmatrix.sync.aligned.m8n8.x2.trans.shared.b16 {%0,%1}, [%2];" : "=r"(r[0]), "=r"(r[1]) : "r"(a) : "memory");
}
__device__ __forceinline__ void stsm4t(uint32_t a, uint32_t r0, uint32_t r1, uint32_t r2, uint32_t r3) {
  asm volatile("stmatrix.sync.aligned.m8n8.x4.trans.shared.b16 [%0], {%1,%2,%3,%4};" ::"r"(a), "r"(r0), "r"(r1), "r"(r2), "r"(r3) : "memory");
}
__device__ __forceinline__ void stsm2t(uint32_t a, uint32_t r0, uint32_t r1) {
  asm volatile("stmatrix.sync.aligned.m8n8.x2.trans.shared.b16 [%0], {%1,%2};" ::"r"(a), "r"(r0), "r"(r1) : "memory");
}
__device__ __forceinline__ uint32_t movmat(uint32_t a) { uint32_t d; asm volatile("movmatrix.sync.aligned.m8n8.trans.b16 %0, %1;" : "=r"(d) : "r"(a)); return d; }
__device__ __forceinline__ void mma16816(float* d, const uint32_t* a, uint32_t b0, uint32_t b1) {
  asm volatile("mma.sync.aligned.m16n8k16.row.col.f32.bf16.bf16.f32 {%0,%1,%2,%3}, {%4,%5,%6,%7}, {%8,%9}, {%0,%1,%2,%3};"
               : "+f"(d[0]), "+f"(d[1]), "+f"(d[2]), "+f"(d[3]) : "r"(a[0]), "r"(a[1]), "r"(a[2]), "r"(a[3]), "r"(b0), "r"(b1));
}
__device__ __forceinline__ void mma1688(float* d, uint32_t a0, uint32_t a1, uint32_t b0) {
  asm volatile("mma.sync.aligned.m16n8k8.row.col.f32.bf16.bf16.f32 {%0,%1,%2,%3}, {%4,%5}, {%6}, {%0,%1,%2,%3};"
               : "+f"(d[0]), "+f"(d[1]), "+f"(d[2]), "+f"(d[3]) : "r"(a0), "r"(a1), "r"(b0));
}
__device__ __forceinline__ uint32_t pack2(float lo, float hi) { uint32_t r; asm("cvt.rn.bf16x2.f32 %0, %1, %2;" : "=r"(r) : "f"(hi), "f"(lo)); return r; }
__device__ __forceinline__ float bf_lo(uint32_t w) { return __uint_as_float(w << 16); }
__device__ __forceinline__ float bf_hi(uint32_t w) { return __uint_as_float(w & 0xffff0000u); }
__device__ __forceinline__ float ex2(float x) { float y; asm("ex2.approx.ftz.f32 %0, %1;" : "=f"(y) : "f"(x)); return y; }
__device__ __forceinline__ void sts128(uint32_t a, uint32_t x, uint32_t y, uint32_t z, uint32_t w) { asm volatile("st.shared.v4.b32 [%0], {%1,%2,%3,%4};" ::"r"(a), "r"(x), "r"(y), "r"(z), "r"(w) : "memory"); }
__device__ __forceinline__ void sts128f(uint32_t a, float x, float y, float z, float w) { asm volatile("st.shared.v4.f32 [%0], {%1,%2,%3,%4};" ::"r"(a), "f"(x), "f"(y), "f"(z), "f"(w) : "memory"); }
__device__ __forceinline__ void sts64f(uint32_t a, float x, float y) { asm volatile("st.shared.v2.f32 [%0], {%1,%2};" ::"r"(a), "f"(x), "f"(y) : "memory"); }
__device__ __forceinline__ void sts32(uint32_t a, uint32_t x) { asm volatile("st.shared.b32 [%0], %1;" ::"r"(a), "r"(x) : "memory"); }
__device__ __forceinline__ void smax32(uint32_t a, uint32_t x) { asm volatile("red.shared.max.u32 [%0], %1;" ::"r"(a), "r"(x) : "memory"); }
__device__ __forceinline__ uint32_t lds32(uint32_t a) { uint32_t v; asm volatile("ld.shared.b32 %0, [%1];" : "=r"(v) : "r"(a) : "memory"); return v; }
__device__ __forceinline__ float4 lds128f(uint32_t a) { float4 v; asm volatile("ld.shared.v4.f32 {%0,%1,%2,%3}, [%4];" : "=f"(v.x), "=f"(v.y), "=f"(v.z), "=f"(v.w) : "r"(a) : "memory"); return v; }
__device__ __forceinline__ uint4 lds128(uint32_t a) { uint4 v; asm volatile("ld.shared.v4.b32 {%0,%1,%2,%3}, [%4];" : "=r"(v.x), "=r"(v.y), "=r"(v.z), "=r"(v.w) : "r"(a) : "memory"); return v; }
__device__ __forceinline__ float2 lds64f(uint32_t a) { float2 v; asm volatile("ld.shared.v2.f32 {%0,%1}, [%2];" : "=f"(v.x), "=f"(v.y) : "r"(a) : "memory"); return v; }
__device__ __forceinline__ void st_async2(uint32_t a, uint32_t x, uint32_t y, uint32_t bar) {
  asm volatile("st.async.weak.shared::cluster.mbarrier::complete_tx::bytes.v2.b32 [%0], {%1,%2}, [%3];" ::"r"(a), "r"(x), "r"(y), "r"(bar) : "memory");
}
__device__ __forceinline__ void st_async4(uint32_t a, uint32_t x, uint32_t y, uint32_t z, uint32_t w, uint32_t bar) {
  asm volatile("st.async.weak.shared::cluster.mbarrier::complete_tx::bytes.v4.b32 [%0], {%1,%2,%3,%4}, [%5];" ::"r"(a), "r"(x), "r"(y), "r"(z), "r"(w), "r"(bar) : "memory");
}
__device__ __forceinline__ void sts64(uint32_t a, uint32_t x, uint32_t y) { asm volatile("st.shared.v2.b32 [%0], {%1,%2};" ::"r"(a), "r"(x), "r"(y) : "memory"); }
__device__ __forceinline__ bool bar_red_or(int id, int n, bool q) {
  uint32_t r;
  asm volatile("{.reg .pred p, q; setp.ne.u32 q, %3, 0; barrier.cta.red.or.aligned.pred p, %1, %2, q; selp.u32 %0,1,0,p;}" : "=r"(r) : "r"(id), "r"(n), "r"((uint32_t)q) : "memory");
  return r;
}
__device__ __forceinline__ float rcp(float x) { float y; asm("rcp.approx.ftz.f32 %0, %1;" : "=f"(y) : "f"(x)); return y; }
__device__ __forceinline__ uint32_t hadd2(uint32_t a, uint32_t b) { uint32_t r; asm("add.rn.bf16x2 %0, %1, %2;" : "=r"(r) : "r"(a), "r"(b)); return r; }
__device__ __forceinline__ uint32_t pin(uint32_t v) { asm volatile("" : "+r"(v)); return v; }
template <int ID> __device__ __forceinline__ void sched_fence_(uint32_t a) {
  asm volatile("{.reg .pred p;\nsetp.eq.u32 p, %0, %1;\nSF: @p pmevent 0;\n@p bra.uni SF;}" ::"r"(a), "n"(0x40000000 + ID) : "memory");
}
#define sched_fence(a) sched_fence_<__LINE__>(a)
__device__ __forceinline__ bool elect() {
  uint32_t p;
  asm volatile("{.reg .pred p; elect.sync _|p, 0xffffffff; selp.u32 %0,1,0,p;}" : "=r"(p));
  return p;
}
__device__ __forceinline__ uint32_t opaque(uint32_t v) { return __shfl_sync(~0u, v, threadIdx.x & 31); }
__device__ __forceinline__ uint4 ldg_rlx128(const void* p) {
  uint4 v; asm volatile("ld.relaxed.gpu.global.v4.b32 {%0,%1,%2,%3}, [%4];" : "=r"(v.x), "=r"(v.y), "=r"(v.z), "=r"(v.w) : "l"(p) : "memory"); return v;
}
__device__ __forceinline__ uint2 ldg_rlx64(const void* p) {
  uint2 v; asm volatile("{.reg .b64 t; ld.relaxed.gpu.global.b64 t, [%2]; mov.b64 {%0,%1}, t;}" : "=r"(v.x), "=r"(v.y) : "l"(p) : "memory"); return v;
}
__device__ __forceinline__ uint32_t hmaxabs2(uint32_t a, uint32_t b) { uint32_t r; asm("max.xorsign.abs.bf16x2 %0, %1, %2;" : "=r"(r) : "r"(a), "r"(b)); return r; }
__device__ __forceinline__ uint32_t ldg_rlx32(const void* p) {
  uint32_t v; asm volatile("ld.relaxed.gpu.global.b32 %0, [%1];" : "=r"(v) : "l"(p) : "memory"); return v;
}
__device__ __forceinline__ float ldg_cg(const float* p) { float v; asm volatile("ld.global.cg.f32 %0, [%1];" : "=f"(v) : "l"(p) : "memory"); return v; }
__device__ __forceinline__ void spin_until(uint32_t t0, int d) {
#pragma unroll 1
  while ((int)(clk32() - t0) < d) {}
}
__device__ __forceinline__ void stg_rlx64(void* p, uint32_t a, uint32_t b) {
  asm volatile("{.reg .b64 t; mov.b64 t, {%1,%2}; st.relaxed.gpu.global.b64 [%0], t;}" ::"l"(p), "r"(a), "r"(b) : "memory");
}
__device__ __forceinline__ uint32_t ldg_acq32(const void* p) { uint32_t v; asm volatile("ld.acquire.gpu.global.b32 %0, [%1];" : "=r"(v) : "l"(p) : "memory"); return v; }
__device__ __forceinline__ void stg_rel32(void* p, uint32_t v) { asm volatile("st.release.gpu.global.b32 [%0], %1;" ::"l"(p), "r"(v) : "memory"); }
__device__ __forceinline__ void cp_async16(uint32_t dst, const void* src) { asm volatile("cp.async.cg.shared.global [%0], [%1], 16;" ::"r"(dst), "l"(src) : "memory"); }
__device__ __forceinline__ void cp_async_wait_all() { asm volatile("cp.async.wait_all;" ::: "memory"); }
__device__ __forceinline__ void prefetch_l2(const void* p) { asm volatile("prefetch.global.L2 [%0];" ::"l"(p)); }
__device__ __forceinline__ void tma_load3(uint32_t dst, const CUtensorMap* tm, int c0, int c1, int c2, uint32_t bar) {
  asm volatile("cp.async.bulk.tensor.3d.shared::cluster.global.mbarrier::complete_tx::bytes [%0], [%1, {%3,%4,%5}], [%2];"
               ::"r"(dst), "l"(tm), "r"(bar), "r"(c0), "r"(c1), "r"(c2) : "memory");
}
__device__ __forceinline__ void tma_load2(uint32_t dst, const CUtensorMap* tm, int c0, int c1, uint32_t bar) {
  asm volatile("cp.async.bulk.tensor.2d.shared::cluster.global.mbarrier::complete_tx::bytes [%0], [%1, {%3,%4}], [%2];"
               ::"r"(dst), "l"(tm), "r"(bar), "r"(c0), "r"(c1) : "memory");
}
__device__ __forceinline__ void bulk_load(uint32_t dst, const void* src, uint32_t bytes, uint32_t bar) {
  asm volatile("cp.async.bulk.shared::cluster.global.mbarrier::complete_tx::bytes [%0], [%1], %2, [%3];" ::"r"(dst), "l"(src), "r"(bytes), "r"(bar) : "memory");
}
__device__ __forceinline__ void bulk_s2s(uint32_t dst, uint32_t src, uint32_t bytes, uint32_t bar) {
  asm volatile("cp.async.bulk.shared::cluster.shared::cta.mbarrier::complete_tx::bytes [%0], [%1], %2, [%3];" ::"r"(dst), "r"(src), "r"(bytes), "r"(bar) : "memory");
}
__device__ __forceinline__ void prefetch_map(const CUtensorMap* tm) { asm volatile("prefetch.tensormap [%0];" ::"l"(tm) : "memory"); }
__device__ __forceinline__ void tma_store2(const CUtensorMap* tm, uint32_t src, int c0, int c1) {
  asm volatile("cp.async.bulk.tensor.2d.global.shared::cta.bulk_group [%0, {%2,%3}], [%1];" ::"l"(tm), "r"(src), "r"(c0), "r"(c1) : "memory");
}
__device__ __forceinline__ void bulk_commit() { asm volatile("cp.async.bulk.commit_group;" ::: "memory"); }
__device__ __forceinline__ void bulk_wait0() { asm volatile("cp.async.bulk.wait_group 0;" ::: "memory"); }
__device__ __forceinline__ void bulk_wait_read0() { asm volatile("cp.async.bulk.wait_group.read 0;" ::: "memory"); }
__device__ __forceinline__ void wg_fence() { asm volatile("wgmma.fence.sync.aligned;" ::: "memory"); }
__device__ __forceinline__ void wg_commit() { asm volatile("wgmma.commit_group.sync.aligned;" ::: "memory"); }
__device__ __forceinline__ void wg_wait0() { asm volatile("wgmma.wait_group.sync.aligned 0;" ::: "memory"); }
__device__ __forceinline__ uint64_t desc_sw128(uint32_t addr) {
  return (uint64_t)((addr & 0x3FFFF) >> 4) | ((uint64_t)1 << 16) | ((uint64_t)64 << 32) | ((uint64_t)1 << 62);
}
template <int ACC>
__device__ __forceinline__ void wgmma_rs32(float* d, const uint32_t* a, uint64_t db) {
  asm volatile("{.reg .pred p; setp.ne.b32 p, %21, 0;\n"
               "wgmma.mma_async.sync.aligned.m64n32k16.f32.bf16.bf16 {%0,%1,%2,%3,%4,%5,%6,%7,%8,%9,%10,%11,%12,%13,%14,%15}, {%16,%17,%18,%19}, %20, p, 1, 1, 0;}"
               : "+f"(d[0]), "+f"(d[1]), "+f"(d[2]), "+f"(d[3]), "+f"(d[4]), "+f"(d[5]), "+f"(d[6]), "+f"(d[7]), "+f"(d[8]), "+f"(d[9]),
                 "+f"(d[10]), "+f"(d[11]), "+f"(d[12]), "+f"(d[13]), "+f"(d[14]), "+f"(d[15])
               : "r"(a[0]), "r"(a[1]), "r"(a[2]), "r"(a[3]), "l"(db), "n"(ACC));
}

template <int N> __device__ __forceinline__ void fence_regs(float* d) {
#pragma unroll
  for (int i = 0; i < N; i++) asm volatile("" : "+f"(d[i])::"memory");
}
__device__ __forceinline__ void wg_wait1() { asm volatile("wgmma.wait_group.sync.aligned 1;" ::: "memory"); }
__device__ __forceinline__ void tma_store3(const CUtensorMap* tm, uint32_t src, int c0, int c1, int c2) {
  asm volatile("cp.async.bulk.tensor.3d.global.shared::cta.bulk_group [%0, {%2,%3,%4}], [%1];" ::"l"(tm), "r"(src), "r"(c0), "r"(c1), "r"(c2) : "memory");
}
__device__ __forceinline__ void tma_red3(const CUtensorMap* tm, uint32_t src, int c0, int c1, int c2) {
  asm volatile("cp.reduce.async.bulk.tensor.3d.global.shared::cta.add.bulk_group [%0, {%2,%3,%4}], [%1];" ::"l"(tm), "r"(src), "r"(c0), "r"(c1), "r"(c2) : "memory");
}
__device__ __forceinline__ void stsm4(uint32_t a, uint32_t r0, uint32_t r1, uint32_t r2, uint32_t r3) {
  asm volatile("stmatrix.sync.aligned.m8n8.x4.shared.b16 [%0], {%1,%2,%3,%4};" ::"r"(a), "r"(r0), "r"(r1), "r"(r2), "r"(r3) : "memory");
}
__device__ __forceinline__ uint2 lds64(uint32_t a) { uint2 v; asm volatile("ld.shared.v2.b32 {%0,%1}, [%2];" : "=r"(v.x), "=r"(v.y) : "r"(a) : "memory"); return v; }
__device__ __forceinline__ uint32_t hmul2(uint32_t a, uint32_t b) { uint32_t r; asm("mul.rn.bf16x2 %0, %1, %2;" : "=r"(r) : "r"(a), "r"(b)); return r; }
__device__ __forceinline__ void wgmma_ss192t(float* d, uint64_t da, uint64_t db, int acc) {
  asm volatile("{.reg .pred p; setp.ne.b32 p, %98, 0;\n"
    "wgmma.mma_async.sync.aligned.m64n192k16.f32.bf16.bf16 "
    "{%0,%1,%2,%3,%4,%5,%6,%7,%8,%9,%10,%11,%12,%13,%14,%15,%16,%17,%18,%19,%20,%21,%22,%23,%24,%25,%26,%27,%28,%29,%30,%31,%32,%33,%34,%35,%36,%37,%38,%39,%40,%41,%42,%43,%44,%45,%46,%47,%48,%49,%50,%51,%52,%53,%54,%55,%56,%57,%58,%59,%60,%61,%62,%63,%64,%65,%66,%67,%68,%69,%70,%71,%72,%73,%74,%75,%76,%77,%78,%79,%80,%81,%82,%83,%84,%85,%86,%87,%88,%89,%90,%91,%92,%93,%94,%95}, %96, %97, p, 1, 1, 0, 1;}"
    : "+f"(d[0]), "+f"(d[1]), "+f"(d[2]), "+f"(d[3]), "+f"(d[4]), "+f"(d[5]), "+f"(d[6]), "+f"(d[7]), "+f"(d[8]), "+f"(d[9]), "+f"(d[10]), "+f"(d[11]),
      "+f"(d[12]), "+f"(d[13]), "+f"(d[14]), "+f"(d[15]), "+f"(d[16]), "+f"(d[17]), "+f"(d[18]), "+f"(d[19]), "+f"(d[20]), "+f"(d[21]), "+f"(d[22]),
      "+f"(d[23]), "+f"(d[24]), "+f"(d[25]), "+f"(d[26]), "+f"(d[27]), "+f"(d[28]), "+f"(d[29]), "+f"(d[30]), "+f"(d[31]), "+f"(d[32]), "+f"(d[33]),
      "+f"(d[34]), "+f"(d[35]), "+f"(d[36]), "+f"(d[37]), "+f"(d[38]), "+f"(d[39]), "+f"(d[40]), "+f"(d[41]), "+f"(d[42]), "+f"(d[43]), "+f"(d[44]),
      "+f"(d[45]), "+f"(d[46]), "+f"(d[47]), "+f"(d[48]), "+f"(d[49]), "+f"(d[50]), "+f"(d[51]), "+f"(d[52]), "+f"(d[53]), "+f"(d[54]), "+f"(d[55]),
      "+f"(d[56]), "+f"(d[57]), "+f"(d[58]), "+f"(d[59]), "+f"(d[60]), "+f"(d[61]), "+f"(d[62]), "+f"(d[63]), "+f"(d[64]), "+f"(d[65]), "+f"(d[66]),
      "+f"(d[67]), "+f"(d[68]), "+f"(d[69]), "+f"(d[70]), "+f"(d[71]), "+f"(d[72]), "+f"(d[73]), "+f"(d[74]), "+f"(d[75]), "+f"(d[76]), "+f"(d[77]),
      "+f"(d[78]), "+f"(d[79]), "+f"(d[80]), "+f"(d[81]), "+f"(d[82]), "+f"(d[83]), "+f"(d[84]), "+f"(d[85]), "+f"(d[86]), "+f"(d[87]), "+f"(d[88]),
      "+f"(d[89]), "+f"(d[90]), "+f"(d[91]), "+f"(d[92]), "+f"(d[93]), "+f"(d[94]), "+f"(d[95])
    : "l"(da), "l"(db), "r"(acc));
}
__device__ __forceinline__ void wgmma_rs128t(float* d, const uint32_t* a, uint64_t db, int acc) {
  asm volatile("{.reg .pred p; setp.ne.b32 p, %69, 0;\n"
    "wgmma.mma_async.sync.aligned.m64n128k16.f32.bf16.bf16 "
    "{%0,%1,%2,%3,%4,%5,%6,%7,%8,%9,%10,%11,%12,%13,%14,%15,%16,%17,%18,%19,%20,%21,%22,%23,%24,%25,%26,%27,%28,%29,%30,%31,%32,%33,%34,%35,%36,%37,%38,%39,%40,%41,%42,%43,%44,%45,%46,%47,%48,%49,%50,%51,%52,%53,%54,%55,%56,%57,%58,%59,%60,%61,%62,%63}, {%64,%65,%66,%67}, %68, p, 1, 1, 1;}"
    : "+f"(d[0]), "+f"(d[1]), "+f"(d[2]), "+f"(d[3]), "+f"(d[4]), "+f"(d[5]), "+f"(d[6]), "+f"(d[7]), "+f"(d[8]), "+f"(d[9]), "+f"(d[10]), "+f"(d[11]),
      "+f"(d[12]), "+f"(d[13]), "+f"(d[14]), "+f"(d[15]), "+f"(d[16]), "+f"(d[17]), "+f"(d[18]), "+f"(d[19]), "+f"(d[20]), "+f"(d[21]), "+f"(d[22]),
      "+f"(d[23]), "+f"(d[24]), "+f"(d[25]), "+f"(d[26]), "+f"(d[27]), "+f"(d[28]), "+f"(d[29]), "+f"(d[30]), "+f"(d[31]), "+f"(d[32]), "+f"(d[33]),
      "+f"(d[34]), "+f"(d[35]), "+f"(d[36]), "+f"(d[37]), "+f"(d[38]), "+f"(d[39]), "+f"(d[40]), "+f"(d[41]), "+f"(d[42]), "+f"(d[43]), "+f"(d[44]),
      "+f"(d[45]), "+f"(d[46]), "+f"(d[47]), "+f"(d[48]), "+f"(d[49]), "+f"(d[50]), "+f"(d[51]), "+f"(d[52]), "+f"(d[53]), "+f"(d[54]), "+f"(d[55]),
      "+f"(d[56]), "+f"(d[57]), "+f"(d[58]), "+f"(d[59]), "+f"(d[60]), "+f"(d[61]), "+f"(d[62]), "+f"(d[63])
    : "r"(a[0]), "r"(a[1]), "r"(a[2]), "r"(a[3]), "l"(db), "r"(acc));
}
__device__ __forceinline__ void wgmma_rs80(float* d, const uint32_t* a, uint64_t db, int acc) {
  asm volatile("{.reg .pred p; setp.ne.b32 p, %45, 0;\n"
    "wgmma.mma_async.sync.aligned.m64n80k16.f32.bf16.bf16 "
    "{%0,%1,%2,%3,%4,%5,%6,%7,%8,%9,%10,%11,%12,%13,%14,%15,%16,%17,%18,%19,%20,%21,%22,%23,%24,%25,%26,%27,%28,%29,%30,%31,%32,%33,%34,%35,%36,%37,%38,%39}, {%40,%41,%42,%43}, %44, p, 1, 1, 0;}"
    : "+f"(d[0]), "+f"(d[1]), "+f"(d[2]), "+f"(d[3]), "+f"(d[4]), "+f"(d[5]), "+f"(d[6]), "+f"(d[7]), "+f"(d[8]), "+f"(d[9]), "+f"(d[10]), "+f"(d[11]),
      "+f"(d[12]), "+f"(d[13]), "+f"(d[14]), "+f"(d[15]), "+f"(d[16]), "+f"(d[17]), "+f"(d[18]), "+f"(d[19]), "+f"(d[20]), "+f"(d[21]), "+f"(d[22]),
      "+f"(d[23]), "+f"(d[24]), "+f"(d[25]), "+f"(d[26]), "+f"(d[27]), "+f"(d[28]), "+f"(d[29]), "+f"(d[30]), "+f"(d[31]), "+f"(d[32]), "+f"(d[33]),
      "+f"(d[34]), "+f"(d[35]), "+f"(d[36]), "+f"(d[37]), "+f"(d[38]), "+f"(d[39])
    : "r"(a[0]), "r"(a[1]), "r"(a[2]), "r"(a[3]), "l"(db), "r"(acc));
}
__device__ __forceinline__ void wgmma_rs192t(float* d, const uint32_t* a, uint64_t db, int acc) {
  asm volatile("{.reg .pred p; setp.ne.b32 p, %101, 0;\n"
    "wgmma.mma_async.sync.aligned.m64n192k16.f32.bf16.bf16 "
    "{%0,%1,%2,%3,%4,%5,%6,%7,%8,%9,%10,%11,%12,%13,%14,%15,%16,%17,%18,%19,%20,%21,%22,%23,%24,%25,%26,%27,%28,%29,%30,%31,%32,%33,%34,%35,%36,%37,%38,%39,%40,%41,%42,%43,%44,%45,%46,%47,%48,%49,%50,%51,%52,%53,%54,%55,%56,%57,%58,%59,%60,%61,%62,%63,%64,%65,%66,%67,%68,%69,%70,%71,%72,%73,%74,%75,%76,%77,%78,%79,%80,%81,%82,%83,%84,%85,%86,%87,%88,%89,%90,%91,%92,%93,%94,%95}, {%96,%97,%98,%99}, %100, p, 1, 1, 1;}"
    : "+f"(d[0]), "+f"(d[1]), "+f"(d[2]), "+f"(d[3]), "+f"(d[4]), "+f"(d[5]), "+f"(d[6]), "+f"(d[7]), "+f"(d[8]), "+f"(d[9]), "+f"(d[10]), "+f"(d[11]),
      "+f"(d[12]), "+f"(d[13]), "+f"(d[14]), "+f"(d[15]), "+f"(d[16]), "+f"(d[17]), "+f"(d[18]), "+f"(d[19]), "+f"(d[20]), "+f"(d[21]), "+f"(d[22]),
      "+f"(d[23]), "+f"(d[24]), "+f"(d[25]), "+f"(d[26]), "+f"(d[27]), "+f"(d[28]), "+f"(d[29]), "+f"(d[30]), "+f"(d[31]), "+f"(d[32]), "+f"(d[33]),
      "+f"(d[34]), "+f"(d[35]), "+f"(d[36]), "+f"(d[37]), "+f"(d[38]), "+f"(d[39]), "+f"(d[40]), "+f"(d[41]), "+f"(d[42]), "+f"(d[43]), "+f"(d[44]),
      "+f"(d[45]), "+f"(d[46]), "+f"(d[47]), "+f"(d[48]), "+f"(d[49]), "+f"(d[50]), "+f"(d[51]), "+f"(d[52]), "+f"(d[53]), "+f"(d[54]), "+f"(d[55]),
      "+f"(d[56]), "+f"(d[57]), "+f"(d[58]), "+f"(d[59]), "+f"(d[60]), "+f"(d[61]), "+f"(d[62]), "+f"(d[63]), "+f"(d[64]), "+f"(d[65]), "+f"(d[66]),
      "+f"(d[67]), "+f"(d[68]), "+f"(d[69]), "+f"(d[70]), "+f"(d[71]), "+f"(d[72]), "+f"(d[73]), "+f"(d[74]), "+f"(d[75]), "+f"(d[76]), "+f"(d[77]),
      "+f"(d[78]), "+f"(d[79]), "+f"(d[80]), "+f"(d[81]), "+f"(d[82]), "+f"(d[83]), "+f"(d[84]), "+f"(d[85]), "+f"(d[86]), "+f"(d[87]), "+f"(d[88]),
      "+f"(d[89]), "+f"(d[90]), "+f"(d[91]), "+f"(d[92]), "+f"(d[93]), "+f"(d[94]), "+f"(d[95])
    : "r"(a[0]), "r"(a[1]), "r"(a[2]), "r"(a[3]), "l"(db), "r"(acc));
}

constexpr int NPQ = 2;
#define NQ 12
#define NQ_WIN 8
#define NO_EARLY 6
#define NO_MID 9
#define NW1 16
#define NW1A 10
#define VLD 6
#define VB 0
#define XPF 3
#define WSPLIT 8
#define PEARLY 0
#define NQ_W1 8
#define B5LATE 0
#define WD 750
#define DFENCE 0
#define PDS 300
#define PDT 50
#define LDEP 2
#define LDT 6000
#define VBULK 1
#define VBW 3
#define PD 780
constexpr int R_WQ = 0;
constexpr int R_WO = R_WQ + 8 * (20 - NPQ) * 512;
constexpr int R_XT = R_WO + 14 * 12 * 512;
constexpr int R_MEM = R_XT;
constexpr int R_QB = R_XT + 40960;
constexpr int R_QA = R_QB + 1024;
constexpr int R_O2 = R_QA + 1024;
constexpr int R_VS = R_O2 + 1024;
constexpr int R_KT = R_VS + 1024;
constexpr int R_VT = R_KT + 5120;
constexpr int R_V1 = R_VT + 5120;
constexpr int R_SX = R_V1 + 8192;
constexpr int R_VM = R_SX + 4608;
constexpr int R_BAR = R_VM + 2048;
constexpr int R_MI = R_BAR + 64;
constexpr int R_SMEM = R_MI + 64;
static_assert(NPQ == 2 && R_XT % 1024 == 0 && R_KT % 1024 == 0 && R_VT % 1024 == 0 && R_V1 % 1024 == 0 && R_WO % 1024 == 0, "align");
constexpr int R_SMEM_ALLOC = R_SMEM;
static_assert(R_SMEM_ALLOC <= 232448, "smem");

#define TR(i) do {} while (0)

__device__ __forceinline__ void red_pair(unsigned char* p, float lo, float hi) {
  const int b = __float2int_rn(lo), a = __float2int_rn(hi);
  asm volatile("{.reg .b64 t; mov.b64 t, {%1,%2}; red.relaxed.gpu.global.add.u64 [%0], t;}" ::"l"(p), "r"(b + ((1 << 29) + (1 << 23))), "r"(a * 8) : "memory");
}
__device__ __forceinline__ unsigned long long swap0(unsigned char* p) {
  unsigned long long r;
  asm volatile("atom.relaxed.gpu.global.exch.b64 %0, [%1], 0;" : "=l"(r) : "l"(p) : "memory");
  return r;
}
__device__ __forceinline__ uint32_t dec_pair(uint32_t lo, uint32_t hi, uint32_t bias) { return pack2((float)(int)(lo * 8u + bias), (float)(int)hi); }

__global__ void __cluster_dims__(3, 1, 1) __launch_bounds__(256, 1)
rec_kernel(const __grid_constant__ CUtensorMap tmX, const __grid_constant__ CUtensorMap tmK, const __grid_constant__ CUtensorMap tmV,
           const __grid_constant__ CUtensorMap tmWq, const __grid_constant__ CUtensorMap tmWq2, const __grid_constant__ CUtensorMap tmWk,
           const __grid_constant__ CUtensorMap tmWv, const __grid_constant__ CUtensorMap tmWo, const bf16* __restrict__ mem0,
           const bf16* __restrict__ Wq, const bf16* __restrict__ Wo, const bf16* __restrict__ x, unsigned char* __restrict__ red) {
  extern __shared__ __align__(1024) unsigned char smem[];
  const uint32_t sb = smem_u32(smem);
  const int tid = threadIdx.x, lane = tid & 31, wid = __shfl_sync(~0u, tid >> 5, 0), g = wid >> 2, w = wid & 3;
  const int cta = blockIdx.x, head = cta / 3, rank = cta % 3;
  const int D0 = head * DH + rank * 64;
  const int tile0 = rank == 0 ? 0 : (rank == 1 ? 14 : 26);
  const uint32_t XBAR = sb + R_BAR, SBAR = XBAR + 8, OBAR = XBAR + 16, VBAR = XBAR + 24, FBAR = XBAR + 32, WBAR = XBAR + 40;
  constexpr uint32_t ONES = 0x3F803F80u;
  if (LDEP == 0) asm volatile("griddepcontrol.launch_dependents;" ::: "memory");
  GTR(0);
  if (wid == 0) {
    if (lane == 0) {
      mbar_init(XBAR, 1); mbar_init(SBAR, 4); mbar_init(OBAR, 5); mbar_init(VBAR, 1); mbar_init(FBAR, 2);
      mbar_init(WBAR, 1); mbar_init(WBAR + 8, 1); mbar_init(WBAR + 16, 1);
      asm volatile("fence.mbarrier_init.release.cluster;" ::: "memory");
      mbar_expect(WBAR, 81920); mbar_expect(WBAR + 8, 81920 + 2 * NPQ * 2048); mbar_expect(XBAR, 40960);
      mbar_expect(SBAR, 3072); mbar_expect(OBAR, 2048); mbar_expect(VBAR, 8192);
      sts128(sb + R_MI + 48, 0, 0, 0, 0);
    }
    __syncwarp();
    if (lane < 5) tma_load2(sb + lane * 16384, &tmWk, D0, lane * 128, WBAR);
    if (lane == 5) tma_load3(sb + R_XT, &tmX, 0, 0, 0, XBAR);
    if (lane < 5) tma_load2(lane < 4 ? sb + 81920 + lane * 16384 : sb + R_QB, &tmWv, D0, lane * 128, WBAR + 8);
    if (lane < 2) tma_load2(sb + R_QB + 16384 + lane * 4096, &tmWq2, D0, lane * 320, WBAR + 8);
  }
  if (tid == 32) { prefetch_map(&tmWq); prefetch_map(&tmWo); prefetch_map(&tmK); prefetch_map(&tmV); }
  if (tid >= 64 && tid < 144) prefetch_l2(mem0 + (tid - 64) * 64);
  __syncthreads();
  GTR(1);
  if (LDEP == 1) asm volatile("griddepcontrol.launch_dependents;" ::: "memory");
  if (LDEP == 4 && wid == 7) { spin_until(clk32(), LDT); asm volatile("griddepcontrol.launch_dependents;" ::: "memory"); }
#pragma unroll
  for (int i = 0; i < 5; i++) { const int l = tid + i * 256; prefetch_l2((l < 640 ? Wq : Wo - 40960) + (size_t)cta * 40960 + l * 64); }
  uint32_t ww[40][4], wqp[NPQ][4];
  {
    uint32_t xm = 0;
#pragma unroll
    for (int i = 0; i < 7; i++) {
      const int v = tid + i * 256, gv = cta * 1707 + v;
      if (v < 1707 && gv < S_TOK * DM / 8) {
        const uint4 q = __ldg((const uint4*)x + gv);
        xm = hmaxabs2(hmaxabs2(xm, hmaxabs2(q.x, q.y)), hmaxabs2(q.z, q.w));
      }
    }
    xm = __reduce_max_sync(~0u, max((xm << 16) & 0x7fffffffu, xm & 0x7fff0000u));
    const uint32_t p = sb + (lane >> 4) * 1024 + (lane & 7) * 128 + (((2 * w + ((lane >> 3) & 1)) ^ (lane & 7)) << 4);
    if (LDEP == 2) asm volatile("griddepcontrol.launch_dependents;" ::: "memory");
    mbar_wait(WBAR + 8 * g, 0);
    GTR(2);
#pragma unroll
    for (int f = 0; f < 40; f++) ldsm4t(ww[f], (f >= 32 && g == 1) ? p + R_QB + (f - 32) * 2048 : p + g * 81920 + f * 2048);
    mbar_wait(WBAR + 8, 0);
    GTR(3);
#pragma unroll
    for (int f = 0; f < NPQ; f++) ldsm4t(wqp[f], p + R_QB + 16384 + g * 4096 + f * 2048);
    __syncthreads();
    asm volatile("barrier.cluster.arrive.relaxed.aligned;" ::: "memory");
    if (wid == 0) {
      if (lane == 0) mbar_expect(WBAR + 16, 18 * 4096 + 21 * 4096);
      __syncwarp();
      if (lane < 4) tma_load2(sb + R_WQ + lane * 18432, &tmWq, D0, (lane >> 1) * 320 + 32 + (lane & 1) * 144, WBAR + 16);
      else if (lane < 7) tma_load3(sb + R_WO + ((lane - 1 - rank) % 3) * 28672, &tmWo, 0, head * DH + (lane - 4) * 64, tile0 >> 1, WBAR + 16);
      __syncwarp();
    }
    float nv[4] = {0.f, 0.f, 0.f, 0.f};
#pragma unroll
    for (int f = 0; f < 40; f++) {
      const uint32_t a[4] = {ww[f][0] & 0x7fff7fffu, ww[f][1] & 0x7fff7fffu, ww[f][2] & 0x7fff7fffu, ww[f][3] & 0x7fff7fffu};
      mma16816(nv, a, ONES, ONES);
    }
    const uint32_t mv = __reduce_max_sync(~0u, __float_as_uint(fmaxf(nv[0], nv[2])));
    if (lane == 0) { if (g == 1) smax32(sb + R_MI + 48, mv); smax32(sb + R_MI + 52, xm); }
  }
  GTR(4);
  if (LDEP == 3) asm volatile("griddepcontrol.launch_dependents;" ::: "memory");

  const uint32_t rF_ = opaque(sb + lane * 16);
  const uint32_t rP_ = opaque(sb + (lane >> 4) * 1024 + (lane & 7) * 128 + (((2 * w + ((lane >> 3) & 1)) ^ (lane & 7)) << 4));
  const int tA = g == 1 ? 2 * w : (rank != 1 ? (w < 2 ? 8 + 2 * w : 10 + w) : 8 + w);
  const bool two = g == 1 || (w < 2 && rank != 1);
  const uint32_t r1 = rank == 2 ? 0 : rank + 1, r2 = rank == 0 ? 2 : rank - 1;
  const uint32_t rW_ = opaque(sb + R_WO + (tA >> 1) * 4096 + ((lane >> 4) * 8 + (lane & 7)) * 64 +
                             (((2 * (tA & 1) + ((lane >> 3) & 1)) ^ ((lane >> 1) & 3)) << 4));
  const uint32_t toff = rb_q((tile0 + tA) >> 2) + rb_j(4 * (tile0 + tA)), zoff = rb_q((cta % 20) >> 1) + rb_j((cta % 20) * 8);
  uint32_t wqt[NQ][4];
  float u = 1.f;
  uint32_t t0 = 0;
  int s = -1;

#define WOFF(ks) (((ks) >> 2) * 28672 + ((ks) & 3) * 1024)
#define XDESC(j) (((uint64_t)0x40000040 << 32) | (dlo + ((((j) >> 2) * 4096 + ((j) & 3) * 32) >> 4)))

  auto vsend = [&]() {
    if (elect()) {
      if (VBULK != 1) fence_async_smem();
      bulk_s2s(mapa(sb + R_V1 + 4096, r1), sb + R_VT + 1024, 4096, mapa(VBAR, r1));
      bulk_s2s(mapa(sb + R_V1, r2), sb + R_VT + 1024, 4096, mapa(VBAR, r2));
    }
    __syncwarp();
  };
  auto window = [&](auto G_, auto FIRST_) {
    constexpr int G = decltype(G_)::value;
    constexpr bool FIRST = decltype(FIRST_)::value;
    const uint32_t rF = pin(rF_), rP = pin(rP_);
    float d[16];
    const uint32_t dlo = pin(((sb + R_XT) >> 4) | 0x10000);
    const uint32_t wqS = rP + R_WQ + G * (20 - NPQ) * 2048;
    uint4 y[5];
    unsigned long long zr = 0;
    const uint32_t t = w * 32 + ((rF - sb) >> 4);
    if (G == 0) zr = swap0(red + (rb_b(s + 2) + zoff + rb_j(t >> 4) + (t & 15) * 8));
    if (G == 0) {
      if (!FIRST && w == 3) {
        if (elect()) {
          mbar_expect(SBAR, 3072); mbar_expect(OBAR, 2048); mbar_expect(VBAR, 8192);
          asm volatile("mbarrier.arrive.relaxed.cluster.shared::cluster.b64 _, [%0];" ::"r"(mapa(FBAR, r1)) : "memory");
          asm volatile("mbarrier.arrive.relaxed.cluster.shared::cluster.b64 _, [%0];" ::"r"(mapa(FBAR, r2)) : "memory");
        }
        __syncwarp();
      }
    }
    const unsigned char* yp = red + (rb_b(s) + rb_j(t >> 3) + (t & 7) * 16);
    auto poll = [&]() {
      TR(10);
      spin_until(t0, PD);
#pragma unroll
      for (int q = 0; q < 5; q++) y[q] = ldg_rlx128(yp + rb_q(G * 5 + q));
      TR(9);
      sched_fence(sb);
    };
    constexpr int WS = FIRST || G == 1 ? 40 : WSPLIT;
    if (!FIRST && G == 0) {
#pragma unroll
      for (int f = 0; f < NQ_WIN; f++) ldsm4t(wqt[f], wqS + f * 2048);
      asm volatile("" : "+l"(yp));
      mbar_wait(XBAR, (s + 1) & 1);
      if (WS) spin_until(t0, WD);
    } else {
      mbar_wait(XBAR, (s + 1) & 1);
    }
    TR(11);
    if (WS == 0) { poll(); spin_until(t0, WD); }
    wg_fence();
    wgmma_rs32<0>(d, ww[0], XDESC(0));
#pragma unroll
    for (int j = 1; j < WS; j++) wgmma_rs32<1>(d, ww[j], XDESC(j));
    if (FIRST) {
      const unsigned short* m = (const unsigned short*)mem0 + (t & 1) * 4 * DM + G * 320 + (t >> 1);
#pragma unroll
      for (int q = 0; q < 5; q++) y[q] = make_uint4(m[q * 64], m[q * 64 + DM], m[q * 64 + 2 * DM], m[q * 64 + 3 * DM]);
    } else if (G == 0 && WS) {
      poll();
    }
#pragma unroll
    for (int j = WS ? WS : 1; j < 40; j++) wgmma_rs32<1>(d, ww[j], XDESC(j));
    wg_commit();
    if (!FIRST && G == 1) {
      asm volatile("" : "+l"(yp));
      if (PEARLY && (VBULK != 4 || w != VBW)) poll();
      mbar_wait(FBAR, s & 1);
#pragma unroll
      for (int f = 0; f < NQ_W1; f++) ldsm4t(wqt[f], wqS + f * 2048);
    }
    if (FIRST) asm volatile("barrier.cluster.wait.acquire.aligned;" ::: "memory");
    wg_wait0();
    fence_regs<16>(d);
    TR(13);
    bar_arrive(8 + G, 256);
    if (!FIRST && G == 1 && !PEARLY && (VBULK != 4 || w != VBW)) poll();
    {
      uint32_t pk[8];
#pragma unroll
      for (int q = 0; q < 8; q++) pk[q] = pack2(d[2 * q], d[2 * q + 1]);
      stsm4t(rP + (G == 1 ? R_VT : R_KT) + 1024, pk[0], pk[1], pk[2], pk[3]);
      stsm4t(rP + (G == 1 ? R_VT : R_KT) + 3072, pk[4], pk[5], pk[6], pk[7]);
      if (G == 1 && VBULK) {
        if (VBULK == 1) fence_async_smem();
        if (VBULK == 1 || VBULK == 4) {
          if (w != VBW) bar_arrive(6, 128);
          else {
            bar_sync(6, 128);
            vsend();
            if (VBULK == 4 && !FIRST) poll();
          }
        }
      } else if (G == 1) {
        const uint32_t e1 = mapa(rF + R_V1 + 4096 + w * 512, r1), e2 = mapa(rF + R_V1 + w * 512, r2), b1 = mapa(VBAR, r1), b2 = mapa(VBAR, r2);
        st_async4(e1, pk[0], pk[1], pk[2], pk[3], b1);
        st_async4(e2, pk[0], pk[1], pk[2], pk[3], b2);
        st_async4(e1 + 2048, pk[4], pk[5], pk[6], pk[7], b1);
        st_async4(e2 + 2048, pk[4], pk[5], pk[6], pk[7], b2);
      }
    }
    if (FIRST) {
      mbar_wait(WBAR + 16, 0);
      const uint32_t woA = rW_;
      float na[4] = {0.f, 0.f, 0.f, 0.f}, nb[4] = {0.f, 0.f, 0.f, 0.f};
#pragma unroll
      for (int ks = 0; ks < 12; ks++) {
        uint32_t a[4], b[4];
        ldsm4t(a, woA + WOFF(ks));
        ldsm4t(b, (two ? woA ^ 32 : woA) + WOFF(ks));
#pragma unroll
        for (int q = 0; q < 4; q++) { a[q] &= 0x7fff7fffu; b[q] &= 0x7fff7fffu; }
        mma16816(na, a, ONES, ONES);
        mma16816(nb, b, ONES, ONES);
      }
      const uint32_t mo = __reduce_max_sync(~0u, __float_as_uint(fmaxf(fmaxf(na[0], na[2]), fmaxf(nb[0], nb[2]))));
      if (rF == sb) smax32(sb + R_MI + 56, mo);
      __syncthreads();
      if (G == 1 && w == 2) {
        const uint4 r = lds128(sb + R_MI + 48);
        const uint32_t epoch = *(volatile uint32_t*)&g_epoch + 1;
        if (rF == sb) stg_rlx64(&g_rec[cta], (r.y & 0xffff0000u) | (epoch & 0xffffu), ((r.x + 0xffffu) & 0xffff0000u) | ((r.z + 0xffffu) >> 16));
      }
    }
#pragma unroll
    for (int f = FIRST ? 0 : (G == 1 ? NQ_W1 : NQ_WIN); f < NQ; f++) ldsm4t(wqt[f], wqS + f * 2048);
    if (FIRST || DFENCE) sched_fence(sb);
    TR(14);
    const uint32_t ma = sb + R_MEM + G * 5120 + t * 8;
    if (FIRST) {
      bar_sync(9 - G, 256);
#pragma unroll
      for (int j = 0; j < 5; j++) sts64(ma + j * 1024, y[j].x | (y[j].y << 16), y[j].z | (y[j].w << 16));
    } else {
      int n = 0;
#pragma unroll 1
      while (!__all_sync(~0u, (y[0].y & y[0].w & y[1].y) & (y[1].w & y[2].y & y[2].w) & (y[3].y & y[3].w & y[4].y) & (y[4].w & 4))) {
#pragma unroll
        for (int j = 0; j < 5; j++) if (!(y[j].y & y[j].w & 4)) y[j] = ldg_rlx128(yp + rb_q(G * 5 + j));
        if (++n > SPIN_MAX) { g_err = 5; break; }
      }
      const uint32_t bias = 0x80000000u + (sb >> 31);
      bar_sync(9 - G, 256);
#pragma unroll
      for (int j = 0; j < 5; j++) sts64(ma + j * 1024, dec_pair(y[j].x, y[j].y, bias), dec_pair(y[j].z, y[j].w, bias));
    }
    if (G == 0 && zr == ~0ull) g_err = 9;
    TR(0);
  };

  auto oproj = [&](auto TWO_, auto NPRE_, auto& wot, const uint32_t rF, const uint32_t woA, const uint32_t woB,
                   float sm0, float sm1, bool have_sums) {
    constexpr bool TWO = decltype(TWO_)::value;
    constexpr int NPRE = decltype(NPRE_)::value;
    float c[4][4];
#pragma unroll
    for (int q = 0; q < 4; q++) c[q][0] = c[q][1] = c[q][2] = c[q][3] = 0.f;
    unsigned char* sp = red + (rb_b(s) + toff + ((rF - sb) & 256) + (((rF - sb) >> 1) & 120));
    bar_sync(3, 256);
    TR(8);
    uint4 ob[6];
    ob[0] = lds128(rF + R_QB); ob[1] = lds128(rF + R_QB + 512);
    const float2 su = lds64f(sb + R_MI + 48);
    if (!have_sums) { const float2 t = lds64f(sb + R_MI + 16 + (((rF - sb) >> 1) & 24)); sm0 = t.x; sm1 = t.y; }
#pragma unroll
    for (int p = 0; p < 6; p++) {
      if (p + 2 < 6) ob[p + 2] = lds128(rF + (p < 2 ? R_QA : R_O2) + (p & 1) * 512);
#pragma unroll
      for (int e = 0; e < 2; e++) {
        const int ks = 2 * p + e;
        const uint32_t b0 = e ? ob[p].z : ob[p].x, b1 = e ? ob[p].w : ob[p].y;
        if (TWO) {
          const int iA = 2 * ks, iB = iA + 1;
          mma16816(c[e], wot[iA % NPRE], b0, b1);
          if (iA + NPRE < 24) ldsm4t(wot[iA % NPRE], woA + WOFF((iA + NPRE) >> 1));
          mma16816(c[2 + e], wot[iB % NPRE], b0, b1);
          if (iB + NPRE < 24) ldsm4t(wot[iB % NPRE], woB + WOFF((iB + NPRE) >> 1));
        } else {
          mma16816(c[ks & 3], wot[ks], b0, b1);
        }
      }
    }
    const float f0 = su.x * rcp(sm0), f1 = su.x * rcp(sm1);
    t0 = clk32() + (TWO ? (have_sums ? -PDT : 0) : PDS);
    u = su.y;
    if (TWO) {
      red_pair(sp, (c[0][0] + c[1][0]) * f0, (c[0][1] + c[1][1]) * f1);
      red_pair(sp + rb_j(2), (c[0][2] + c[1][2]) * f0, (c[0][3] + c[1][3]) * f1);
      red_pair(sp + rb_j(4), (c[2][0] + c[3][0]) * f0, (c[2][1] + c[3][1]) * f1);
      red_pair(sp + rb_j(6), (c[2][2] + c[3][2]) * f0, (c[2][3] + c[3][3]) * f1);
    } else {
      red_pair(sp, ((c[0][0] + c[1][0]) + (c[2][0] + c[3][0])) * f0, ((c[0][1] + c[1][1]) + (c[2][1] + c[3][1])) * f1);
      red_pair(sp + rb_j(2), ((c[0][2] + c[1][2]) + (c[2][2] + c[3][2])) * f0, ((c[0][3] + c[1][3]) + (c[2][3] + c[3][3])) * f1);
    }
    TR(15);
  };

  auto step = [&](auto G_, auto LAST_) {
    constexpr int G = decltype(G_)::value;
    constexpr bool LAST = decltype(LAST_)::value;
    __syncthreads();
    const uint32_t rF = pin(rF_), rP = pin(rP_);
    TR(1);
    const uint32_t wqS = rP + R_WQ + G * (20 - NPQ) * 2048, rM = rF + R_MEM;
    const uint32_t l8 = sb + ((rF - sb) >> 1) + w * 256;
    const uint32_t woA = pin(rW_), woB = woA ^ 32;
    float aq[2][4] = {};
    const uint32_t ln = (rF - sb) >> 4;
    const uint32_t rS = sb + (ln & 7) * 128 + (ln < 16 ? R_QB + (ln & 8) * 128 + (((2 * w + G) ^ (ln & 7)) << 4) : R_KT + (((2 * w + ((ln >> 3) & 1)) ^ (ln & 7)) << 4));
    auto qmma = [&](int f, uint32_t b0, uint32_t b1) {
      if (f < NPQ) mma16816(aq[f & 1], wqp[f], b0, b1);
      else {
        const int slot = (f - NPQ) % NQ;
        mma16816(aq[f & 1], wqt[slot], b0, b1);
        if (f + NQ < 20) ldsm4t(wqt[slot], wqS + (f - NPQ + NQ) * 2048);
      }
    };
    if constexpr (G == 1) {
      uint32_t bb[20][4];
      if (!LAST) {
        if (VBULK == 2 && w == VBW) vsend();
        ldsm4t(bb[10], rM + 5120);
        ldsm4t(bb[11], rM + 5632);
#pragma unroll
        for (int i = 10; i < 20; i++) {
          if (i + 2 < 20) ldsm4t(bb[i + 2], rM + (i + 2) * 512);
          qmma(2 * i - 20, bb[i][0], bb[i][1]);
          qmma(2 * i - 19, bb[i][2], bb[i][3]);
        }
        stsm2t(rS, pack2(aq[0][0] + aq[1][0], aq[0][1] + aq[1][1]), pack2(aq[0][2] + aq[1][2], aq[0][3] + aq[1][3]));
        bar_arrive(1, 256);
        if (VBULK == 3 && w == VBW) vsend();
      }
      TR(2);
      float av[4][4] = {};
      uint32_t m0 = 0, m1 = 0;
      auto vmma = [&](auto MAX_) {
#pragma unroll
        for (int n = 0; n < 20; n++) {
          const int i = (n + 10) % 20;
          if (LAST && n < 8) ldsm4t(bb[(n + 10) % 20], rM + ((n + 10) % 20) * 512);
          if (LAST && n == 0) { ldsm4t(bb[18], rM + 18 * 512); ldsm4t(bb[19], rM + 19 * 512); }
          if (n == VB && !LAST) { bar_sync(5, 256); sched_fence(sb); }
          if (n == VLD) {
            if (VB != VLD && !LAST) sched_fence(sb);
#pragma unroll
            for (int q = 0; q < 10; q++) ldsm4t(bb[q], rM + q * 512);
            if (!LAST) sched_fence(sb);
          }
          mma16816(av[(2 * n) & 3], ww[2 * i], bb[i][0], bb[i][1]);
          mma16816(av[(2 * n + 1) & 3], ww[2 * i + 1], bb[i][2], bb[i][3]);
          if (decltype(MAX_)::value) { m0 = hmaxabs2(m0, hmaxabs2(bb[i][0], bb[i][1])); m1 = hmaxabs2(m1, hmaxabs2(bb[i][2], bb[i][3])); }
        }
      };
      auto vout = [&]() {
        const uint32_t vm0 = pack2(((av[0][0] + av[1][0]) + (av[2][0] + av[3][0])) * u, ((av[0][1] + av[1][1]) + (av[2][1] + av[3][1])) * u);
        const uint32_t vm1 = pack2(((av[0][2] + av[1][2]) + (av[2][2] + av[3][2])) * u, ((av[0][3] + av[1][3]) + (av[2][3] + av[3][3])) * u);
        if (!LAST) {
          st_async2(mapa(l8 + R_VM + 1024, r1), vm0, vm1, mapa(OBAR, r1));
          st_async2(mapa(l8 + R_VM, r2), vm0, vm1, mapa(OBAR, r2));
          sts64(l8 + R_VS, vm0, vm1);
          __syncwarp();
          if (rF == sb) mbar_arrive(OBAR);
        }
        stsm2t(rP + R_VT, vm0, vm1);
      };
      if (LAST) { vmma(std::false_type{}); vout(); return; }
      uint32_t wot[NW1][4];
      auto wpre = [&](int i0, int i1) {
#pragma unroll
        for (int i = i0; i < i1; i++) ldsm4t(wot[i], ((i & 1) ? woB : woA) + WOFF(i >> 1));
      };
      if (w != 1) {
        vmma(std::false_type{});
        bar_arrive(7, 128);
        vout();
        bar_arrive(2, 128);
        TR(5);
        wpre(0, NW1A);
      } else {
        vmma(std::true_type{});
        bar_sync(7, 128);
        if (elect()) { mbar_expect(XBAR, 40960); tma_load3(sb + R_XT, &tmX, 0, (s + 1) * SEG, 0, XBAR); }
        __syncwarp();
        vout();
        if (XPF && s + XPF < NSEG && rF - sb < 64 && cta < 80) prefetch_l2(x + (size_t)(s + XPF) * SEG * DM + cta * 256 + (rF - sb) * 4);
        TR(5);
        m0 = hmaxabs2(m0, m1);
        const uint32_t mx = __reduce_max_sync(~0u, max((m0 << 16) & 0x7fffffffu, m0 & 0x7fff0000u));
        const float2 mi = lds64f(sb + R_MI + 8);
        wpre(0, NW1A);
        bar_sync(2, 128);
        if (elect()) {
          fence_async_smem();
          if (s > 0) {
            bulk_wait0();
            asm volatile("red.relaxed.gpu.global.add.u32 [%0], 1;" ::"l"(&g_segcnt[s - 1]) : "memory");
            asm volatile("red.relaxed.gpu.global.add.u32 [%0], 1;" ::"l"(&g_prog) : "memory");
          }
          tma_store2(&tmK, sb + R_KT, D0, s * LK);
          tma_store2(&tmV, sb + R_VT, D0, s * LK);
          bulk_commit();
        }
        __syncwarp();
        float wb = mi.x, xm = mi.y;
        if (s == 0) {
          const uint32_t epoch = *(volatile uint32_t*)&g_epoch + 1;
          uint32_t av_ = 0, ao = 0, xi = 0;
#pragma unroll 1
          for (int j = 0; j < 3; j++) {
            uint2 r;
            int n = 0;
#pragma unroll 1
            while (true) {
              r = ldg_rlx64(&g_rec[j * 32 + ((rF - sb) >> 4)]);
              if (((r.x ^ epoch) & 0xffffu) == 0) break;
              if (++n > SPIN_MAX) { g_err = 6; break; }
            }
            av_ = max(av_, r.y & 0xffff0000u); ao = max(ao, r.y << 16); xi = max(xi, r.x & 0xffff0000u);
          }
          av_ = __reduce_max_sync(~0u, av_); ao = __reduce_max_sync(~0u, ao); xi = __reduce_max_sync(~0u, xi);
          wb = __uint_as_float(av_) * __uint_as_float(ao) * 33.f; xm = __uint_as_float(xi);
          if (rF == sb) sts64f(sb + R_MI + 8, wb, xm);
          __syncwarp();
        }
        const float hm = fmaxf(__uint_as_float(mx) * u, xm);
        const uint32_t eb = min(max(__float_as_uint(hm * wb) >> 23, 40u), 200u);
        if (rF == sb) sts64(sb + R_MI + 48, (280u - eb) << 23, (eb - 29u) << 23);
        if (elect()) bulk_wait_read0();
        __syncwarp();
      }
      if (NW1A < NW1) {
        bar_sync(4, 256);
        wpre(NW1A, NW1);
      }
      TR(6);
      oproj(std::true_type{}, std::integral_constant<int, NW1>{}, wot, rF, woA, woB, 0.f, 0.f, false);
    } else {
      {
        uint32_t bb[20][4];
        float ak[4][4] = {};
        ldsm4t(bb[0], rM);
        ldsm4t(bb[10], rM + 5120);
#pragma unroll
        for (int i = 0; i < 10; i++) {
          if (i + 1 < 10) { ldsm4t(bb[i + 1], rM + (i + 1) * 512); ldsm4t(bb[i + 11], rM + (i + 11) * 512); }
          mma16816(ak[0], ww[2 * i], bb[i][0], bb[i][1]);
          if (!LAST) qmma(2 * i, bb[i][0], bb[i][1]);
          mma16816(ak[1], ww[2 * i + 1], bb[i][2], bb[i][3]);
          if (!LAST) qmma(2 * i + 1, bb[i][2], bb[i][3]);
          mma16816(ak[2], ww[2 * i + 20], bb[i + 10][0], bb[i + 10][1]);
          mma16816(ak[3], ww[2 * i + 21], bb[i + 10][2], bb[i + 10][3]);
        }
#pragma unroll
        for (int q = 0; q < 4; q++) { ak[0][q] += ak[2][q]; ak[1][q] += ak[3][q]; }
        stsm4t(rS, pack2(aq[0][0] + aq[1][0], aq[0][1] + aq[1][1]), pack2(aq[0][2] + aq[1][2], aq[0][3] + aq[1][3]),
               pack2((ak[0][0] + ak[1][0]) * u, (ak[0][1] + ak[1][1]) * u), pack2((ak[0][2] + ak[1][2]) * u, (ak[0][3] + ak[1][3]) * u));
      }
      if (LAST) return;
      bar_sync(1, 256);
      if (!B5LATE) bar_arrive(5, 256);
      TR(2);
      if (w != 3) {
        uint32_t qa[4][4], kk[4][4];
        float x[4][4] = {};
#pragma unroll
        for (int i = 0; i < 4; i++) { ldsm4(qa[i], (rP ^ (i << 5)) + R_QB); ldsm4(kk[i], ((rP ^ (i << 5)) + w * 2048) + R_KT); }
        const uint32_t dst = rF + R_SX + rank * 1536 + w * 512;
        const uint32_t e1 = mapa(dst, r1), e2 = mapa(dst, r2), s1 = mapa(SBAR, r1), s2 = mapa(SBAR, r2);
#pragma unroll
        for (int i = 0; i < 4; i++) { mma16816(x[i & 1], qa[i], kk[i][0], kk[i][1]); mma16816(x[2 + (i & 1)], qa[i], kk[i][2], kk[i][3]); }
        const uint32_t u0 = __float_as_uint((x[0][0] + x[0][2]) + (x[1][0] + x[1][2])), u1 = __float_as_uint((x[0][1] + x[0][3]) + (x[1][1] + x[1][3]));
        const uint32_t u2 = __float_as_uint((x[2][0] + x[2][2]) + (x[3][0] + x[3][2])), u3 = __float_as_uint((x[2][1] + x[2][3]) + (x[3][1] + x[3][3]));
        st_async4(e1, u0, u1, u2, u3, s1);
        st_async4(e2, u0, u1, u2, u3, s2);
        sts128(dst, u0, u1, u2, u3);
        __syncwarp();
        if (rF == sb) mbar_arrive(SBAR);
      }
      if (B5LATE) bar_arrive(5, 256);
      TR(4);
      mbar_wait(VBAR, s & 1);
      uint32_t wot[12][4], va[3][8];
      ldsm4t(va[0], rP + R_VT + 1024); ldsm4t(va[0] + 4, rP + R_VT + 3072);
#pragma unroll
      for (int q = 0; q < 4; q++) {
        if (VBULK) { ldsm4t(va[1 + (q >> 1)] + (q & 1) * 4, rP + R_V1 + q * 2048); continue; }
        const uint4 t = lds128(rF + R_V1 + w * 512 + q * 2048);
        uint32_t* v = va[1 + (q >> 1)] + (q & 1) * 4;
        v[0] = t.x; v[1] = t.y; v[2] = t.z; v[3] = t.w;
      }
      auto wpre = [&](int i0, int i1) {
        if (two) {
#pragma unroll
          for (int i = i0; i < i1; i++) ldsm4t(wot[i], ((i & 1) ? woB : woA) + WOFF(i >> 1));
        } else {
#pragma unroll
          for (int i = i0; i < i1; i++) ldsm4t(wot[i], woA + WOFF(i));
        }
      };
      wpre(0, NO_EARLY);
      const uint32_t dst = rF + (w >> 1) * 512 + (w & 1) * 8;
      const float scl = u * (0.07216878364870322f * 1.4426950408889634f);
      mbar_wait(SBAR, s & 1);
      TR(6);
      float sc[10];
      {
        const float4 a0 = lds128f(rF + R_SX), b0 = lds128f(rF + R_SX + 1536), c0 = lds128f(rF + R_SX + 3072);
        const float4 a1 = lds128f(rF + R_SX + 512), b1 = lds128f(rF + R_SX + 2048), c1 = lds128f(rF + R_SX + 3584);
        const float2 a2 = lds64f(rF + R_SX + 1024), b2 = lds64f(rF + R_SX + 2560), c2 = lds64f(rF + R_SX + 4096);
        sc[8] = a0.x + b0.x + c0.x; sc[9] = a0.y + b0.y + c0.y; sc[0] = a0.z + b0.z + c0.z; sc[1] = a0.w + b0.w + c0.w;
        sc[2] = a1.x + b1.x + c1.x; sc[3] = a1.y + b1.y + c1.y; sc[4] = a1.z + b1.z + c1.z; sc[5] = a1.w + b1.w + c1.w;
        sc[6] = a2.x + b2.x + c2.x; sc[7] = a2.y + b2.y + c2.y;
      }
      float mx = fmaxf(fmaxf(fmaxf(sc[0], sc[1]), fmaxf(sc[2], sc[3])), fmaxf(fmaxf(sc[4], sc[5]), fmaxf(sc[6], sc[7])));
      mx = fmaxf(mx, fmaxf(sc[8], sc[9]));
      mx = fmaxf(mx, __shfl_xor_sync(~0u, mx, 1));
      const bool vok = mbar_test(OBAR, s & 1);
      mx = fmaxf(mx, __shfl_xor_sync(~0u, mx, 2));
      if (NW1A < NW1) bar_arrive(4, 256);
      const float mo = mx * scl;
      uint32_t pb[5];
#pragma unroll
      for (int j = 0; j < 5; j++) pb[j] = pack2(ex2(fmaf(sc[2 * j], scl, -mo)), ex2(fmaf(sc[2 * j + 1], scl, -mo)));
      if (!vok) mbar_wait(OBAR, s & 1);
      const uint2 m0 = lds64(l8 + R_VS), m1 = lds64(l8 + R_VM), m2 = lds64(l8 + R_VM + 1024);
      const uint32_t ones[4] = {ONES, ONES, ONES, ONES};
      float o[3][4], o2[3][4], sm[4] = {0.f, 0.f, 0.f, 0.f}, sn[4] = {0.f, 0.f, 0.f, 0.f}, so[4] = {0.f, 0.f, 0.f, 0.f};
#pragma unroll
      for (int b = 0; b < 3; b++) {
        o[b][0] = o[b][1] = o[b][2] = o[b][3] = o2[b][0] = o2[b][1] = o2[b][2] = o2[b][3] = 0.f;
        mma16816(o[b], va[b], pb[0], pb[1]);
      }
#pragma unroll
      for (int b = 0; b < 3; b++) mma16816(o2[b], va[b] + 4, pb[2], pb[3]);
      mma1688(o[0], m0.x, m0.y, pb[4]);
      mma1688(o[1], m1.x, m1.y, pb[4]);
      mma1688(o[2], m2.x, m2.y, pb[4]);
      mma16816(sm, ones, pb[0], pb[1]);
      mma16816(sn, ones, pb[2], pb[3]);
      mma1688(so, ONES, ONES, pb[4]);
      wpre(NO_EARLY, NO_MID);
#pragma unroll
      for (int b = 0; b < 3; b++)
        sts64(dst + (b == 0 ? R_QB : (b == 1 ? R_QA : R_O2)), movmat(pack2(o[b][0] + o2[b][0], o[b][1] + o2[b][1])),
              movmat(pack2(o[b][2] + o2[b][2], o[b][3] + o2[b][3])));
      sm[0] += sn[0] + so[0]; sm[1] += sn[1] + so[1];
      if (rF - sb < 64) sts64f(sb + R_MI + 16 + ((rF - sb) >> 1), sm[0], sm[1]);
      wpre(NO_MID, 12);
      TR(7);
      if (two) oproj(std::true_type{}, std::integral_constant<int, 12>{}, wot, rF, woA, woB, sm[0], sm[1], true);
      else oproj(std::false_type{}, std::integral_constant<int, 12>{}, wot, rF, woA, woB, sm[0], sm[1], true);
    }
  };

  GTR(5); GTR(6);
  if (g == 0) {
    window(std::integral_constant<int, 0>{}, std::true_type{});
    GTR(7);
#pragma unroll 1
    for (s = 0; s < NSEG - 1; s++) {
      step(std::integral_constant<int, 0>{}, std::false_type{});
      window(std::integral_constant<int, 0>{}, std::false_type{});
    }
    step(std::integral_constant<int, 0>{}, std::true_type{});
  } else {
    window(std::integral_constant<int, 1>{}, std::true_type{});
#pragma unroll 1
    for (s = 0; s < NSEG - 1; s++) {
      step(std::integral_constant<int, 1>{}, std::false_type{});
      window(std::integral_constant<int, 1>{}, std::false_type{});
    }
    step(std::integral_constant<int, 1>{}, std::true_type{});
  }
  __syncthreads();
  if (tid == 160) {
    fence_async_smem();
    tma_store2(&tmK, sb + R_KT, D0, (NSEG - 1) * LK);
    tma_store2(&tmV, sb + R_VT, D0, (NSEG - 1) * LK);
    bulk_commit();
    bulk_wait0();
    asm volatile("red.relaxed.gpu.global.add.u32 [%0], 1;" ::"l"(&g_segcnt[NSEG - 2]) : "memory");
    asm volatile("red.relaxed.gpu.global.add.u32 [%0], 1;" ::"l"(&g_segcnt[NSEG - 1]) : "memory");
    asm volatile("red.relaxed.gpu.global.add.u32 [%0], 2;" ::"l"(&g_prog) : "memory");
  }
  GTR(8);
  if (tid == 0 && VBULK != 2 && VBULK != 3) mbar_wait(VBAR, (NSEG - 1) & 1);
  GTR(9);
}

enum { IT_GATE = 0, IT_QKV = 1, IT_XATT = 2, IT_OUT = 3, IT_BATT = 4, IT_CVT = 5, IT_INIT = 6, IT_END = 7 };
constexpr int C_GATE = 0, C_QKV = 16, C_OB = 32, C_ACC = 48, C_O = 80;
constexpr uint32_t NONE = ~0u;
#define HP 0x1223346888888888ull
#define XD 0x4589aaaaaaaaaaaaull
#define KREQ 4
#define ADELAY 0
#define LAG 0
#define W_PRO 11
#define W_SCH 8
#define W_AG1 10
#define KEARLY 1
#define CVTS 6
#define RSL 20
#define SPLITW 0
#define XPP 22
#define PP 3
__host__ __device__ constexpr uint32_t mk_item(int ty, int t, int a, int b = 0, int c = 0) { return ty | (t << 3) | (a << 8) | (b << 16) | (c << 24); }
struct ItemTab { uint32_t v[1280]; int n; };
constexpr ItemTab make_items() {
  ItemTab T{};
  int n = 0;
  for (int t = 0; t < 16; t++) T.v[n++] = mk_item(IT_GATE, t, 0);
  for (int t = 0; t < 16; t++) for (int a = 0; a < 5; a++) T.v[n++] = mk_item(IT_QKV, t, a);
  for (int t = 0; t < 32; t++) for (int a = 0; a < 4; a++) T.v[n++] = mk_item(IT_BATT, t, a);
  for (int t = 0; t < 16; t++) for (int a = 0; a < 2; a++) T.v[n++] = mk_item(IT_INIT, t, a);
  for (int t = 0; t < 16; t++) {
    const int hp = (HP >> 4 * t) & 15;
    for (int h = 0; h < 32; h += hp) for (int a = 0; a < 2; a++) T.v[n++] = mk_item(IT_OUT, t, a, h, h + hp < 32 ? h + hp : 32);
  }
  T.n = n;
  return T;
}
constexpr ItemTab k_items_host = make_items();
constexpr int NITEMS = k_items_host.n;
__constant__ ItemTab c_items = make_items();

constexpr int AUX_GRID = 132, NST = 7, STG = 32768;
constexpr int A_FULL = NST * STG, A_EMPTY = A_FULL + 64, A_ITEM = A_EMPTY + 64, A_QBAR = A_ITEM + 32, A_QENT = A_QBAR + 128, A_MISC = A_QENT + 256,
              A_SMEM = A_MISC + 64, A_REQ = A_FULL + 56, A_RSP = A_EMPTY + 56, A_MAIL = A_MISC + 48, A_RDY = A_MISC + 32;
static_assert(A_SMEM <= 232448, "smem");
enum { OP_END = 0, OP_O = 1, OP_QKV = 2, OP_OB = 3, OP_SET = 4, OP_ADD = 5 };

struct AuxMaps { CUtensorMap xA, wq, wqkv, wo, wob, k, v, oA, oS, obA, obS, qkvS, qkvQ, qkvK, out; };

__device__ __forceinline__ void mbar_wait_long(uint32_t b, uint32_t par) {
  int n = 0;
#pragma unroll 1
  while (!mbar_try(b, par)) { if (++n > (SPIN_MAX << 4)) { g_err = 8; break; } }
}
__device__ __forceinline__ void mbar_wait_u(uint32_t b, uint32_t par) {
  asm volatile("{.reg .pred p; .reg .u32 n;\nmov.u32 n, 0;\nLW: mbarrier.try_wait.parity.shared::cta.b64 p, [%0], %1;\n@p bra.uni LD;\n"
               "add.u32 n, n, 1;\nsetp.lt.u32 p, n, %2;\n@p bra.uni LW;\nLD:\n}" ::"r"(b), "r"(par), "n"(SPIN_MAX << 4) : "memory");
}
struct Desc {
  uint32_t lo, hi;
  __device__ __forceinline__ Desc operator+(uint32_t o) const { return {lo + o, hi}; }
  __device__ __forceinline__ operator uint64_t() const { return ((uint64_t)hi << 32) | lo; }
};
__device__ __forceinline__ Desc mk_desc(uint32_t addr, uint32_t lbo, uint32_t sbo, uint32_t mode) {
  return {(addr >> 4) | ((lbo >> 4) << 16), (sbo >> 4) | (mode << 30)};
}

__global__ void __launch_bounds__(384, 1)
aux_kernel(const __grid_constant__ AuxMaps tm, const bf16* __restrict__ x, const bf16* __restrict__ gate_w) {
  extern __shared__ __align__(1024) unsigned char smem[];
  const uint32_t sb = smem_u32(smem);
  const int tid = threadIdx.x, lane = tid & 31, wid = __shfl_sync(~0u, tid >> 5, 0);
  uint32_t epoch = 0, j0 = 0;
  const uint32_t c0 = clk32();
  if (tid == W_SCH * 32) GTA(0);
  if (tid >= 256) epoch = *(volatile uint32_t*)&g_epoch + 1;
  if (tid == W_SCH * 32) j0 = atomicAdd(&g_queue[32], 1u);
  if (tid == 0) {
    mbar_init(sb + A_REQ, 1); mbar_init(sb + A_RSP, 1); mbar_init(sb + A_RDY, 1);
    for (int i = 0; i < NST; i++) { mbar_init(sb + A_FULL + i * 8, 1); mbar_init(sb + A_EMPTY + i * 8, 8); }
    for (int i = 0; i < 16; i++) mbar_init(sb + A_QBAR + i * 8, 4);
    asm volatile("fence.mbarrier_init.release.cluster;" ::: "memory");
  }
  if (tid < 15) prefetch_map(&tm.xA + tid);
  if (tid == W_SCH * 32) GTA(4);
  __syncthreads();
  if (tid == W_SCH * 32) GTA(5);
  uint32_t st = 0, ph = 0;
  auto advance = [&]() { if (++st == NST) { st = 0; ph ^= 1; } };

  if (wid >= 8) {
    asm volatile("setmaxnreg.dec.sync.aligned.u32 40;");
    if (tid == W_SCH * 32) GTA(6);
    auto cnt = [&](int c, uint32_t per) -> bool { return (int)(ldg_rlx32(&g_cnt[c * 8]) - epoch * per) >= 0; };
    auto ready = [&](uint32_t item) -> int {
      const int ty = item & 7, t = (item >> 3) & 31, b = (item >> 17) & 127, n = (((item >> 24) + 1) >> 1) - b;
      int r;
      if (ty == IT_OUT) {
        const int c = C_O + t * 16 + b;
        const bool r0 = cnt(c, 2), r1 = cnt(c + (n > 1), 2), r2 = cnt(c + (n > 2) * 2, 2), r3 = cnt(c + (n > 3) * 3, 2);
        r = r0 & cnt(C_ACC + t, 4) ? (r1 ? (r2 ? (r3 ? 4 : 3) : 2) : 1) : 0;
      } else if (ty == IT_XATT) {
        const uint4 v = ldg_rlx128(&g_segcnt[4 * t]);
        const uint32_t e = epoch * 96;
        r = ((int)(v.x - e) >= 0) & ((int)(v.y - e) >= 0) & ((int)(v.z - e) >= 0) & ((int)(v.w - e) >= 0);
      } else if (ty == IT_BATT) {
        r = cnt(C_GATE, 16) & cnt(C_QKV + (t >> 1), 10) & cnt(C_QKV + (max(t - 1, 0) >> 1), 10);
      } else {
        r = ty <= IT_QKV || cnt(C_OB + t, 8);
      }
      asm volatile("fence.acquire.gpu; fence.proxy.async.global;" ::: "memory");
      return r;
    };
    if (wid == W_SCH && lane == 0) {
      uint32_t pend = j0 < (uint32_t)NITEMS ? c_items.v[j0] : (uint32_t)IT_END;
      bool xleft = true;
      uint32_t nidx = 0, pidx = j0;
      GTA(1);
      if (j0 < 64) spin_until(c0, ADELAY);
      if (pend != 12345) GTA(2);
#pragma unroll 1
      for (uint32_t e = 0;; e++) {
        if (e) mbar_wait_long(sb + A_REQ, (e - 1) & 1);
        uint32_t item = NONE;
        int rdy = 0, spins = 0;
#pragma unroll 1
        while (true) {
          const bool fresh = pend == NONE;
          if (xleft) {
            const uint4 c = ldg_rlx128(&g_queue[0]);
            const uint32_t pr = ldg_rlx32(&g_prog) - (epoch - 1) * (96 * NSEG);
            const bool gates = cnt(C_GATE, 16);
            if (!fresh) rdy = ready(pend);
            auto full = [](uint32_t v) { v = (v | (v >> 2)) & 0x30303030u; return __popc((v | (v >> 1)) & 0x10101010u); };
            const int t = full(c.x) + full(c.y) + full(c.z) + full(c.w);
            xleft = t < 16;
            if (xleft && gates && (int)pr >= 96 * (4 * t - 8 + (int)((XD >> 4 * t) & 15))) {
              const uint32_t j = (atomicAdd(&g_queue[t >> 2], 1u << (t & 3) * 8) >> (t & 3) * 8) & 255;
              if (j < 16) { item = mk_item(IT_XATT, t, j); rdy = 0; nidx = NITEMS + 132 + t * 16 + j; }
            }
          } else if (!fresh) {
            rdy = ready(pend);
          }
          if (item == NONE) {
            if (fresh) {
              pidx = atomicAdd(&g_queue[32], 1u);
              pend = pidx < (uint32_t)NITEMS ? c_items.v[pidx] : (uint32_t)IT_END;
              rdy = ready(pend);
            }
            const int need = (pend & 7) == IT_OUT && xleft ? (((pend >> 24) + 1) >> 1) - ((pend >> 17) & 127) : 1;
            if (pend == IT_END ? !xleft : rdy >= need) { item = pend; pend = NONE; nidx = pidx; }
          }
          if (item != NONE) break;
          if (++spins > SPIN_MAX) { g_err = 10; item = IT_END; break; }
          __nanosleep(50);
        }
        if (e == 0) GTA(3);
        sts128(sb + A_MAIL, item, rdy, nidx, 0);
        mbar_arrive(sb + A_RSP);
        if (item == IT_END) break;
        if ((item & 7) == IT_XATT) {
#pragma unroll 1
          for (spins = 0; !ready(item); __nanosleep(RSL))
            if (++spins > SPIN_MAX) { g_err = 11; break; }
          mbar_arrive(sb + A_RDY);
        }
      }
      if (atomicAdd(&g_queue[64], 1u) == AUX_GRID - 1) { *(uint4*)g_queue = make_uint4(0, 0, 0, 0); g_queue[32] = 0; g_queue[64] = 0; g_epoch = epoch; }
      asm volatile("griddepcontrol.wait;" ::: "memory");
    } else if (wid == W_PRO) {
      uint32_t xph = 0;
      auto arm = [&](uint32_t bytes) -> uint32_t {
        mbar_wait_u(sb + A_EMPTY + st * 8, ph ^ 1);
        return sb + st * STG;
      };
#pragma unroll 1
      for (uint32_t e = 0;; e++) {
        mbar_wait_long(sb + A_RSP, e & 1);
        const uint4 mail = lds128(sb + A_MAIL);
        asm volatile("fence.proxy.async.global;" ::: "memory");
        const uint32_t item = __shfl_sync(~0u, mail.x, 0);
        const int ty = item & 7, t = (item >> 3) & 31, a = (item >> 8) & 255;
        arm(0);
        if (elect()) {
          sts32(sb + A_ITEM + st * 4, item);
        }
        if (ty == IT_OUT || ty == IT_INIT) {
          const bool out_ = ty == IT_OUT;
          const CUtensorMap *pa = out_ ? &tm.oA : &tm.obA, *pb = out_ ? &tm.wo : &tm.wob;
          int k = out_ ? ((item >> 16) & 255) * 6 : 0;
          const int k1 = out_ ? (item >> 24) * 6 : 20, kreq = max(k1 - KREQ, k);
          int kdep = out_ ? (((item >> 17) & 127) + __shfl_sync(~0u, mail.y, 0)) * 12 : 20;
#pragma unroll 1
          for (; k < k1; k++) {
            if (k >= kdep) {
              int n = 0;
#pragma unroll 1
              while (k >= (kdep = (((item >> 17) & 127) + __shfl_sync(~0u, ready(item), 0)) * 12)) {
                if (++n > SPIN_MAX) { g_err = 7; break; }
                __nanosleep(20);
              }
            }
            PTR((item & 255) == PT && lane == 0, 0, k & 63);
            const uint32_t d = arm(0), fb = sb + A_FULL + st * 8;
            PTR((item & 255) == PT && lane == 0, 1, k & 63);
            if (elect()) {
              mbar_expect(fb, 28672);
              tma_load2(d, pa, k * 32, t * 128, fb);
              tma_load3(d + 8192, pb, 0, k * 32, a * 5, fb);
              if (k == kreq) mbar_arrive(sb + A_REQ);
            }
            PTR((item & 255) == PT && lane == 0, 2, k & 63);
            advance();
          }
        } else if (ty == IT_QKV || ty == IT_XATT) {
          const CUtensorMap* pb = ty == IT_QKV ? &tm.wqkv : &tm.wq;
          const int kreq = ty == IT_QKV ? 20 - KREQ : 28 - KREQ;
#pragma unroll 1
          for (int k = 0; k < 20; k++) {
            PTR((item & 255) == PT && lane == 0, 0, k & 63);
            const uint32_t d = arm(0), fb = sb + A_FULL + st * 8;
            PTR((item & 255) == PT && lane == 0, 1, k & 63);
            if (elect()) {
              mbar_expect(fb, 32768);
              tma_load2(d, &tm.xA, k * 32, t * 128, fb);
              tma_load3(d + 8192, pb, 0, k * 32, a * 6, fb);
              if (k == kreq) mbar_arrive(sb + A_REQ);
            }
            PTR((item & 255) == PT && lane == 0, 2, k & 63);
            advance();
          }
          if (ty == IT_XATT) {
            mbar_wait_long(sb + A_RDY, xph);
            xph ^= 1;
            asm volatile("fence.proxy.async.global;" ::: "memory");
#pragma unroll 1
            for (int k = 20; k < 28; k++) {
              PTR((item & 255) == PT && lane == 0, 0, k & 63);
              const uint32_t d = arm(0), fb = sb + A_FULL + st * 8;
              PTR((item & 255) == PT && lane == 0, 1, k & 63);
              if (elect()) {
                mbar_expect(fb, 30720);
                tma_load3(d, k < 24 ? &tm.k : &tm.v, 0, (4 * t + (k & 2)) * LK, (2 * a + (k & 1)) * 3, fb);
                if (k == kreq) mbar_arrive(sb + A_REQ);
              }
              PTR((item & 255) == PT && lane == 0, 2, k & 63);
              advance();
            }
          }
        } else if (ty == IT_BATT) {
#pragma unroll 1
          for (int k = 0; k < 3; k++) {
            const uint32_t d = arm(0), fb = sb + A_FULL + st * 8;
            if (elect()) {
              mbar_expect(fb, k ? 25600 : 20480);
              tma_load2(d, k ? &tm.qkvK : &tm.qkvQ, k * 640 + a * 160, t * 64 - (k ? 16 : 0), fb);
              if (k == 0) mbar_arrive(sb + A_REQ);
            }
            advance();
          }
        } else {
          if (elect()) { mbar_arrive(sb + A_FULL + st * 8); mbar_arrive(sb + A_REQ); }
          advance();
        }
        if (item == IT_END) break;
        if ((0x4a >> ty) & 1) {
#pragma unroll 1
          for (int k = 0; k < 4; k++) {
            arm(0);
            if (elect()) mbar_arrive(sb + A_FULL + st * 8);
            advance();
          }
        }
      }
    } else if (lane == 0) {
      const uint32_t qb = sb + A_QBAR + (wid == W_AG1) * 64, qe = sb + A_QENT + (wid == W_AG1) * 128;
      for (uint32_t e = 0;; e++) {
        mbar_wait_long(qb + (e & 7) * 8, (e >> 3) & 1);
        const uint4 en = lds128(qe + (e & 7) * 16);
        const int op = en.x & 15, sg = (en.x >> 4) & 15, rel = (en.x >> 8) & 15, nb = (en.x >> 12) & 15;
        if (op == OP_END) break;
        const uint32_t src = sb + sg * STG;
        if (op == OP_OB) tma_store2(&tm.obS, src, en.z, en.y);
        else {
          const CUtensorMap* pm = op == OP_O ? &tm.oS : (op == OP_QKV ? &tm.qkvS : &tm.out);
#pragma unroll 1
          for (int i = 0; i < nb; i++) {
            if (op == OP_ADD) tma_red3(pm, src + i * 8192, 0, en.y, en.z + i); else tma_store3(pm, src + i * 8192, 0, en.y, en.z + i);
            if (SPLITW && i + 1 < nb) { bulk_commit(); bulk_wait_read0(); }
          }
        }
        bulk_commit();
        bulk_wait_read0();
        asm volatile("mbarrier.arrive.shared::cta.b64 _, [%0], %1;" ::"r"(sb + A_EMPTY + sg * 8), "r"(rel) : "memory");
        if (en.w) {
          bulk_wait0();
          asm volatile("red.relaxed.gpu.global.add.u32 [%0], %1;" ::"l"(&g_cnt[(en.w - 1) * 8]), "r"(1) : "memory");
        }
      }
      bulk_wait0();
      if (wid == W_AG1) GTA(7);
    }
  } else {
    asm volatile("setmaxnreg.inc.sync.aligned.u32 232;");
    const int g = wid >> 2, w = wid & 3;
    uint32_t qn = 0;
    auto wait_full = [&]() { mbar_wait_u(sb + A_FULL + st * 8, ph); };
    auto release = [&](uint32_t s_) { if (lane == 0) mbar_arrive(sb + A_EMPTY + s_ * 8); };
    auto take_pair = [&]() -> uint32_t {
      wait_full();
      const uint32_t s0 = st; advance();
      wait_full();
      const uint32_t s1 = st; advance();
      release(g ? s0 : s1);
      return g ? s1 : s0;
    };
    auto push = [&](uint32_t w0, uint32_t w1, uint32_t w2, uint32_t w3) {
      fence_async_smem();
      if (w == 0 && lane == 0) sts128(sb + A_QENT + g * 128 + (qn & 7) * 16, w0, w1, w2, w3);
      __syncwarp();
      if (lane == 0) mbar_arrive(sb + A_QBAR + g * 64 + (qn & 7) * 8);
      qn++;
    };
    const uint32_t stm = (16 * w + (lane & 7) + (lane & 8)) * 128, stx = lane & 7, sth = lane >> 4;
    auto stage_bf16 = [&](uint32_t dst, const float* d, int nks = 12) {
#pragma unroll
      for (int ks = 0; ks < nks; ks++)
        stsm4(dst + (ks >> 2) * 8192 + stm + (((2 * (ks & 3) + sth) ^ stx) << 4), pack2(d[8 * ks], d[8 * ks + 1]), pack2(d[8 * ks + 2], d[8 * ks + 3]),
              pack2(d[8 * ks + 4], d[8 * ks + 5]), pack2(d[8 * ks + 6], d[8 * ks + 7]));
    };
#pragma unroll 1
    while (true) {
      wait_full();
      const uint32_t item = lds32(sb + A_ITEM + st * 4);
      const int ty = item & 7, t = (item >> 3) & 31, a = (item >> 8) & 255;
      if (ty == IT_QKV || ty == IT_XATT) {
        float acc[192] = {};
        uint32_t prev = 0;
#define XG(i) do {} while (0)
#pragma unroll 1
        for (int k = 0; k < 20; k++) {
          if (k) wait_full();
          PTR((item & 255) == PT && tid == 32, 3, k);
          if (LAG && k == (g ? 0 : LAG)) { if (g) bar_sync(7, 256); else bar_arrive(7, 256); }
          const uint32_t s_ = sb + st * STG;
          const Desc da = mk_desc(s_, 16, 512, 2), db = mk_desc(s_ + 8192 + g * 12288, 4096, 1024, 1);
          wg_fence();
          wgmma_ss192t(acc, da, db, k);
          wgmma_ss192t(acc + 96, da + 256, db, k);
          wgmma_ss192t(acc, da + 2, db + 128, 1);
          wgmma_ss192t(acc + 96, da + 258, db + 128, 1);
          wg_commit();
          if (k) { wg_wait1(); release(prev); }
          prev = st; advance();
        }
        uint32_t kst[2];
        if (KEARLY && ty == IT_XATT) { kst[0] = take_pair(); kst[1] = take_pair(); }
        wg_wait0();
        fence_regs<192>(acc);
        release(prev);
        XG(0);
        if (ty == IT_QKV) {
#pragma unroll
          for (int q = 0; q < 2; q++) {
            const uint32_t m = take_pair();
            stage_bf16(sb + m * STG, acc + q * 96);
            push(OP_QKV | (m << 4) | (4 << 8) | (3 << 12), t * 128 + q * 64, a * 6 + g * 3, q ? C_QKV + t + 1 : 0);
          }
        } else {
          uint32_t qf[24][4];
          float sc[2][40], gt[4];
#pragma unroll
          for (int q = 0; q < 2; q++) {
#pragma unroll
            for (int ks = 23; ks >= 0; ks--)
#pragma unroll
              for (int j = 0; j < 4; j++)
                if ((ks >= 12 && ks < 12 + CVTS) == (q == 1))
                  asm volatile("cvt.rn.bf16x2.f32 %0, %1, %2;" : "=r"(qf[ks][j]) : "f"(acc[8 * ks + 2 * j + 1]), "f"(acc[8 * ks + 2 * j]));
            if (!KEARLY) kst[q] = take_pair();
            if (q == 0) XG(1);
            if (q == 0 && XPP && g == 1) bar_sync(6, 256);
            if (q == 1) {
              const float* gp = g_gate + t * 128 + 16 * w + (lane >> 2);
              gt[0] = ldg_cg(gp); gt[1] = ldg_cg(gp + 8); gt[2] = ldg_cg(gp + 64); gt[3] = ldg_cg(gp + 72);
            }
#pragma unroll
            for (int i = 0; i < 40; i++) sc[q][i] = 0.f;
            const Desc db = mk_desc(sb + kst[q] * STG, 16, 1024, 1);
            wg_fence();
#pragma unroll
            for (int ks = 0; ks < 12; ks++) {
              if (XPP && g == 0 && q * 12 + ks == XPP) bar_arrive(6, 256);
              wgmma_rs80(sc[q], qf[q * 12 + ks], db + (((ks >> 2) * 10240 + (ks & 3) * 32) >> 4), ks);
            }
            wg_commit();
          }
          uint32_t pf[2][5][4];
          constexpr float SCL = 0.07216878364870322f * 1.4426950408889634f;
          const uint32_t hi = pin(tid & 64);
          const float c0 = hi ? 0.f : SCL, c1 = hi ? SCL : 0.f;
          float mb[10];
          {
            const int tt = (int)pin(16 * (w & 1) + (lane >> 2) - 2 * (lane & 3));
#pragma unroll
            for (int i = 0; i < 10; i++) mb[i] = 8 * ((i >> 1) - 1) + (i & 1) > tt ? -INFINITY : 0.f;
          }
          auto softmax = [&](const float* s_, uint32_t (&p)[5][4], float g0, float g1) {
            float v[20], mx[2], sum[2];
#pragma unroll
            for (int i = 0; i < 20; i++)
              if (i != 16 && i != 17) v[i] = fmaf(s_[20 + i], c1, i < 4 ? s_[i] * c0 : fmaf(s_[i], c0, mb[2 * ((i >> 2) - ((i >> 1) & 1)) + (i & 1)]));
            mx[0] = fmaxf(fmaxf(fmaxf(v[0], v[1]), fmaxf(v[4], v[5])), fmaxf(fmaxf(v[8], v[9]), fmaxf(v[12], v[13])));
            mx[1] = fmaxf(fmaxf(fmaxf(v[2], v[3]), fmaxf(v[6], v[7])), fmaxf(fmaxf(v[10], v[11]), fmaxf(v[14], v[15])));
            mx[1] = fmaxf(mx[1], fmaxf(v[18], v[19]));
            {
              const float ni = __uint_as_float(0xff800000u | (sb >> 31)), a_ = fminf(mx[0], ni), b_ = fminf(mx[1], ni);
              mx[0] = fmaxf(mx[0], b_); mx[1] = fmaxf(mx[1], a_);
            }
#pragma unroll
            for (int o = 1; o < 4; o <<= 1)
#pragma unroll
              for (int h = 0; h < 2; h++) mx[h] = fmaxf(mx[h], __shfl_xor_sync(~0u, mx[h], o));
#pragma unroll
            for (int i = 0; i < 20; i++) v[i] = i == 16 || i == 17 ? 0.f : ex2(v[i] - mx[(i >> 1) & 1]);
            sum[0] = ((v[0] + v[1]) + (v[4] + v[5])) + ((v[8] + v[9]) + (v[12] + v[13]));
            sum[1] = ((v[2] + v[3]) + (v[6] + v[7])) + ((v[10] + v[11]) + (v[14] + v[15])) + (v[18] + v[19]);
            {
              const float z = __uint_as_float(sb >> 31), a_ = sum[0];
              sum[0] = fmaf(sum[1], z, a_); sum[1] = fmaf(a_, z, sum[1]);
            }
            sum[0] += __shfl_xor_sync(~0u, sum[0], 1);
            sum[1] += __shfl_xor_sync(~0u, sum[1], 1);
            {
              const float z = __uint_as_float(sb >> 31), a_ = sum[0];
              sum[0] = fmaf(sum[1], z, a_); sum[1] = fmaf(a_, z, sum[1]);
            }
            sum[0] += __shfl_xor_sync(~0u, sum[0], 2);
            sum[1] += __shfl_xor_sync(~0u, sum[1], 2);
            const float r0 = g0 * rcp(sum[0]), r1 = g1 * rcp(sum[1]);
#pragma unroll
            for (int j = 0; j < 5; j++)
#pragma unroll
              for (int h = 0; h < 2; h++) {
                const uint32_t pt = j == 4 && h == 0 ? 0u : pack2(v[4 * j + 2 * h] * (h ? r1 : r0), v[4 * j + 2 * h + 1] * (h ? r1 : r0));
                p[j >> 1][(j & 1) * 2 + h] = hi ? 0u : pt;
                p[(j + 5) >> 1][((j + 5) & 1) * 2 + h] = hi ? pt : 0u;
              }
#pragma unroll
            for (int i = 0; i < 20; i++) asm volatile("" : "+r"(p[i >> 2][i & 3]));
          };
          wg_wait1();
          fence_regs<40>(sc[0]);
          XG(2);
          release(kst[0]);
          sched_fence(sb);
          softmax(sc[0], pf[0], gt[0], gt[1]);
          XG(3);
          float o[96] = {};
          auto pv = [&](int q, uint32_t m) {
            const Desc db = mk_desc(sb + m * STG, 10240, 1024, 1);
            wg_fence();
#pragma unroll
            for (int ks = 0; ks < 5; ks++) wgmma_rs192t(o, pf[q][ks], db + ks * 128, ks);
            wg_commit();
          };
          PTR((item & 255) == PT && tid == 32, 3, 24);
          const uint32_t m0 = take_pair();
          PTR((item & 255) == PT && tid == 32, 3, 25);
          pv(0, m0);
          wg_wait1();
          fence_regs<40>(sc[1]);
          release(kst[1]);
          softmax(sc[1], pf[1], gt[2], gt[3]);
          PTR((item & 255) == PT && tid == 32, 3, 26);
          const uint32_t m1 = take_pair();
          PTR((item & 255) == PT && tid == 32, 3, 27);
          wg_wait0();
          fence_regs<96>(o);
          XG(4);
#pragma unroll
          for (int i = 0; i < 48; i++) asm volatile("cvt.rn.bf16x2.f32 %0, %1, %2;" : "=r"(qf[i >> 2][i & 3]) : "f"(o[2 * i + 1]), "f"(o[2 * i]));
          pv(1, m1);
          bar_sync(1 + g, 128);
#pragma unroll
          for (int ks = 0; ks < 12; ks++)
            stsm4(sb + m0 * STG + (ks >> 2) * 8192 + stm + (((2 * (ks & 3) + sth) ^ stx) << 4), qf[ks][0], qf[ks][1], qf[ks][2], qf[ks][3]);
          push(OP_O | (m0 << 4) | (4 << 8) | (3 << 12), t * 128, a * 6 + g * 3, 0);
          XG(5);
          wg_wait0();
          fence_regs<96>(o);
          XG(6);
          bar_sync(1 + g, 128);
          stage_bf16(sb + m1 * STG, o);
          push(OP_O | (m1 << 4) | (4 << 8) | (3 << 12), t * 128 + 64, a * 6 + g * 3, C_O + t * 16 + a + 1);
          XG(7);
        }
      } else if (ty == IT_OUT || ty == IT_INIT) {
        float acc[160] = {};
        const int hb = (item >> 16) & 255, nh = (item >> 24) - hb, nk = ty == IT_OUT ? nh * 6 : 20, jh = a & 1;
        const uint32_t ln = pin(lane), ao = (g * 64 + 16 * w + (ln & 15)) * 64 + (((ln >> 4) ^ ((ln >> 1) & 3)) << 4);
        if (PP && g == 1) bar_arrive(4, 256);
#pragma unroll 1
        for (int k = 0; k < nk; k += 2) {
          uint32_t af[4][4], sg[2];
#pragma unroll
          for (int e = 0; e < 2; e++) {
            if (k + e) wait_full();
            sg[e] = st;
            ldsm4(af[2 * e], sb + st * STG + ao);
            ldsm4(af[2 * e + 1], sb + st * STG + (ao ^ 32));
            advance();
          }
          if (PP) bar_sync(4 + g, 256);
          wg_fence();
#pragma unroll
          for (int e = 0; e < 4; e++) {
            const Desc db = mk_desc(sb + sg[e >> 1] * STG + 8192 + (e & 1) * 2048, 4096, 1024, 1);
            if (PP == 2 && e == 3 && (g == 0 || k + 2 < nk)) bar_arrive(5 - g, 256);
            wgmma_rs192t(acc, af[e], db, 1);
            if (PP == 3 && e == 3 && (g == 0 || k + 2 < nk)) bar_arrive(5 - g, 256);
            wgmma_rs128t(acc + 96, af[e], db + 768, 1);
          }
          wg_commit();
          if (PP == 1 && (g == 0 || k + 2 < nk)) bar_arrive(5 - g, 256);
          wg_wait0();
          release(sg[0]); release(sg[1]);
        }
        fence_regs<160>(acc);
        const uint32_t row = t * 128 + g * 64;
#pragma unroll
        for (int q = 0; q < 2; q++) {
          const uint32_t m = take_pair();
          stage_bf16(sb + m * STG, acc + q * 96, q ? 8 : 12);
          push((ty == IT_OUT ? OP_ADD : OP_SET) | (m << 4) | (4 << 8) | ((3 - q) << 12), row, jh * 5 + q * 3, q && ty == IT_INIT ? C_ACC + t + 1 : 0);
        }
      } else if (ty == IT_BATT) {
        const uint32_t sq = st; advance();
        wait_full();
        const uint32_t sk = st; advance();
        wait_full();
        const uint32_t sv = st; advance();
        const int h = tid & 7;
#pragma unroll 1
        for (int p = 0; p < 2; p++) {
          const int tok = (tid >> 3) + 32 * p, pos = t * 64 + tok;
          const uint32_t qa = sb + sq * STG + tok * 320 + h * 40, ka = sb + sk * STG + (tok + 16) * 320 + h * 40, va = sb + sv * STG + (tok + 16) * 320 + h * 40;
          const float gt = __ldcg(g_gate + 2048 + pos);
          float q[20], l[8];
#pragma unroll
          for (int i = 0; i < 5; i++) { const uint2 u = lds64(qa + i * 8); q[4 * i] = bf_lo(u.x); q[4 * i + 1] = bf_hi(u.x); q[4 * i + 2] = bf_lo(u.y); q[4 * i + 3] = bf_hi(u.y); }
          float mx = -INFINITY;
#pragma unroll
          for (int j = 0; j < 8; j++) {
            float s0 = 0.f, s1 = 0.f;
#pragma unroll
            for (int i = 0; i < 5; i++) {
              const uint2 u = lds64(ka - j * 640 + i * 8);
              s0 = fmaf(q[4 * i], bf_lo(u.x), s0); s1 = fmaf(q[4 * i + 1], bf_hi(u.x), s1);
              s0 = fmaf(q[4 * i + 2], bf_lo(u.y), s0); s1 = fmaf(q[4 * i + 3], bf_hi(u.y), s1);
            }
            l[j] = pos - 2 * j >= 0 ? s0 + s1 : -INFINITY;
            mx = fmaxf(mx, l[j]);
          }
          constexpr float SCL = 0.22360679774997896f * 1.4426950408889634f;
          const float mo = mx * SCL;
          float sum = 0.f;
#pragma unroll
          for (int j = 0; j < 8; j++) { l[j] = ex2(fmaf(l[j], SCL, -mo)); sum += l[j]; }
          const float r = gt * rcp(sum);
#pragma unroll
          for (int i = 0; i < 20; i++) q[i] = 0.f;
#pragma unroll
          for (int j = 0; j < 8; j++) {
#pragma unroll
            for (int i = 0; i < 5; i++) {
              const uint2 u = lds64(va - j * 640 + i * 8);
              q[4 * i] = fmaf(l[j], bf_lo(u.x), q[4 * i]); q[4 * i + 1] = fmaf(l[j], bf_hi(u.x), q[4 * i + 1]);
              q[4 * i + 2] = fmaf(l[j], bf_lo(u.y), q[4 * i + 2]); q[4 * i + 3] = fmaf(l[j], bf_hi(u.y), q[4 * i + 3]);
            }
          }
#pragma unroll
          for (int i = 0; i < 5; i++) sts64(qa + i * 8, pack2(q[4 * i] * r, q[4 * i + 1] * r), pack2(q[4 * i + 2] * r, q[4 * i + 3] * r));
        }
        __syncwarp();
        release(sk); release(sv);
        fence_async_smem();
        bar_sync(3, 256);
        if (g == 0) push(OP_OB | (sq << 4) | (8 << 8), t * 64, a * 160, C_OB + (t >> 1) + 1);
      } else if (ty == IT_GATE) {
        release(st); advance();
        uint4 gw[3];
#pragma unroll
        for (int i = 0; i < 3; i++) gw[i] = (i < 2 || lane < 16) ? __ldg((const uint4*)gate_w + lane + 32 * i) : make_uint4(0, 0, 0, 0);
        const uint4* xr = (const uint4*)(x + (size_t)(t * 128 + wid * 16) * DM) + lane;
        uint4 v[16][3];
#pragma unroll
        for (int r = 0; r < 16; r++)
#pragma unroll
          for (int i = 0; i < 3; i++) v[r][i] = (i < 2 || lane < 16) ? __ldg(xr + r * (DM / 8) + 32 * i) : make_uint4(0, 0, 0, 0);
        float z = 0.f;
#pragma unroll
        for (int r = 0; r < 16; r++) {
          float s_ = 0.f;
#pragma unroll
          for (int i = 0; i < 3; i++) {
            const uint32_t p0 = hmul2(v[r][i].x, gw[i].x), p1 = hmul2(v[r][i].y, gw[i].y), p2 = hmul2(v[r][i].z, gw[i].z), p3 = hmul2(v[r][i].w, gw[i].w);
            s_ += ((bf_lo(p0) + bf_hi(p0)) + (bf_lo(p1) + bf_hi(p1))) + ((bf_lo(p2) + bf_hi(p2)) + (bf_lo(p3) + bf_hi(p3)));
          }
#pragma unroll
          for (int o = 16; o; o >>= 1) s_ += __shfl_xor_sync(~0u, s_, o);
          if (lane == r) z = s_;
        }
        z = bf_lo(pack2(z, 0.f));
        const float gv = bf_lo(pack2(1.f / (1.f + __expf(-z)), 0.f));
        if (lane < 16) { g_gate[t * 128 + wid * 16 + lane] = gv; g_gate[2048 + t * 128 + wid * 16 + lane] = bf_lo(pack2(1.f - gv, 0.f)); }
        __threadfence();
        bar_sync(3, 256);
        if (tid == 0) asm volatile("red.release.gpu.global.add.u32 [%0], 1;" ::"l"(&g_cnt[C_GATE * 8]) : "memory");
      } else {
        release(st);
        push(OP_END, 0, 0, 0);
        break;
      }
    }
  }
}

typedef CUresult (*EncFn)(CUtensorMap*, CUtensorMapDataType, cuuint32_t, void*, const cuuint64_t*, const cuuint64_t*, const cuuint32_t*,
                          const cuuint32_t*, CUtensorMapInterleave, CUtensorMapSwizzle, CUtensorMapL2promotion, CUtensorMapFloatOOBfill);

#define PROMO CU_TENSOR_MAP_L2_PROMOTION_L2_128B
void make_map(EncFn enc, CUtensorMap* tm, const void* base, int rank, const cuuint64_t* dims, const cuuint64_t* strides, const cuuint32_t* box,
              CUtensorMapSwizzle sw = CU_TENSOR_MAP_SWIZZLE_128B, CUtensorMapDataType dt = CU_TENSOR_MAP_DATA_TYPE_BFLOAT16) {
  const cuuint32_t es[5] = {1, 1, 1, 1, 1};
  enc(tm, dt, rank, const_cast<void*>(base), dims, strides, box, es, CU_TENSOR_MAP_INTERLEAVE_NONE, sw, PROMO,
      CU_TENSOR_MAP_FLOAT_OOB_FILL_NONE);
}
void map_blk(EncFn enc, CUtensorMap* tm, const void* base, int rows, int cols, int brows, int bblk) {
  const cuuint64_t d[3] = {64, (cuuint64_t)rows, (cuuint64_t)cols / 64}, st[2] = {(cuuint64_t)cols * 2, 128};
  const cuuint32_t b[3] = {64, (cuuint32_t)brows, (cuuint32_t)bblk};
  make_map(enc, tm, base, 3, d, st, b);
}
void map_2d(EncFn enc, CUtensorMap* tm, const void* base, int rows, int cols, int brows, int bcols, CUtensorMapSwizzle sw) {
  const cuuint64_t d[2] = {(cuuint64_t)cols, (cuuint64_t)rows}, st[1] = {(cuuint64_t)cols * 2};
  const cuuint32_t b[2] = {(cuuint32_t)bcols, (cuuint32_t)brows};
  make_map(enc, tm, base, 2, d, st, b, sw);
}

}

extern "C" void kernel_launch(void* const* d_in, const int* in_sizes, int n_in, void* d_out, int out_size) {
  const bf16* x = (const bf16*)d_in[0];
  const bf16* mem0 = (const bf16*)d_in[1];
  const bf16* Wq = (const bf16*)d_in[2];
  const bf16* Wk = (const bf16*)d_in[3];
  const bf16* Wv = (const bf16*)d_in[4];
  const bf16* Wo = (const bf16*)d_in[5];
  const bf16* wqkv = (const bf16*)d_in[8];
  const bf16* wob = (const bf16*)d_in[9];
  const bf16* gate_w = (const bf16*)d_in[10];
  static EncFn enc = nullptr;
  static void *pR = nullptr, *pK = nullptr, *pV = nullptr, *pO = nullptr, *pQ = nullptr, *pB = nullptr;
  if (!enc) {
    void* fn = nullptr;
    cudaDriverEntryPointQueryResult qr;
    cudaGetDriverEntryPoint("cuTensorMapEncodeTiled", &fn, cudaEnableDefault, &qr);
    enc = (EncFn)fn;
    cudaGetSymbolAddress(&pR, g_red);
    cudaGetSymbolAddress(&pK, g_K);
    cudaGetSymbolAddress(&pV, g_V);
    cudaGetSymbolAddress(&pO, g_O);
    cudaGetSymbolAddress(&pQ, g_qkv);
    cudaGetSymbolAddress(&pB, g_Ob);
    cudaFuncSetAttribute(rec_kernel, cudaFuncAttributeMaxDynamicSharedMemorySize, R_SMEM_ALLOC);
    cudaFuncSetAttribute(aux_kernel, cudaFuncAttributeMaxDynamicSharedMemorySize, A_SMEM);
  }
  CUtensorMap tmX, tmK, tmV, tmWq, tmWq2, tmWk, tmWv, tmWo;
  map_2d(enc, &tmWq, Wq, DM, HD, 144, 64, CU_TENSOR_MAP_SWIZZLE_128B);
  map_2d(enc, &tmWq2, Wq, DM, HD, 32, 64, CU_TENSOR_MAP_SWIZZLE_128B);
  map_2d(enc, &tmWk, Wk, DM, HD, 128, 64, CU_TENSOR_MAP_SWIZZLE_128B);
  map_2d(enc, &tmWv, Wv, DM, HD, 128, 64, CU_TENSOR_MAP_SWIZZLE_128B);
  {
    const cuuint64_t d[3] = {32, HD, 20}, st[2] = {DM * 2, 64};
    const cuuint32_t b[3] = {32, 64, 7};
    make_map(enc, &tmWo, Wo, 3, d, st, b, CU_TENSOR_MAP_SWIZZLE_64B);
  }
  map_blk(enc, &tmX, x, S_TOK, DM, 32, 10);
  map_2d(enc, &tmK, pK, NSEG * LK, HD, LK, 64, CU_TENSOR_MAP_SWIZZLE_128B);
  map_2d(enc, &tmV, pV, NSEG * LK, HD, LK, 64, CU_TENSOR_MAP_SWIZZLE_128B);
  AuxMaps am;
  map_2d(enc, &am.xA, x, S_TOK, DM, 128, 32, CU_TENSOR_MAP_SWIZZLE_64B);
  map_blk(enc, &am.wq, Wq, DM, HD, 32, 6);
  map_blk(enc, &am.wqkv, wqkv, DM, 3 * DM, 32, 6);
  map_blk(enc, &am.wo, Wo, HD, DM, 32, 5);
  map_blk(enc, &am.wob, wob, DM, DM, 32, 5);
  map_blk(enc, &am.k, pK, NSEG * LK, HD, 80, 3);
  map_blk(enc, &am.v, pV, NSEG * LK, HD, 80, 3);
  map_2d(enc, &am.oA, pO, S_TOK, HD, 128, 32, CU_TENSOR_MAP_SWIZZLE_64B);
  map_blk(enc, &am.oS, pO, S_TOK, HD, 64, 1);
  map_2d(enc, &am.obA, pB, S_TOK, DM, 128, 32, CU_TENSOR_MAP_SWIZZLE_64B);
  map_2d(enc, &am.obS, pB, S_TOK, DM, 64, 160, CU_TENSOR_MAP_SWIZZLE_NONE);
  map_blk(enc, &am.qkvS, pQ, S_TOK, 3 * DM, 64, 1);
  map_2d(enc, &am.qkvQ, pQ, S_TOK, 3 * DM, 64, 160, CU_TENSOR_MAP_SWIZZLE_NONE);
  map_2d(enc, &am.qkvK, pQ, S_TOK, 3 * DM, 80, 160, CU_TENSOR_MAP_SWIZZLE_NONE);
  map_blk(enc, &am.out, d_out, S_TOK, DM, 64, 1);
  rec_kernel<<<96, 256, R_SMEM_ALLOC, cudaStreamPerThread>>>(tmX, tmK, tmV, tmWq, tmWq2, tmWk, tmWv, tmWo, mem0, Wq, Wo, x,
                                                               (unsigned char*)(((uintptr_t)pR + 0x1fffff) & ~(uintptr_t)0x1fffff));
  cudaLaunchConfig_t cfg = {};
  cfg.gridDim = dim3(AUX_GRID); cfg.blockDim = dim3(384); cfg.dynamicSmemBytes = A_SMEM; cfg.stream = cudaStreamPerThread;
  cudaLaunchAttribute at[1];
  at[0].id = cudaLaunchAttributeProgrammaticStreamSerialization;
  at[0].val.programmaticStreamSerializationAllowed = 1;
  cfg.attrs = at;
  cfg.numAttrs = 1;
  cudaLaunchKernelEx(&cfg, aux_kernel, am, x, gate_w);
}
```

```cpp
#include <cuda_runtime.h>
#include <cuda_bf16.h>
#include <cuda.h>
#include <stdint.h>
#include <type_traits>

typedef __nv_bfloat16 bf16;

namespace {

constexpr int S_TOK = 2048, DM = 640, NH = 32, DH = 192, HD = NH * DH, SEG = 32, NSEG = 64, MT = 8, LK = 40;
constexpr int SPIN_MAX = 1 << 20, NGATE = 96;

__device__ __align__(4096) unsigned char g_red[(2 << 20) + (640 << 10)];
__host__ __device__ constexpr uint32_t rb_q(int q) { return (q < 5 ? q : q - 5) * 131072 + (uint32_t)((0x3122120330ull >> 4 * q) & 15) * 2048; }
__host__ __device__ constexpr uint32_t rb_j(int j) { return (j & 1) * 256 + (j & 2) * 512 + (j & 12) * 2048; }
__host__ __device__ constexpr uint32_t rb_b(int b) { return (b & 1) * 128 + (b & 2) * 256; }
__device__ unsigned long long g_rec[96];
__device__ uint32_t g_epoch;
__device__ uint32_t g_err;
__device__ __align__(16) uint32_t g_segcnt[NSEG];
__device__ __align__(1024) bf16 g_K[NSEG * LK * HD];
__device__ __align__(1024) bf16 g_V[NSEG * LK * HD];
__device__ __align__(1024) bf16 g_O[S_TOK * HD];
__device__ __align__(1024) uint4 g_Ql[NH * 2 * 4 * 12 * 32];
__device__ __align__(1024) bf16 g_qkv[S_TOK * 3 * DM];
__device__ __align__(1024) bf16 g_Ob[S_TOK * DM];
__device__ float g_gate[2 * S_TOK];
__device__ uint32_t g_cnt[512 * 8];
constexpr int C_GATE = 0, C_QKV = 16, C_OB = 32, C_ACC = 48, C_O = 80;
__device__ __align__(128) uint32_t g_queue[3 * 32];
__device__ uint32_t g_prog;
#define GTR(i) do {} while (0)
#define GTA(i) do {} while (0)
#define PTR(c, r, k) do {} while (0)

__device__ __forceinline__ uint32_t smem_u32(const void* p) { return (uint32_t)__cvta_generic_to_shared(p); }
__device__ __forceinline__ uint32_t clk32() { uint32_t t; asm volatile("mov.u32 %0, %%clock;" : "=r"(t)::"memory"); return t; }
__device__ __forceinline__ uint32_t mapa(uint32_t a, uint32_t r) { uint32_t o; asm("mapa.shared::cluster.u32 %0, %1, %2;" : "=r"(o) : "r"(a), "r"(r)); return o; }
__device__ __forceinline__ void mbar_init(uint32_t b, uint32_t c) { asm volatile("mbarrier.init.shared::cta.b64 [%0], %1;" ::"r"(b), "r"(c) : "memory"); }
__device__ __forceinline__ void mbar_expect(uint32_t b, uint32_t bytes) { asm volatile("mbarrier.arrive.expect_tx.shared::cta.b64 _, [%0], %1;" ::"r"(b), "r"(bytes) : "memory"); }
__device__ __forceinline__ void mbar_arrive(uint32_t b) { asm volatile("mbarrier.arrive.shared::cta.b64 _, [%0];" ::"r"(b) : "memory"); }
__device__ __forceinline__ bool mbar_try(uint32_t b, uint32_t par) {
  uint32_t p;
  asm volatile("{.reg .pred p; mbarrier.try_wait.parity.shared::cta.b64 p, [%1], %2; selp.u32 %0,1,0,p;}" : "=r"(p) : "r"(b), "r"(par) : "memory");
  return p;
}
__device__ __forceinline__ bool mbar_test(uint32_t b, uint32_t par) {
  uint32_t p;
  asm volatile("{.reg .pred p; mbarrier.test_wait.parity.shared::cta.b64 p, [%1], %2; selp.u32 %0,1,0,p;}" : "=r"(p) : "r"(b), "r"(par) : "memory");
  return p;
}
__device__ __forceinline__ bool mbar_try_cl(uint32_t b, uint32_t par) {
  uint32_t p;
  asm volatile("{.reg .pred p; mbarrier.try_wait.parity.acquire.cluster.shared::cta.b64 p, [%1], %2; selp.u32 %0,1,0,p;}" : "=r"(p) : "r"(b), "r"(par) : "memory");
  return p;
}
__device__ __forceinline__ void mbar_wait(uint32_t b, uint32_t par) {
  int n = 0;
#pragma unroll 1
  while (!mbar_try(b, par)) { if (++n > SPIN_MAX) { g_err = 1; break; } }
}
__device__ __forceinline__ void mbar_wait_cl(uint32_t b, uint32_t par) {
  int n = 0;
#pragma unroll 1
  while (!mbar_try_cl(b, par)) { if (++n > SPIN_MAX) { g_err = 2; break; } }
}
__device__ __forceinline__ void cluster_sync() { asm volatile("barrier.cluster.arrive.release.aligned; barrier.cluster.wait.acquire.aligned;" ::: "memory"); }
__device__ __forceinline__ void bar_sync(int id, int n) { asm volatile("bar.sync %0, %1;" ::"r"(id), "r"(n) : "memory"); }
__device__ __forceinline__ void bar_arrive(int id, int n) { asm volatile("bar.arrive %0, %1;" ::"r"(id), "r"(n) : "memory"); }
__device__ __forceinline__ void fence_async_smem() { asm volatile("fence.proxy.async.shared::cta;" ::: "memory"); }
__device__ __forceinline__ void ldsm4(uint32_t* r, uint32_t a) {
  asm volatile("ldmatrix.sync.aligned.m8n8.x4.shared.b16 {%0,%1,%2,%3}, [%4];" : "=r"(r[0]), "=r"(r[1]), "=r"(r[2]), "=r"(r[3]) : "r"(a) : "memory");
}
__device__ __forceinline__ void ldsm4t(uint32_t* r, uint32_t a) {
  asm volatile("ldmatrix.sync.aligned.m8n8.x4.trans.shared.b16 {%0,%1,%2,%3}, [%4];" : "=r"(r[0]), "=r"(r[1]), "=r"(r[2]), "=r"(r[3]) : "r"(a) : "memory");
}
__device__ __forceinline__ void ldsm2t(uint32_t* r, uint32_t a) {
  asm volatile("ldmatrix.sync.aligned.m8n8.x2.trans.shared.b16 {%0,%1}, [%2];" : "=r"(r[0]), "=r"(r[1]) : "r"(a) : "memory");
}
__device__ __forceinline__ void stsm4t(uint32_t a, uint32_t r0, uint32_t r1, uint32_t r2, uint32_t r3) {
  asm volatile("stmatrix.sync.aligned.m8n8.x4.trans.shared.b16 [%0], {%1,%2,%3,%4};" ::"r"(a), "r"(r0), "r"(r1), "r"(r2), "r"(r3) : "memory");
}
__device__ __forceinline__ void stsm2t(uint32_t a, uint32_t r0, uint32_t r1) {
  asm volatile("stmatrix.sync.aligned.m8n8.x2.trans.shared.b16 [%0], {%1,%2};" ::"r"(a), "r"(r0), "r"(r1) : "memory");
}
__device__ __forceinline__ uint32_t movmat(uint32_t a) { uint32_t d; asm volatile("movmatrix.sync.aligned.m8n8.trans.b16 %0, %1;" : "=r"(d) : "r"(a)); return d; }
__device__ __forceinline__ void mma16816(float* d, const uint32_t* a, uint32_t b0, uint32_t b1) {
  asm volatile("mma.sync.aligned.m16n8k16.row.col.f32.bf16.bf16.f32 {%0,%1,%2,%3}, {%4,%5,%6,%7}, {%8,%9}, {%0,%1,%2,%3};"
               : "+f"(d[0]), "+f"(d[1]), "+f"(d[2]), "+f"(d[3]) : "r"(a[0]), "r"(a[1]), "r"(a[2]), "r"(a[3]), "r"(b0), "r"(b1));
}
__device__ __forceinline__ void mma1688(float* d, uint32_t a0, uint32_t a1, uint32_t b0) {
  asm volatile("mma.sync.aligned.m16n8k8.row.col.f32.bf16.bf16.f32 {%0,%1,%2,%3}, {%4,%5}, {%6}, {%0,%1,%2,%3};"
               : "+f"(d[0]), "+f"(d[1]), "+f"(d[2]), "+f"(d[3]) : "r"(a0), "r"(a1), "r"(b0));
}
__device__ __forceinline__ uint32_t pack2(float lo, float hi) { uint32_t r; asm("cvt.rn.bf16x2.f32 %0, %1, %2;" : "=r"(r) : "f"(hi), "f"(lo)); return r; }
__device__ __forceinline__ float bf_lo(uint32_t w) { return __uint_as_float(w << 16); }
__device__ __forceinline__ float bf_hi(uint32_t w) { return __uint_as_float(w & 0xffff0000u); }
__device__ __forceinline__ float ex2(float x) { float y; asm("ex2.approx.ftz.f32 %0, %1;" : "=f"(y) : "f"(x)); return y; }
__device__ __forceinline__ void sts128(uint32_t a, uint32_t x, uint32_t y, uint32_t z, uint32_t w) { asm volatile("st.shared.v4.b32 [%0], {%1,%2,%3,%4};" ::"r"(a), "r"(x), "r"(y), "r"(z), "r"(w) : "memory"); }
__device__ __forceinline__ void sts128f(uint32_t a, float x, float y, float z, float w) { asm volatile("st.shared.v4.f32 [%0], {%1,%2,%3,%4};" ::"r"(a), "f"(x), "f"(y), "f"(z), "f"(w) : "memory"); }
__device__ __forceinline__ void sts64f(uint32_t a, float x, float y) { asm volatile("st.shared.v2.f32 [%0], {%1,%2};" ::"r"(a), "f"(x), "f"(y) : "memory"); }
__device__ __forceinline__ void sts32(uint32_t a, uint32_t x) { asm volatile("st.shared.b32 [%0], %1;" ::"r"(a), "r"(x) : "memory"); }
__device__ __forceinline__ void smax32(uint32_t a, uint32_t x) { asm volatile("red.shared.max.u32 [%0], %1;" ::"r"(a), "r"(x) : "memory"); }
__device__ __forceinline__ uint32_t lds32(uint32_t a) { uint32_t v; asm volatile("ld.shared.b32 %0, [%1];" : "=r"(v) : "r"(a) : "memory"); return v; }
__device__ __forceinline__ float4 lds128f(uint32_t a) { float4 v; asm volatile("ld.shared.v4.f32 {%0,%1,%2,%3}, [%4];" : "=f"(v.x), "=f"(v.y), "=f"(v.z), "=f"(v.w) : "r"(a) : "memory"); return v; }
__device__ __forceinline__ uint4 lds128(uint32_t a) { uint4 v; asm volatile("ld.shared.v4.b32 {%0,%1,%2,%3}, [%4];" : "=r"(v.x), "=r"(v.y), "=r"(v.z), "=r"(v.w) : "r"(a) : "memory"); return v; }
__device__ __forceinline__ float2 lds64f(uint32_t a) { float2 v; asm volatile("ld.shared.v2.f32 {%0,%1}, [%2];" : "=f"(v.x), "=f"(v.y) : "r"(a) : "memory"); return v; }
__device__ __forceinline__ void st_async2(uint32_t a, uint32_t x, uint32_t y, uint32_t bar) {
  asm volatile("st.async.weak.shared::cluster.mbarrier::complete_tx::bytes.v2.b32 [%0], {%1,%2}, [%3];" ::"r"(a), "r"(x), "r"(y), "r"(bar) : "memory");
}
__device__ __forceinline__ void st_async4(uint32_t a, uint32_t x, uint32_t y, uint32_t z, uint32_t w, uint32_t bar) {
  asm volatile("st.async.weak.shared::cluster.mbarrier::complete_tx::bytes.v4.b32 [%0], {%1,%2,%3,%4}, [%5];" ::"r"(a), "r"(x), "r"(y), "r"(z), "r"(w), "r"(bar) : "memory");
}
__device__ __forceinline__ void sts64(uint32_t a, uint32_t x, uint32_t y) { asm volatile("st.shared.v2.b32 [%0], {%1,%2};" ::"r"(a), "r"(x), "r"(y) : "memory"); }
__device__ __forceinline__ bool bar_red_or(int id, int n, bool q) {
  uint32_t r;
  asm volatile("{.reg .pred p, q; setp.ne.u32 q, %3, 0; barrier.cta.red.or.aligned.pred p, %1, %2, q; selp.u32 %0,1,0,p;}" : "=r"(r) : "r"(id), "r"(n), "r"((uint32_t)q) : "memory");
  return r;
}
__device__ __forceinline__ float rcp(float x) { float y; asm("rcp.approx.ftz.f32 %0, %1;" : "=f"(y) : "f"(x)); return y; }
__device__ __forceinline__ uint32_t hadd2(uint32_t a, uint32_t b) { uint32_t r; asm("add.rn.bf16x2 %0, %1, %2;" : "=r"(r) : "r"(a), "r"(b)); return r; }
__device__ __forceinline__ uint32_t pin(uint32_t v) { asm volatile("" : "+r"(v)); return v; }
template <int ID> __device__ __forceinline__ void sched_fence_(uint32_t a) {
  asm volatile("{.reg .pred p;\nsetp.eq.u32 p, %0, %1;\nSF: @p pmevent 0;\n@p bra.uni SF;}" ::"r"(a), "n"(0x40000000 + ID) : "memory");
}
#define sched_fence(a) sched_fence_<__LINE__>(a)
__device__ __forceinline__ bool elect() {
  uint32_t p;
  asm volatile("{.reg .pred p; elect.sync _|p, 0xffffffff; selp.u32 %0,1,0,p;}" : "=r"(p));
  return p;
}
__device__ __forceinline__ uint32_t opaque(uint32_t v) { return __shfl_sync(~0u, v, threadIdx.x & 31); }
__device__ __forceinline__ uint4 ldg_rlx128(const void* p) {
  uint4 v; asm volatile("ld.relaxed.gpu.global.v4.b32 {%0,%1,%2,%3}, [%4];" : "=r"(v.x), "=r"(v.y), "=r"(v.z), "=r"(v.w) : "l"(p) : "memory"); return v;
}
__device__ __forceinline__ uint2 ldg_rlx64(const void* p) {
  uint2 v; asm volatile("{.reg .b64 t; ld.relaxed.gpu.global.b64 t, [%2]; mov.b64 {%0,%1}, t;}" : "=r"(v.x), "=r"(v.y) : "l"(p) : "memory"); return v;
}
__device__ __forceinline__ uint32_t hmaxabs2(uint32_t a, uint32_t b) { uint32_t r; asm("max.xorsign.abs.bf16x2 %0, %1, %2;" : "=r"(r) : "r"(a), "r"(b)); return r; }
__device__ __forceinline__ uint32_t ldg_rlx32(const void* p) {
  uint32_t v; asm volatile("ld.relaxed.gpu.global.b32 %0, [%1];" : "=r"(v) : "l"(p) : "memory"); return v;
}
__device__ __forceinline__ float ldg_cg(const float* p) { float v; asm volatile("ld.global.cg.f32 %0, [%1];" : "=f"(v) : "l"(p) : "memory"); return v; }
__device__ __forceinline__ void spin_until(uint32_t t0, int d) {
#pragma unroll 1
  while (clk32() - t0 < (uint32_t)d) {}
}
__device__ __forceinline__ void stg_rlx64(void* p, uint32_t a, uint32_t b) {
  asm volatile("{.reg .b64 t; mov.b64 t, {%1,%2}; st.relaxed.gpu.global.b64 [%0], t;}" ::"l"(p), "r"(a), "r"(b) : "memory");
}
__device__ __forceinline__ uint32_t ldg_acq32(const void* p) { uint32_t v; asm volatile("ld.acquire.gpu.global.b32 %0, [%1];" : "=r"(v) : "l"(p) : "memory"); return v; }
__device__ __forceinline__ void stg_rel32(void* p, uint32_t v) { asm volatile("st.release.gpu.global.b32 [%0], %1;" ::"l"(p), "r"(v) : "memory"); }
__device__ __forceinline__ void cp_async16(uint32_t dst, const void* src) { asm volatile("cp.async.cg.shared.global [%0], [%1], 16;" ::"r"(dst), "l"(src) : "memory"); }
__device__ __forceinline__ void cp_async_wait_all() { asm volatile("cp.async.wait_all;" ::: "memory"); }
__device__ __forceinline__ void prefetch_l2(const void* p) { asm volatile("prefetch.global.L2 [%0];" ::"l"(p)); }
__device__ __forceinline__ void tma_load3(uint32_t dst, const CUtensorMap* tm, int c0, int c1, int c2, uint32_t bar) {
  asm volatile("cp.async.bulk.tensor.3d.shared::cluster.global.mbarrier::complete_tx::bytes [%0], [%1, {%3,%4,%5}], [%2];"
               ::"r"(dst), "l"(tm), "r"(bar), "r"(c0), "r"(c1), "r"(c2) : "memory");
}
__device__ __forceinline__ void tma_load2(uint32_t dst, const CUtensorMap* tm, int c0, int c1, uint32_t bar) {
  asm volatile("cp.async.bulk.tensor.2d.shared::cluster.global.mbarrier::complete_tx::bytes [%0], [%1, {%3,%4}], [%2];"
               ::"r"(dst), "l"(tm), "r"(bar), "r"(c0), "r"(c1) : "memory");
}
__device__ __forceinline__ void bulk_load(uint32_t dst, const void* src, uint32_t bytes, uint32_t bar) {
  asm volatile("cp.async.bulk.shared::cluster.global.mbarrier::complete_tx::bytes [%0], [%1], %2, [%3];" ::"r"(dst), "l"(src), "r"(bytes), "r"(bar) : "memory");
}
__device__ __forceinline__ void bulk_s2s(uint32_t dst, uint32_t src, uint32_t bytes, uint32_t bar) {
  asm volatile("cp.async.bulk.shared::cluster.shared::cta.mbarrier::complete_tx::bytes [%0], [%1], %2, [%3];" ::"r"(dst), "r"(src), "r"(bytes), "r"(bar) : "memory");
}
__device__ __forceinline__ void prefetch_map(const CUtensorMap* tm) { asm volatile("prefetch.tensormap [%0];" ::"l"(tm) : "memory"); }
__device__ __forceinline__ void tma_store2(const CUtensorMap* tm, uint32_t src, int c0, int c1) {
  asm volatile("cp.async.bulk.tensor.2d.global.shared::cta.bulk_group [%0, {%2,%3}], [%1];" ::"l"(tm), "r"(src), "r"(c0), "r"(c1) : "memory");
}
__device__ __forceinline__ void bulk_commit() { asm volatile("cp.async.bulk.commit_group;" ::: "memory"); }
__device__ __forceinline__ void bulk_wait0() { asm volatile("cp.async.bulk.wait_group 0;" ::: "memory"); }
__device__ __forceinline__ void bulk_wait_read0() { asm volatile("cp.async.bulk.wait_group.read 0;" ::: "memory"); }
__device__ __forceinline__ void wg_fence() { asm volatile("wgmma.fence.sync.aligned;" ::: "memory"); }
__device__ __forceinline__ void wg_commit() { asm volatile("wgmma.commit_group.sync.aligned;" ::: "memory"); }
__device__ __forceinline__ void wg_wait0() { asm volatile("wgmma.wait_group.sync.aligned 0;" ::: "memory"); }
__device__ __forceinline__ uint64_t desc_sw128(uint32_t addr) {
  return (uint64_t)((addr & 0x3FFFF) >> 4) | ((uint64_t)1 << 16) | ((uint64_t)64 << 32) | ((uint64_t)1 << 62);
}
template <int ACC>
__device__ __forceinline__ void wgmma_rs32(float* d, const uint32_t* a, uint64_t db) {
  asm volatile("{.reg .pred p; setp.ne.b32 p, %21, 0;\n"
               "wgmma.mma_async.sync.aligned.m64n32k16.f32.bf16.bf16 {%0,%1,%2,%3,%4,%5,%6,%7,%8,%9,%10,%11,%12,%13,%14,%15}, {%16,%17,%18,%19}, %20, p, 1, 1, 0;}"
               : "+f"(d[0]), "+f"(d[1]), "+f"(d[2]), "+f"(d[3]), "+f"(d[4]), "+f"(d[5]), "+f"(d[6]), "+f"(d[7]), "+f"(d[8]), "+f"(d[9]),
                 "+f"(d[10]), "+f"(d[11]), "+f"(d[12]), "+f"(d[13]), "+f"(d[14]), "+f"(d[15])
               : "r"(a[0]), "r"(a[1]), "r"(a[2]), "r"(a[3]), "l"(db), "n"(ACC));
}

template <int N> __device__ __forceinline__ void fence_regs(float* d) {
#pragma unroll
  for (int i = 0; i < N; i++) asm volatile("" : "+f"(d[i])::"memory");
}
__device__ __forceinline__ void wg_wait1() { asm volatile("wgmma.wait_group.sync.aligned 1;" ::: "memory"); }
__device__ __forceinline__ void tma_store3(const CUtensorMap* tm, uint32_t src, int c0, int c1, int c2) {
  asm volatile("cp.async.bulk.tensor.3d.global.shared::cta.bulk_group [%0, {%2,%3,%4}], [%1];" ::"l"(tm), "r"(src), "r"(c0), "r"(c1), "r"(c2) : "memory");
}
__device__ __forceinline__ void tma_red3(const CUtensorMap* tm, uint32_t src, int c0, int c1, int c2) {
  asm volatile("cp.reduce.async.bulk.tensor.3d.global.shared::cta.add.bulk_group [%0, {%2,%3,%4}], [%1];" ::"l"(tm), "r"(src), "r"(c0), "r"(c1), "r"(c2) : "memory");
}
__device__ __forceinline__ void tma_red2(const CUtensorMap* tm, uint32_t src, int c0, int c1) {
  asm volatile("cp.reduce.async.bulk.tensor.2d.global.shared::cta.add.bulk_group [%0, {%2,%3}], [%1];" ::"l"(tm), "r"(src), "r"(c0), "r"(c1) : "memory");
}
__device__ __forceinline__ void stsm4(uint32_t a, uint32_t r0, uint32_t r1, uint32_t r2, uint32_t r3) {
  asm volatile("stmatrix.sync.aligned.m8n8.x4.shared.b16 [%0], {%1,%2,%3,%4};" ::"r"(a), "r"(r0), "r"(r1), "r"(r2), "r"(r3) : "memory");
}
__device__ __forceinline__ uint2 lds64(uint32_t a) { uint2 v; asm volatile("ld.shared.v2.b32 {%0,%1}, [%2];" : "=r"(v.x), "=r"(v.y) : "r"(a) : "memory"); return v; }
__device__ __forceinline__ uint32_t hmul2(uint32_t a, uint32_t b) { uint32_t r; asm("mul.rn.bf16x2 %0, %1, %2;" : "=r"(r) : "r"(a), "r"(b)); return r; }
__device__ __forceinline__ void wgmma_ss192t(float* d, uint64_t da, uint64_t db, int acc) {
  asm volatile("{.reg .pred p; setp.ne.b32 p, %98, 0;\n"
    "wgmma.mma_async.sync.aligned.m64n192k16.f32.bf16.bf16 "
    "{%0,%1,%2,%3,%4,%5,%6,%7,%8,%9,%10,%11,%12,%13,%14,%15,%16,%17,%18,%19,%20,%21,%22,%23,%24,%25,%26,%27,%28,%29,%30,%31,%32,%33,%34,%35,%36,%37,%38,%39,%40,%41,%42,%43,%44,%45,%46,%47,%48,%49,%50,%51,%52,%53,%54,%55,%56,%57,%58,%59,%60,%61,%62,%63,%64,%65,%66,%67,%68,%69,%70,%71,%72,%73,%74,%75,%76,%77,%78,%79,%80,%81,%82,%83,%84,%85,%86,%87,%88,%89,%90,%91,%92,%93,%94,%95}, %96, %97, p, 1, 1, 0, 1;}"
    : "+f"(d[0]), "+f"(d[1]), "+f"(d[2]), "+f"(d[3]), "+f"(d[4]), "+f"(d[5]), "+f"(d[6]), "+f"(d[7]), "+f"(d[8]), "+f"(d[9]), "+f"(d[10]), "+f"(d[11]),
      "+f"(d[12]), "+f"(d[13]), "+f"(d[14]), "+f"(d[15]), "+f"(d[16]), "+f"(d[17]), "+f"(d[18]), "+f"(d[19]), "+f"(d[20]), "+f"(d[21]), "+f"(d[22]),
      "+f"(d[23]), "+f"(d[24]), "+f"(d[25]), "+f"(d[26]), "+f"(d[27]), "+f"(d[28]), "+f"(d[29]), "+f"(d[30]), "+f"(d[31]), "+f"(d[32]), "+f"(d[33]),
      "+f"(d[34]), "+f"(d[35]), "+f"(d[36]), "+f"(d[37]), "+f"(d[38]), "+f"(d[39]), "+f"(d[40]), "+f"(d[41]), "+f"(d[42]), "+f"(d[43]), "+f"(d[44]),
      "+f"(d[45]), "+f"(d[46]), "+f"(d[47]), "+f"(d[48]), "+f"(d[49]), "+f"(d[50]), "+f"(d[51]), "+f"(d[52]), "+f"(d[53]), "+f"(d[54]), "+f"(d[55]),
      "+f"(d[56]), "+f"(d[57]), "+f"(d[58]), "+f"(d[59]), "+f"(d[60]), "+f"(d[61]), "+f"(d[62]), "+f"(d[63]), "+f"(d[64]), "+f"(d[65]), "+f"(d[66]),
      "+f"(d[67]), "+f"(d[68]), "+f"(d[69]), "+f"(d[70]), "+f"(d[71]), "+f"(d[72]), "+f"(d[73]), "+f"(d[74]), "+f"(d[75]), "+f"(d[76]), "+f"(d[77]),
      "+f"(d[78]), "+f"(d[79]), "+f"(d[80]), "+f"(d[81]), "+f"(d[82]), "+f"(d[83]), "+f"(d[84]), "+f"(d[85]), "+f"(d[86]), "+f"(d[87]), "+f"(d[88]),
      "+f"(d[89]), "+f"(d[90]), "+f"(d[91]), "+f"(d[92]), "+f"(d[93]), "+f"(d[94]), "+f"(d[95])
    : "l"(da), "l"(db), "r"(acc));
}
__device__ __forceinline__ void wgmma_rs128t(float* d, const uint32_t* a, uint64_t db, int acc) {
  asm volatile("{.reg .pred p; setp.ne.b32 p, %69, 0;\n"
    "wgmma.mma_async.sync.aligned.m64n128k16.f32.bf16.bf16 "
    "{%0,%1,%2,%3,%4,%5,%6,%7,%8,%9,%10,%11,%12,%13,%14,%15,%16,%17,%18,%19,%20,%21,%22,%23,%24,%25,%26,%27,%28,%29,%30,%31,%32,%33,%34,%35,%36,%37,%38,%39,%40,%41,%42,%43,%44,%45,%46,%47,%48,%49,%50,%51,%52,%53,%54,%55,%56,%57,%58,%59,%60,%61,%62,%63}, {%64,%65,%66,%67}, %68, p, 1, 1, 1;}"
    : "+f"(d[0]), "+f"(d[1]), "+f"(d[2]), "+f"(d[3]), "+f"(d[4]), "+f"(d[5]), "+f"(d[6]), "+f"(d[7]), "+f"(d[8]), "+f"(d[9]), "+f"(d[10]), "+f"(d[11]),
      "+f"(d[12]), "+f"(d[13]), "+f"(d[14]), "+f"(d[15]), "+f"(d[16]), "+f"(d[17]), "+f"(d[18]), "+f"(d[19]), "+f"(d[20]), "+f"(d[21]), "+f"(d[22]),
      "+f"(d[23]), "+f"(d[24]), "+f"(d[25]), "+f"(d[26]), "+f"(d[27]), "+f"(d[28]), "+f"(d[29]), "+f"(d[30]), "+f"(d[31]), "+f"(d[32]), "+f"(d[33]),
      "+f"(d[34]), "+f"(d[35]), "+f"(d[36]), "+f"(d[37]), "+f"(d[38]), "+f"(d[39]), "+f"(d[40]), "+f"(d[41]), "+f"(d[42]), "+f"(d[43]), "+f"(d[44]),
      "+f"(d[45]), "+f"(d[46]), "+f"(d[47]), "+f"(d[48]), "+f"(d[49]), "+f"(d[50]), "+f"(d[51]), "+f"(d[52]), "+f"(d[53]), "+f"(d[54]), "+f"(d[55]),
      "+f"(d[56]), "+f"(d[57]), "+f"(d[58]), "+f"(d[59]), "+f"(d[60]), "+f"(d[61]), "+f"(d[62]), "+f"(d[63])
    : "r"(a[0]), "r"(a[1]), "r"(a[2]), "r"(a[3]), "l"(db), "r"(acc));
}
__device__ __forceinline__ void wgmma_rs80(float* d, const uint32_t* a, uint64_t db, int acc) {
  asm volatile("{.reg .pred p; setp.ne.b32 p, %45, 0;\n"
    "wgmma.mma_async.sync.aligned.m64n80k16.f32.bf16.bf16 "
    "{%0,%1,%2,%3,%4,%5,%6,%7,%8,%9,%10,%11,%12,%13,%14,%15,%16,%17,%18,%19,%20,%21,%22,%23,%24,%25,%26,%27,%28,%29,%30,%31,%32,%33,%34,%35,%36,%37,%38,%39}, {%40,%41,%42,%43}, %44, p, 1, 1, 0;}"
    : "+f"(d[0]), "+f"(d[1]), "+f"(d[2]), "+f"(d[3]), "+f"(d[4]), "+f"(d[5]), "+f"(d[6]), "+f"(d[7]), "+f"(d[8]), "+f"(d[9]), "+f"(d[10]), "+f"(d[11]),
      "+f"(d[12]), "+f"(d[13]), "+f"(d[14]), "+f"(d[15]), "+f"(d[16]), "+f"(d[17]), "+f"(d[18]), "+f"(d[19]), "+f"(d[20]), "+f"(d[21]), "+f"(d[22]),
      "+f"(d[23]), "+f"(d[24]), "+f"(d[25]), "+f"(d[26]), "+f"(d[27]), "+f"(d[28]), "+f"(d[29]), "+f"(d[30]), "+f"(d[31]), "+f"(d[32]), "+f"(d[33]),
      "+f"(d[34]), "+f"(d[35]), "+f"(d[36]), "+f"(d[37]), "+f"(d[38]), "+f"(d[39])
    : "r"(a[0]), "r"(a[1]), "r"(a[2]), "r"(a[3]), "l"(db), "r"(acc));
}
__device__ __forceinline__ void wgmma_rs64t(float* d, const uint32_t* a, uint64_t db, int acc) {
  asm volatile("{.reg .pred p; setp.ne.b32 p, %37, 0;\n"
    "wgmma.mma_async.sync.aligned.m64n64k16.f32.bf16.bf16 "
    "{%0,%1,%2,%3,%4,%5,%6,%7,%8,%9,%10,%11,%12,%13,%14,%15,%16,%17,%18,%19,%20,%21,%22,%23,%24,%25,%26,%27,%28,%29,%30,%31}, {%32,%33,%34,%35}, %36, p, 1, 1, 1;}"
    : "+f"(d[0]), "+f"(d[1]), "+f"(d[2]), "+f"(d[3]), "+f"(d[4]), "+f"(d[5]), "+f"(d[6]), "+f"(d[7]), "+f"(d[8]), "+f"(d[9]), "+f"(d[10]), "+f"(d[11]),
      "+f"(d[12]), "+f"(d[13]), "+f"(d[14]), "+f"(d[15]), "+f"(d[16]), "+f"(d[17]), "+f"(d[18]), "+f"(d[19]), "+f"(d[20]), "+f"(d[21]), "+f"(d[22]),
      "+f"(d[23]), "+f"(d[24]), "+f"(d[25]), "+f"(d[26]), "+f"(d[27]), "+f"(d[28]), "+f"(d[29]), "+f"(d[30]), "+f"(d[31])
    : "r"(a[0]), "r"(a[1]), "r"(a[2]), "r"(a[3]), "l"(db), "r"(acc));
}
__device__ __forceinline__ void wgmma_rs224t(float* d, const uint32_t* a, uint64_t db, int acc) {
  asm volatile("{.reg .pred p; setp.ne.b32 p, %117, 0;\n"
    "wgmma.mma_async.sync.aligned.m64n224k16.f32.bf16.bf16 "
    "{%0,%1,%2,%3,%4,%5,%6,%7,%8,%9,%10,%11,%12,%13,%14,%15,%16,%17,%18,%19,%20,%21,%22,%23,%24,%25,%26,%27,%28,%29,%30,%31,%32,%33,%34,%35,%36,%37,%38,%39,%40,%41,%42,%43,%44,%45,%46,%47,%48,%49,%50,%51,%52,%53,%54,%55,%56,%57,%58,%59,%60,%61,%62,%63,%64,%65,%66,%67,%68,%69,%70,%71,%72,%73,%74,%75,%76,%77,%78,%79,%80,%81,%82,%83,%84,%85,%86,%87,%88,%89,%90,%91,%92,%93,%94,%95,%96,%97,%98,%99,%100,%101,%102,%103,%104,%105,%106,%107,%108,%109,%110,%111}, {%112,%113,%114,%115}, %116, p, 1, 1, 1;}"
    : "+f"(d[0]), "+f"(d[1]), "+f"(d[2]), "+f"(d[3]), "+f"(d[4]), "+f"(d[5]), "+f"(d[6]), "+f"(d[7]), "+f"(d[8]), "+f"(d[9]), "+f"(d[10]), "+f"(d[11]),
      "+f"(d[12]), "+f"(d[13]), "+f"(d[14]), "+f"(d[15]), "+f"(d[16]), "+f"(d[17]), "+f"(d[18]), "+f"(d[19]), "+f"(d[20]), "+f"(d[21]), "+f"(d[22]),
      "+f"(d[23]), "+f"(d[24]), "+f"(d[25]), "+f"(d[26]), "+f"(d[27]), "+f"(d[28]), "+f"(d[29]), "+f"(d[30]), "+f"(d[31]), "+f"(d[32]), "+f"(d[33]),
      "+f"(d[34]), "+f"(d[35]), "+f"(d[36]), "+f"(d[37]), "+f"(d[38]), "+f"(d[39]), "+f"(d[40]), "+f"(d[41]), "+f"(d[42]), "+f"(d[43]), "+f"(d[44]),
      "+f"(d[45]), "+f"(d[46]), "+f"(d[47]), "+f"(d[48]), "+f"(d[49]), "+f"(d[50]), "+f"(d[51]), "+f"(d[52]), "+f"(d[53]), "+f"(d[54]), "+f"(d[55]),
      "+f"(d[56]), "+f"(d[57]), "+f"(d[58]), "+f"(d[59]), "+f"(d[60]), "+f"(d[61]), "+f"(d[62]), "+f"(d[63]), "+f"(d[64]), "+f"(d[65]), "+f"(d[66]),
      "+f"(d[67]), "+f"(d[68]), "+f"(d[69]), "+f"(d[70]), "+f"(d[71]), "+f"(d[72]), "+f"(d[73]), "+f"(d[74]), "+f"(d[75]), "+f"(d[76]), "+f"(d[77]),
      "+f"(d[78]), "+f"(d[79]), "+f"(d[80]), "+f"(d[81]), "+f"(d[82]), "+f"(d[83]), "+f"(d[84]), "+f"(d[85]), "+f"(d[86]), "+f"(d[87]), "+f"(d[88]),
      "+f"(d[89]), "+f"(d[90]), "+f"(d[91]), "+f"(d[92]), "+f"(d[93]), "+f"(d[94]), "+f"(d[95]), "+f"(d[96]), "+f"(d[97]), "+f"(d[98]), "+f"(d[99]),
      "+f"(d[100]), "+f"(d[101]), "+f"(d[102]), "+f"(d[103]), "+f"(d[104]), "+f"(d[105]), "+f"(d[106]), "+f"(d[107]), "+f"(d[108]), "+f"(d[109]),
      "+f"(d[110]), "+f"(d[111])
    : "r"(a[0]), "r"(a[1]), "r"(a[2]), "r"(a[3]), "l"(db), "r"(acc));
}
__device__ __forceinline__ void wgmma_rs192t(float* d, const uint32_t* a, uint64_t db, int acc) {
  asm volatile("{.reg .pred p; setp.ne.b32 p, %101, 0;\n"
    "wgmma.mma_async.sync.aligned.m64n192k16.f32.bf16.bf16 "
    "{%0,%1,%2,%3,%4,%5,%6,%7,%8,%9,%10,%11,%12,%13,%14,%15,%16,%17,%18,%19,%20,%21,%22,%23,%24,%25,%26,%27,%28,%29,%30,%31,%32,%33,%34,%35,%36,%37,%38,%39,%40,%41,%42,%43,%44,%45,%46,%47,%48,%49,%50,%51,%52,%53,%54,%55,%56,%57,%58,%59,%60,%61,%62,%63,%64,%65,%66,%67,%68,%69,%70,%71,%72,%73,%74,%75,%76,%77,%78,%79,%80,%81,%82,%83,%84,%85,%86,%87,%88,%89,%90,%91,%92,%93,%94,%95}, {%96,%97,%98,%99}, %100, p, 1, 1, 1;}"
    : "+f"(d[0]), "+f"(d[1]), "+f"(d[2]), "+f"(d[3]), "+f"(d[4]), "+f"(d[5]), "+f"(d[6]), "+f"(d[7]), "+f"(d[8]), "+f"(d[9]), "+f"(d[10]), "+f"(d[11]),
      "+f"(d[12]), "+f"(d[13]), "+f"(d[14]), "+f"(d[15]), "+f"(d[16]), "+f"(d[17]), "+f"(d[18]), "+f"(d[19]), "+f"(d[20]), "+f"(d[21]), "+f"(d[22]),
      "+f"(d[23]), "+f"(d[24]), "+f"(d[25]), "+f"(d[26]), "+f"(d[27]), "+f"(d[28]), "+f"(d[29]), "+f"(d[30]), "+f"(d[31]), "+f"(d[32]), "+f"(d[33]),
      "+f"(d[34]), "+f"(d[35]), "+f"(d[36]), "+f"(d[37]), "+f"(d[38]), "+f"(d[39]), "+f"(d[40]), "+f"(d[41]), "+f"(d[42]), "+f"(d[43]), "+f"(d[44]),
      "+f"(d[45]), "+f"(d[46]), "+f"(d[47]), "+f"(d[48]), "+f"(d[49]), "+f"(d[50]), "+f"(d[51]), "+f"(d[52]), "+f"(d[53]), "+f"(d[54]), "+f"(d[55]),
      "+f"(d[56]), "+f"(d[57]), "+f"(d[58]), "+f"(d[59]), "+f"(d[60]), "+f"(d[61]), "+f"(d[62]), "+f"(d[63]), "+f"(d[64]), "+f"(d[65]), "+f"(d[66]),
      "+f"(d[67]), "+f"(d[68]), "+f"(d[69]), "+f"(d[70]), "+f"(d[71]), "+f"(d[72]), "+f"(d[73]), "+f"(d[74]), "+f"(d[75]), "+f"(d[76]), "+f"(d[77]),
      "+f"(d[78]), "+f"(d[79]), "+f"(d[80]), "+f"(d[81]), "+f"(d[82]), "+f"(d[83]), "+f"(d[84]), "+f"(d[85]), "+f"(d[86]), "+f"(d[87]), "+f"(d[88]),
      "+f"(d[89]), "+f"(d[90]), "+f"(d[91]), "+f"(d[92]), "+f"(d[93]), "+f"(d[94]), "+f"(d[95])
    : "r"(a[0]), "r"(a[1]), "r"(a[2]), "r"(a[3]), "l"(db), "r"(acc));
}

struct Desc {
  uint32_t lo, hi;
  __device__ __forceinline__ Desc operator+(uint32_t o) const { return {lo + o, hi}; }
  __device__ __forceinline__ operator uint64_t() const { return ((uint64_t)hi << 32) | lo; }
};
__device__ __forceinline__ Desc mk_desc(uint32_t addr, uint32_t lbo, uint32_t sbo, uint32_t mode) {
  return {(addr >> 4) | ((lbo >> 4) << 16), (sbo >> 4) | (mode << 30)};
}

struct AttMask {
  uint32_t hi, z;
  float c0, c1, mb[10];
  __device__ __forceinline__ AttMask(uint32_t tid, uint32_t sb) {
    constexpr float SCL = 0.07216878364870322f * 1.4426950408889634f;
    hi = pin(tid & 64); z = sb >> 31;
    c0 = hi ? 0.f : SCL; c1 = hi ? SCL : 0.f;
    const int tt = (int)pin(((tid >> 1) & 16) + ((tid >> 2) & 7) - 2 * (tid & 3));
#pragma unroll
    for (int i = 0; i < 10; i++) mb[i] = 8 * ((i >> 1) - 1) + (i & 1) > tt ? -INFINITY : 0.f;
  }
};
__device__ __forceinline__ void att_softmax(const AttMask& m, const float* s_, uint32_t (&p)[5][4], float g0, float g1) {
  const uint32_t hi = m.hi;
  const float c0 = m.c0, c1 = m.c1;
  const float* mb = m.mb;
  float v[20], mx[2], sum[2];
#pragma unroll
  for (int i = 0; i < 20; i++)
    if (i != 16 && i != 17) v[i] = fmaf(s_[20 + i], c1, i < 4 ? s_[i] * c0 : fmaf(s_[i], c0, mb[2 * ((i >> 2) - ((i >> 1) & 1)) + (i & 1)]));
  mx[0] = fmaxf(fmaxf(fmaxf(v[0], v[1]), fmaxf(v[4], v[5])), fmaxf(fmaxf(v[8], v[9]), fmaxf(v[12], v[13])));
  mx[1] = fmaxf(fmaxf(fmaxf(v[2], v[3]), fmaxf(v[6], v[7])), fmaxf(fmaxf(v[10], v[11]), fmaxf(v[14], v[15])));
  mx[1] = fmaxf(mx[1], fmaxf(v[18], v[19]));
  {
    const float ni = __uint_as_float(0xff800000u | m.z), a_ = fminf(mx[0], ni), b_ = fminf(mx[1], ni);
    mx[0] = fmaxf(mx[0], b_); mx[1] = fmaxf(mx[1], a_);
  }
#pragma unroll
  for (int o = 1; o < 4; o <<= 1)
#pragma unroll
    for (int h = 0; h < 2; h++) mx[h] = fmaxf(mx[h], __shfl_xor_sync(~0u, mx[h], o));
#pragma unroll
  for (int i = 0; i < 20; i++) v[i] = i == 16 || i == 17 ? 0.f : ex2(v[i] - mx[(i >> 1) & 1]);
  sum[0] = ((v[0] + v[1]) + (v[4] + v[5])) + ((v[8] + v[9]) + (v[12] + v[13]));
  sum[1] = ((v[2] + v[3]) + (v[6] + v[7])) + ((v[10] + v[11]) + (v[14] + v[15])) + (v[18] + v[19]);
  {
    const float z = __uint_as_float(m.z), a_ = sum[0];
    sum[0] = fmaf(sum[1], z, a_); sum[1] = fmaf(a_, z, sum[1]);
  }
  sum[0] += __shfl_xor_sync(~0u, sum[0], 1);
  sum[1] += __shfl_xor_sync(~0u, sum[1], 1);
  {
    const float z = __uint_as_float(m.z), a_ = sum[0];
    sum[0] = fmaf(sum[1], z, a_); sum[1] = fmaf(a_, z, sum[1]);
  }
  sum[0] += __shfl_xor_sync(~0u, sum[0], 2);
  sum[1] += __shfl_xor_sync(~0u, sum[1], 2);
  const float r0 = g0 * rcp(sum[0]), r1 = g1 * rcp(sum[1]);
#pragma unroll
  for (int j = 0; j < 5; j++)
#pragma unroll
    for (int h = 0; h < 2; h++) {
      const uint32_t pt = j == 4 && h == 0 ? 0u : pack2(v[4 * j + 2 * h] * (h ? r1 : r0), v[4 * j + 2 * h + 1] * (h ? r1 : r0));
      p[j >> 1][(j & 1) * 2 + h] = hi ? 0u : pt;
      p[(j + 5) >> 1][((j + 5) & 1) * 2 + h] = hi ? pt : 0u;
    }
#pragma unroll
  for (int i = 0; i < 20; i++) asm volatile("" : "+r"(p[i >> 2][i & 3]));
}

constexpr int NPQ = 2;
#define NQ 12
#define NQ_WIN 8
#define NO_EARLY 6
#define NO_MID 9
#define NW1 16
#define NW1A 10
#define VLD 6
#define VB 0
#define XPF 3
#define WSPLIT 8
#define PEARLY 0
#define NQ_W1 8
#define B5LATE 0
#define WD 750
#define DFENCE 0
#define PDS 300
#define PDT 50
#define LDEP 0
#define LDT 6000
#define CT 0
#define ZF 1
#define GS 1
#define PFD 1
#define PFK 0
#define TLD 0
#define PFN 2
#define PFB 8000
#define VBULK 1
#define VBW 3
#define PD 780
constexpr int R_WQ = 0;
constexpr int R_WO = R_WQ + 8 * (20 - NPQ) * 512;
constexpr int R_XT = R_WO + 14 * 12 * 512;
constexpr int R_MEM = R_XT;
constexpr int R_QB = R_XT + 40960;
constexpr int R_QA = R_QB + 1024;
constexpr int R_O2 = R_QA + 1024;
constexpr int R_VS = R_O2 + 1024;
constexpr int R_KT = R_VS + 1024;
constexpr int R_VT = R_KT + 5120;
constexpr int R_V1 = R_VT + 5120;
constexpr int R_SX = R_V1 + 8192;
constexpr int R_VM = R_SX + 4608;
constexpr int R_BAR = R_VM + 2048;
constexpr int R_MI = R_BAR + 64;
constexpr int R_EB = R_MI + 64;
constexpr int R_SMEM = R_EB + 64 + 96;
constexpr int E_KA = 0, E_VA = 30720, E_KB = R_XT + 10240, E_VB0 = 61440, E_VB1 = R_V1, E_VB2 = R_XT;
static_assert(R_V1 + 10240 <= R_BAR && E_VB0 + 10240 <= R_WO, "chunks");
static_assert(NPQ == 2 && R_XT % 1024 == 0 && R_KT % 1024 == 0 && R_VT % 1024 == 0 && R_V1 % 1024 == 0 && R_WO % 1024 == 0, "align");
constexpr int R_SMEM_ALLOC = R_SMEM;
static_assert(R_SMEM_ALLOC <= 232448, "smem");

#define TR(i) do {} while (0)

__device__ __forceinline__ void red_pair(unsigned char* p, float lo, float hi) {
  const int b = __float2int_rn(lo), a = __float2int_rn(hi);
  asm volatile("{.reg .b64 t; mov.b64 t, {%1,%2}; red.relaxed.gpu.global.add.u64 [%0], t;}" ::"l"(p), "r"(b + ((1 << 29) + (1 << 23))), "r"(a * 8) : "memory");
}
__device__ __forceinline__ unsigned long long swap0(unsigned char* p) {
  unsigned long long r;
  asm volatile("atom.relaxed.gpu.global.exch.b64 %0, [%1], 0;" : "=l"(r) : "l"(p) : "memory");
  return r;
}
__device__ __forceinline__ uint32_t dec_pair(uint32_t lo, uint32_t hi, uint32_t bias) { return pack2((float)(int)(lo * 8u + bias), (float)(int)hi); }

__global__ void __cluster_dims__(3, 1, 1) __launch_bounds__(256, 1)
rec_kernel(const __grid_constant__ CUtensorMap tmX, const __grid_constant__ CUtensorMap tmK, const __grid_constant__ CUtensorMap tmV,
           const __grid_constant__ CUtensorMap tmWq, const __grid_constant__ CUtensorMap tmWq2, const __grid_constant__ CUtensorMap tmWk,
           const __grid_constant__ CUtensorMap tmWv, const __grid_constant__ CUtensorMap tmWo, const __grid_constant__ CUtensorMap tmOut,
           const bf16* __restrict__ mem0,
           const bf16* __restrict__ Wq, const bf16* __restrict__ Wk, const bf16* __restrict__ Wv, const bf16* __restrict__ Wo, const bf16* __restrict__ x, const bf16* __restrict__ gate_w,
           bf16* __restrict__ out, unsigned char* __restrict__ red) {
  extern __shared__ __align__(1024) unsigned char smem[];
  const uint32_t sb = smem_u32(smem);
  const int tid = threadIdx.x, lane = tid & 31, wid = __shfl_sync(~0u, tid >> 5, 0), g = wid >> 2, w = wid & 3;
  const int cta = blockIdx.x, head = cta / 3, rank = cta % 3;
  const int D0 = head * DH + rank * 64;
  const int tile0 = rank == 0 ? 0 : (rank == 1 ? 14 : 26);
  const uint32_t XBAR = sb + R_BAR, SBAR = XBAR + 8, OBAR = XBAR + 16, VBAR = XBAR + 24, FBAR = XBAR + 32, WBAR = XBAR + 40;
  constexpr uint32_t ONES = 0x3F803F80u;
  if (LDEP == 0) asm volatile("griddepcontrol.launch_dependents;" ::: "memory");
  GTR(0);
  if (PFK == 1) {
#pragma unroll
    for (int i = 0; i < 5; i++) { const int l = tid + i * 256; prefetch_l2((l < 640 ? Wk : Wv - 40960) + (size_t)cta * 40960 + l * 64); }
  }
  if (PFK >= 2 && wid == 7 && lane < (PFK == 2 ? 10 : 20)) {
    const bf16* b = lane < 5 ? Wk : (lane < 10 ? Wv : (lane < 15 ? Wq : Wo));
    asm volatile("cp.async.bulk.prefetch.L2.global [%0], 16384;" ::"l"(b + (size_t)cta * 40960 + (lane % 5) * 8192) : "memory");
  }
  if (wid == 0) {
    if (lane == 0) {
      mbar_init(XBAR, 1); mbar_init(SBAR, 4); mbar_init(OBAR, 5); mbar_init(VBAR, 1); mbar_init(FBAR, 2);
      mbar_init(WBAR, 1); mbar_init(WBAR + 8, 1); mbar_init(WBAR + 16, 1);
      for (int i = 0; i < 6; i++) mbar_init(sb + R_EB + i * 8, i < 4 ? 1 : 2);
      asm volatile("fence.mbarrier_init.release.cluster;" ::: "memory");
      mbar_expect(WBAR, 81920); mbar_expect(WBAR + 8, 81920 + 2 * NPQ * 2048); mbar_expect(XBAR, 40960);
      mbar_expect(SBAR, 3072); mbar_expect(OBAR, 2048); mbar_expect(VBAR, 8192);
      for (int i = 0; i < 4; i++) mbar_expect(sb + R_EB + i * 8, 30720);
      sts128(sb + R_MI + 48, 0, 0, 0, 0);
      sts32(sb + R_MI, *(volatile uint32_t*)&g_epoch + 1);
    }
    __syncwarp();
    if (TLD) spin_until(clk32(), TLD);
    if (lane < 5) tma_load2(sb + lane * 16384, &tmWk, D0, lane * 128, WBAR);
    if (lane == 5) tma_load3(sb + R_XT, &tmX, 0, 0, 0, XBAR);
    if (lane < 5) tma_load2(lane < 4 ? sb + 81920 + lane * 16384 : sb + R_QB, &tmWv, D0, lane * 128, WBAR + 8);
    if (lane < 2) tma_load2(sb + R_QB + 16384 + lane * 4096, &tmWq2, D0, lane * 320, WBAR + 8);
  }
  if (tid == 32) { prefetch_map(&tmWq); prefetch_map(&tmWo); prefetch_map(&tmK); prefetch_map(&tmV); prefetch_map(&tmOut); }
  if (tid >= 64 && tid < 144) prefetch_l2(mem0 + (tid - 64) * 64);
  __syncthreads();
  GTR(1);
  if (LDEP == 1) asm volatile("griddepcontrol.launch_dependents;" ::: "memory");
  if (LDEP == 4 && wid == 7) { spin_until(clk32(), LDT); asm volatile("griddepcontrol.launch_dependents;" ::: "memory"); }
  const uint32_t c0 = clk32();
  auto pfw = [&]() {
#pragma unroll
    for (int i = 0; i < 5; i++) { const int l = tid + i * 256; prefetch_l2((l < 640 ? Wq : Wo - 40960) + (size_t)cta * 40960 + l * 64); }
  };
  if (PFD == 0) pfw();
  uint32_t ww[40][4], wqp[NPQ][4];
  {
    uint32_t xm = 0;
    {
      const int row = cta * 8 + wid;
      uint4 gw[3], v[3][3];
#pragma unroll
      for (int r = 0; r < 3; r++)
#pragma unroll
        for (int i = 0; i < 3; i++)
          v[r][i] = (i < 2 || lane < 16) && (r < 2 || row < 512) ? __ldg((const uint4*)(x + (size_t)(row + r * 768) * DM) + lane + 32 * i) : make_uint4(0, 0, 0, 0);
#pragma unroll
      for (int i = 0; i < 3; i++) gw[i] = (i < 2 || lane < 16) ? __ldg((const uint4*)gate_w + lane + 32 * i) : make_uint4(0, 0, 0, 0);
      if (PFD > 1) { spin_until(c0, PFD); pfw(); }
      if (PFN && wid == 7) {
        spin_until(c0, PFB);
        if (lane < 4 && lane < PFN)
          asm volatile("cp.async.bulk.prefetch.tensor.2d.L2.global [%0, {%1,%2}];" ::"l"(&tmWq), "r"(D0), "r"((lane >> 1) * 320 + 32 + (lane & 1) * 144) : "memory");
        else if (lane < PFN)
          asm volatile("cp.async.bulk.prefetch.tensor.3d.L2.global [%0, {%1,%2,%3}];" ::"l"(&tmWo), "r"(0), "r"(head * DH + (lane - 4) * 64), "r"(tile0 >> 1) : "memory");
      }
      if (cta < 80 && tid < 128) ((uint4*)(out + (S_TOK - 128) * DM))[cta * 128 + tid] = make_uint4(0, 0, 0, 0);
      float z = 0.f;
#pragma unroll
      for (int r = 0; r < 3; r++) {
        float s_ = 0.f;
#pragma unroll
        for (int i = 0; i < 3; i++) {
          const uint4 q = v[r][i];
          xm = hmaxabs2(hmaxabs2(xm, hmaxabs2(q.x, q.y)), hmaxabs2(q.z, q.w));
          const uint32_t p0 = hmul2(q.x, gw[i].x), p1 = hmul2(q.y, gw[i].y), p2 = hmul2(q.z, gw[i].z), p3 = hmul2(q.w, gw[i].w);
          s_ += ((bf_lo(p0) + bf_hi(p0)) + (bf_lo(p1) + bf_hi(p1))) + ((bf_lo(p2) + bf_hi(p2)) + (bf_lo(p3) + bf_hi(p3)));
        }
#pragma unroll
        for (int o = 16; o; o >>= 1) s_ += __shfl_xor_sync(~0u, s_, o);
        if (lane == r) z = s_;
      }
      z = bf_lo(pack2(z, 0.f));
      const float gv = bf_lo(pack2(1.f / (1.f + __expf(-z)), 0.f));
      if (!GS) { if (lane < (row < 512 ? 3 : 2)) { g_gate[row + lane * 768] = gv; g_gate[S_TOK + row + lane * 768] = bf_lo(pack2(1.f - gv, 0.f)); } }
      else if (lane < 3) sts32(sb + R_EB + 64 + lane * 32 + wid * 4, __float_as_uint(gv));
      if (ZF) asm volatile("fence.proxy.async.global;" ::: "memory");
    }
    xm = __reduce_max_sync(~0u, max((xm << 16) & 0x7fffffffu, xm & 0x7fff0000u));
    const uint32_t p = sb + (lane >> 4) * 1024 + (lane & 7) * 128 + (((2 * w + ((lane >> 3) & 1)) ^ (lane & 7)) << 4);
    if (LDEP == 2) asm volatile("griddepcontrol.launch_dependents;" ::: "memory");
    mbar_wait(WBAR + 8 * g, 0);
    GTR(2);
#pragma unroll
    for (int f = 0; f < 40; f++) ldsm4t(ww[f], (f >= 32 && g == 1) ? p + R_QB + (f - 32) * 2048 : p + g * 81920 + f * 2048);
    mbar_wait(WBAR + 8, 0);
    GTR(3);
#pragma unroll
    for (int f = 0; f < NPQ; f++) ldsm4t(wqp[f], p + R_QB + 16384 + g * 4096 + f * 2048);
    __syncthreads();
    GTR(5);
    asm volatile("barrier.cluster.arrive.relaxed.aligned;" ::: "memory");
    if (GS && wid == 3 && lane < (cta < 64 ? 24 : 16)) {
      const float gv = __uint_as_float(lds32(sb + R_EB + 64 + lane * 4));
      float* gp = g_gate + cta * 8 + (lane >> 3) * 768 + (lane & 7);
      gp[0] = gv; gp[S_TOK] = bf_lo(pack2(1.f - gv, 0.f));
    }
    if (wid == 0) {
      if (lane == 0) mbar_expect(WBAR + 16, 18 * 4096 + 21 * 4096);
      __syncwarp();
      if (lane < 4) tma_load2(sb + R_WQ + lane * 18432, &tmWq, D0, (lane >> 1) * 320 + 32 + (lane & 1) * 144, WBAR + 16);
      else if (lane < 7) tma_load3(sb + R_WO + ((lane - 1 - rank) % 3) * 28672, &tmWo, 0, head * DH + (lane - 4) * 64, tile0 >> 1, WBAR + 16);
      __syncwarp();
    }
    GTR(6);
    float nv[4] = {0.f, 0.f, 0.f, 0.f};
#pragma unroll
    for (int f = 0; f < 40; f++) {
      const uint32_t a[4] = {ww[f][0] & 0x7fff7fffu, ww[f][1] & 0x7fff7fffu, ww[f][2] & 0x7fff7fffu, ww[f][3] & 0x7fff7fffu};
      mma16816(nv, a, ONES, ONES);
    }
    const uint32_t mv = __reduce_max_sync(~0u, __float_as_uint(fmaxf(nv[0], nv[2])));
    if (lane == 0) { if (g == 1) smax32(sb + R_MI + 48, mv); smax32(sb + R_MI + 52, xm); }
  }
  GTR(4);
  if (LDEP == 3) asm volatile("griddepcontrol.launch_dependents;" ::: "memory");

  const uint32_t rF_ = opaque(sb + lane * 16);
  const uint32_t rP_ = opaque(sb + (lane >> 4) * 1024 + (lane & 7) * 128 + (((2 * w + ((lane >> 3) & 1)) ^ (lane & 7)) << 4));
  const int tA = g == 1 ? 2 * w : (rank != 1 ? (w < 2 ? 8 + 2 * w : 10 + w) : 8 + w);
  const bool two = g == 1 || (w < 2 && rank != 1);
  const uint32_t r1 = rank == 2 ? 0 : rank + 1, r2 = rank == 0 ? 2 : rank - 1;
  const uint32_t rW_ = opaque(sb + R_WO + (tA >> 1) * 4096 + ((lane >> 4) * 8 + (lane & 7)) * 64 +
                             (((2 * (tA & 1) + ((lane >> 3) & 1)) ^ ((lane >> 1) & 3)) << 4));
  const uint32_t toff = rb_q((tile0 + tA) >> 2) + rb_j(4 * (tile0 + tA)), zoff = rb_q((cta % 20) >> 1) + rb_j((cta % 20) * 8);
  uint32_t wqt[NQ][4];
  float u = 1.f;
  uint32_t t0 = 0;
  int s = -1;

#define WOFF(ks) (((ks) >> 2) * 28672 + ((ks) & 3) * 1024)
#define XDESC(j) (((uint64_t)0x40000040 << 32) | (dlo + ((((j) >> 2) * 4096 + ((j) & 3) * 32) >> 4)))

  auto vsend = [&]() {
    if (elect()) {
      if (VBULK != 1) fence_async_smem();
      bulk_s2s(mapa(sb + R_V1 + 4096, r1), sb + R_VT + 1024, 4096, mapa(VBAR, r1));
      bulk_s2s(mapa(sb + R_V1, r2), sb + R_VT + 1024, 4096, mapa(VBAR, r2));
    }
    __syncwarp();
  };
  auto window = [&](auto G_, auto FIRST_) {
    constexpr int G = decltype(G_)::value;
    constexpr bool FIRST = decltype(FIRST_)::value;
    const uint32_t rF = pin(rF_), rP = pin(rP_);
    float d[16];
    const uint32_t dlo = pin(((sb + R_XT) >> 4) | 0x10000);
    const uint32_t wqS = rP + R_WQ + G * (20 - NPQ) * 2048;
    uint4 y[5];
    unsigned long long zr = 0;
    const uint32_t t = w * 32 + ((rF - sb) >> 4);
    if (G == 0) zr = swap0(red + (rb_b(s + 2) + zoff + rb_j(t >> 4) + (t & 15) * 8));
    if (G == 0) {
      if (!FIRST && w == 3) {
        if (elect()) {
          mbar_expect(SBAR, 3072); mbar_expect(OBAR, 2048); mbar_expect(VBAR, 8192);
          asm volatile("mbarrier.arrive.relaxed.cluster.shared::cluster.b64 _, [%0];" ::"r"(mapa(FBAR, r1)) : "memory");
          asm volatile("mbarrier.arrive.relaxed.cluster.shared::cluster.b64 _, [%0];" ::"r"(mapa(FBAR, r2)) : "memory");
        }
        __syncwarp();
      }
    }
    const unsigned char* yp = red + (rb_b(s) + rb_j(t >> 3) + (t & 7) * 16);
    auto poll = [&]() {
      TR(10);
      spin_until(t0, PD);
#pragma unroll
      for (int q = 0; q < 5; q++) y[q] = ldg_rlx128(yp + rb_q(G * 5 + q));
      TR(9);
      sched_fence(sb);
    };
    constexpr int WS = FIRST || G == 1 ? 40 : WSPLIT;
    if (!FIRST && G == 0) {
#pragma unroll
      for (int f = 0; f < NQ_WIN; f++) ldsm4t(wqt[f], wqS + f * 2048);
      asm volatile("" : "+l"(yp));
      mbar_wait(XBAR, (s + 1) & 1);
      if (WS) spin_until(t0, WD);
    } else {
      mbar_wait(XBAR, (s + 1) & 1);
    }
    TR(11);
    if (WS == 0) { poll(); spin_until(t0, WD); }
    wg_fence();
    wgmma_rs32<0>(d, ww[0], XDESC(0));
#pragma unroll
    for (int j = 1; j < WS; j++) wgmma_rs32<1>(d, ww[j], XDESC(j));
    if (FIRST) {
      const unsigned short* m = (const unsigned short*)mem0 + (t & 1) * 4 * DM + G * 320 + (t >> 1);
#pragma unroll
      for (int q = 0; q < 5; q++) y[q] = make_uint4(m[q * 64], m[q * 64 + DM], m[q * 64 + 2 * DM], m[q * 64 + 3 * DM]);
    } else if (G == 0 && WS) {
      poll();
    }
#pragma unroll
    for (int j = WS ? WS : 1; j < 40; j++) wgmma_rs32<1>(d, ww[j], XDESC(j));
    wg_commit();
    if (!FIRST && G == 1) {
      asm volatile("" : "+l"(yp));
      if (PEARLY && (VBULK != 4 || w != VBW)) poll();
      mbar_wait(FBAR, s & 1);
#pragma unroll
      for (int f = 0; f < NQ_W1; f++) ldsm4t(wqt[f], wqS + f * 2048);
    }
    if (FIRST) asm volatile("barrier.cluster.wait.acquire.aligned;" ::: "memory");
    wg_wait0();
    fence_regs<16>(d);
    TR(13);
    bar_arrive(8 + G, 256);
    if (!FIRST && G == 1 && !PEARLY && (VBULK != 4 || w != VBW)) poll();
    {
      uint32_t pk[8];
#pragma unroll
      for (int q = 0; q < 8; q++) pk[q] = pack2(d[2 * q], d[2 * q + 1]);
      stsm4t(rP + (G == 1 ? R_VT : R_KT) + 1024, pk[0], pk[1], pk[2], pk[3]);
      stsm4t(rP + (G == 1 ? R_VT : R_KT) + 3072, pk[4], pk[5], pk[6], pk[7]);
      if (G == 1 && VBULK) {
        if (VBULK == 1) fence_async_smem();
        if (VBULK == 1 || VBULK == 4) {
          if (w != VBW) bar_arrive(6, 128);
          else {
            bar_sync(6, 128);
            vsend();
            if (VBULK == 4 && !FIRST) poll();
          }
        }
      } else if (G == 1) {
        const uint32_t e1 = mapa(rF + R_V1 + 4096 + w * 512, r1), e2 = mapa(rF + R_V1 + w * 512, r2), b1 = mapa(VBAR, r1), b2 = mapa(VBAR, r2);
        st_async4(e1, pk[0], pk[1], pk[2], pk[3], b1);
        st_async4(e2, pk[0], pk[1], pk[2], pk[3], b2);
        st_async4(e1 + 2048, pk[4], pk[5], pk[6], pk[7], b1);
        st_async4(e2 + 2048, pk[4], pk[5], pk[6], pk[7], b2);
      }
    }
    if (FIRST) {
      mbar_wait(WBAR + 16, 0);
      if (G == 0 && cta) GTR(11);
      const uint32_t woA = rW_;
      float na[4] = {0.f, 0.f, 0.f, 0.f}, nb[4] = {0.f, 0.f, 0.f, 0.f};
#pragma unroll
      for (int ks = 0; ks < 12; ks++) {
        uint32_t a[4], b[4];
        ldsm4t(a, woA + WOFF(ks));
        ldsm4t(b, (two ? woA ^ 32 : woA) + WOFF(ks));
#pragma unroll
        for (int q = 0; q < 4; q++) { a[q] &= 0x7fff7fffu; b[q] &= 0x7fff7fffu; }
        mma16816(na, a, ONES, ONES);
        mma16816(nb, b, ONES, ONES);
      }
      const uint32_t mo = __reduce_max_sync(~0u, __float_as_uint(fmaxf(fmaxf(na[0], na[2]), fmaxf(nb[0], nb[2]))));
      if (rF == sb) smax32(sb + R_MI + 56, mo);
      __syncthreads();
      if (G == 1 && w == 2) {
        const uint4 r = lds128(sb + R_MI + 48);
        const uint32_t epoch = lds32(sb + R_MI);
        if (rF == sb) stg_rlx64(&g_rec[cta], (r.y & 0xffff0000u) | (epoch & 0xffffu), ((r.x + 0xffffu) & 0xffff0000u) | ((r.z + 0xffffu) >> 16));
      }
    }
#pragma unroll
    for (int f = FIRST ? 0 : (G == 1 ? NQ_W1 : NQ_WIN); f < NQ; f++) ldsm4t(wqt[f], wqS + f * 2048);
    if (FIRST || DFENCE) sched_fence(sb);
    TR(14);
    const uint32_t ma = sb + R_MEM + G * 5120 + t * 8;
    if (FIRST) {
      bar_sync(9 - G, 256);
#pragma unroll
      for (int j = 0; j < 5; j++) sts64(ma + j * 1024, y[j].x | (y[j].y << 16), y[j].z | (y[j].w << 16));
    } else {
      int n = 0;
#pragma unroll 1
      while (!__all_sync(~0u, (y[0].y & y[0].w & y[1].y) & (y[1].w & y[2].y & y[2].w) & (y[3].y & y[3].w & y[4].y) & (y[4].w & 4))) {
#pragma unroll
        for (int j = 0; j < 5; j++) if (!(y[j].y & y[j].w & 4)) y[j] = ldg_rlx128(yp + rb_q(G * 5 + j));
        if (++n > SPIN_MAX) { g_err = 5; break; }
      }
      const uint32_t bias = 0x80000000u + (sb >> 31);
      bar_sync(9 - G, 256);
#pragma unroll
      for (int j = 0; j < 5; j++) sts64(ma + j * 1024, dec_pair(y[j].x, y[j].y, bias), dec_pair(y[j].z, y[j].w, bias));
    }
    if (G == 0 && zr == ~0ull) g_err = 9;
    TR(0);
  };

  auto oproj = [&](auto TWO_, auto NPRE_, auto& wot, const uint32_t rF, const uint32_t woA, const uint32_t woB,
                   float sm0, float sm1, bool have_sums) {
    constexpr bool TWO = decltype(TWO_)::value;
    constexpr int NPRE = decltype(NPRE_)::value;
    float c[4][4];
#pragma unroll
    for (int q = 0; q < 4; q++) c[q][0] = c[q][1] = c[q][2] = c[q][3] = 0.f;
    unsigned char* sp = red + (rb_b(s) + toff + ((rF - sb) & 256) + (((rF - sb) >> 1) & 120));
    bar_sync(3, 256);
    TR(8);
    uint4 ob[6];
    ob[0] = lds128(rF + R_QB); ob[1] = lds128(rF + R_QB + 512);
    const float2 su = lds64f(sb + R_MI + 48);
    if (!have_sums) { const float2 t = lds64f(sb + R_MI + 16 + (((rF - sb) >> 1) & 24)); sm0 = t.x; sm1 = t.y; }
#pragma unroll
    for (int p = 0; p < 6; p++) {
      if (p + 2 < 6) ob[p + 2] = lds128(rF + (p < 2 ? R_QA : R_O2) + (p & 1) * 512);
#pragma unroll
      for (int e = 0; e < 2; e++) {
        const int ks = 2 * p + e;
        const uint32_t b0 = e ? ob[p].z : ob[p].x, b1 = e ? ob[p].w : ob[p].y;
        if (TWO) {
          const int iA = 2 * ks, iB = iA + 1;
          mma16816(c[e], wot[iA % NPRE], b0, b1);
          if (iA + NPRE < 24) ldsm4t(wot[iA % NPRE], woA + WOFF((iA + NPRE) >> 1));
          mma16816(c[2 + e], wot[iB % NPRE], b0, b1);
          if (iB + NPRE < 24) ldsm4t(wot[iB % NPRE], woB + WOFF((iB + NPRE) >> 1));
        } else {
          mma16816(c[ks & 3], wot[ks], b0, b1);
        }
      }
    }
    const float f0 = su.x * rcp(sm0), f1 = su.x * rcp(sm1);
    t0 = clk32() + (TWO ? (have_sums ? -PDT : 0) : PDS);
    u = su.y;
    if (TWO) {
      red_pair(sp, (c[0][0] + c[1][0]) * f0, (c[0][1] + c[1][1]) * f1);
      red_pair(sp + rb_j(2), (c[0][2] + c[1][2]) * f0, (c[0][3] + c[1][3]) * f1);
      red_pair(sp + rb_j(4), (c[2][0] + c[3][0]) * f0, (c[2][1] + c[3][1]) * f1);
      red_pair(sp + rb_j(6), (c[2][2] + c[3][2]) * f0, (c[2][3] + c[3][3]) * f1);
    } else {
      red_pair(sp, ((c[0][0] + c[1][0]) + (c[2][0] + c[3][0])) * f0, ((c[0][1] + c[1][1]) + (c[2][1] + c[3][1])) * f1);
      red_pair(sp + rb_j(2), ((c[0][2] + c[1][2]) + (c[2][2] + c[3][2])) * f0, ((c[0][3] + c[1][3]) + (c[2][3] + c[3][3])) * f1);
    }
    TR(15);
  };

  auto step = [&](auto G_, auto LAST_) {
    constexpr int G = decltype(G_)::value;
    constexpr bool LAST = decltype(LAST_)::value;
    __syncthreads();
    const uint32_t rF = pin(rF_), rP = pin(rP_);
    TR(1);
    if (LAST) {
      const uint32_t l = (rF - sb) >> 4;
      uint4* qp = g_Ql + ((head * 2 + G) * 4 + w) * 384 + l;
      if ((int)lds32(sb + R_MI + 4) < 0) {
#pragma unroll 1
        for (int i = 0; i < 48; i++) {
          const bf16* xr = x + (size_t)(S_TOK - 128 + G * 64 + w * 16 + (l >> 2) + (i & 1) * 8) * DM;
          const uint32_t* wr = (const uint32_t*)(Wq + head * DH + (i >> 2) * 16 + (l & 3) * 2 + (i & 2) * 4);
          float a0 = 0.f, a1 = 0.f;
#pragma unroll 1
          for (int k = 0; k < DM; k++) {
            const float xv = __bfloat162float(xr[k]);
            const uint32_t wv = wr[k * (HD / 2)];
            a0 = fmaf(xv, bf_lo(wv), a0); a1 = fmaf(xv, bf_hi(wv), a1);
          }
          ((uint32_t*)(qp + (i >> 2) * 32))[i & 3] = pack2(a0, a1);
        }
      }
#pragma unroll
      for (int f = 0; f < 12; f++) { const uint4 t = ldg_rlx128(qp + f * 32); wqt[f][0] = t.x; wqt[f][1] = t.y; wqt[f][2] = t.z; wqt[f][3] = t.w; }
      const float* gp = g_gate + (S_TOK - 128) + G * 64 + w * 16 + (l >> 2);
      wqp[0][0] = ldg_rlx32(gp); wqp[0][1] = ldg_rlx32(gp + 8);
      if (G == 1 && w == 1) {
        mbar_wait(VBAR, (NSEG - 1) & 1);
        if (elect()) {
          bulk_wait0();
          asm volatile("mbarrier.arrive.release.cluster.shared::cluster.b64 _, [%0];" ::"r"(mapa(sb + R_EB + 32, r1)) : "memory");
          asm volatile("mbarrier.arrive.release.cluster.shared::cluster.b64 _, [%0];" ::"r"(mapa(sb + R_EB + 32, r2)) : "memory");
#pragma unroll 1
          for (int b = 0; b < 6; b++)
            tma_load2(sb + b * 10240 + 5120, b < 3 ? &tmK : &tmV, head * DH + (b % 3) * 64, (NSEG - 3) * LK, sb + R_EB + (b / 3) * 8);
        }
        __syncwarp();
      }
    }
    const uint32_t wqS = rP + R_WQ + G * (20 - NPQ) * 2048, rM = rF + R_MEM;
    const uint32_t l8 = sb + ((rF - sb) >> 1) + w * 256;
    const uint32_t woA = pin(rW_), woB = woA ^ 32;
    float aq[2][4] = {};
    const uint32_t ln = (rF - sb) >> 4;
    const uint32_t rS = sb + (ln & 7) * 128 + (ln < 16 ? R_QB + (ln & 8) * 128 + (((2 * w + G) ^ (ln & 7)) << 4) : R_KT + (((2 * w + ((ln >> 3) & 1)) ^ (ln & 7)) << 4));
    auto qmma = [&](int f, uint32_t b0, uint32_t b1) {
      if (f < NPQ) mma16816(aq[f & 1], wqp[f], b0, b1);
      else {
        const int slot = (f - NPQ) % NQ;
        mma16816(aq[f & 1], wqt[slot], b0, b1);
        if (f + NQ < 20) ldsm4t(wqt[slot], wqS + (f - NPQ + NQ) * 2048);
      }
    };
    if constexpr (G == 1) {
      uint32_t bb[20][4];
      if (!LAST) {
        if (VBULK == 2 && w == VBW) vsend();
        ldsm4t(bb[10], rM + 5120);
        ldsm4t(bb[11], rM + 5632);
#pragma unroll
        for (int i = 10; i < 20; i++) {
          if (i + 2 < 20) ldsm4t(bb[i + 2], rM + (i + 2) * 512);
          qmma(2 * i - 20, bb[i][0], bb[i][1]);
          qmma(2 * i - 19, bb[i][2], bb[i][3]);
        }
        stsm2t(rS, pack2(aq[0][0] + aq[1][0], aq[0][1] + aq[1][1]), pack2(aq[0][2] + aq[1][2], aq[0][3] + aq[1][3]));
        bar_arrive(1, 256);
        if (VBULK == 3 && w == VBW) vsend();
      }
      TR(2);
      float av[4][4] = {};
      uint32_t m0 = 0, m1 = 0;
      auto vmma = [&](auto MAX_) {
#pragma unroll
        for (int n = 0; n < 20; n++) {
          const int i = (n + 10) % 20;
          if (LAST && n < 8) ldsm4t(bb[(n + 10) % 20], rM + ((n + 10) % 20) * 512);
          if (LAST && n == 0) { ldsm4t(bb[18], rM + 18 * 512); ldsm4t(bb[19], rM + 19 * 512); }
          if (n == VB && !LAST) { bar_sync(5, 256); sched_fence(sb); }
          if (n == VLD) {
            if (VB != VLD && !LAST) sched_fence(sb);
#pragma unroll
            for (int q = 0; q < 10; q++) ldsm4t(bb[q], rM + q * 512);
            if (!LAST) sched_fence(sb);
          }
          mma16816(av[(2 * n) & 3], ww[2 * i], bb[i][0], bb[i][1]);
          mma16816(av[(2 * n + 1) & 3], ww[2 * i + 1], bb[i][2], bb[i][3]);
          if (decltype(MAX_)::value) { m0 = hmaxabs2(m0, hmaxabs2(bb[i][0], bb[i][1])); m1 = hmaxabs2(m1, hmaxabs2(bb[i][2], bb[i][3])); }
        }
      };
      auto vout = [&]() {
        const uint32_t vm0 = pack2(((av[0][0] + av[1][0]) + (av[2][0] + av[3][0])) * u, ((av[0][1] + av[1][1]) + (av[2][1] + av[3][1])) * u);
        const uint32_t vm1 = pack2(((av[0][2] + av[1][2]) + (av[2][2] + av[3][2])) * u, ((av[0][3] + av[1][3]) + (av[2][3] + av[3][3])) * u);
        if (!LAST) {
          st_async2(mapa(l8 + R_VM + 1024, r1), vm0, vm1, mapa(OBAR, r1));
          st_async2(mapa(l8 + R_VM, r2), vm0, vm1, mapa(OBAR, r2));
          sts64(l8 + R_VS, vm0, vm1);
          __syncwarp();
          if (rF == sb) mbar_arrive(OBAR);
        }
        stsm2t(rP + R_VT, vm0, vm1);
      };
      if (LAST) {
        vmma(std::false_type{});
        vout();
        if (w == 1) {
          mbar_wait_cl(sb + R_EB + 32, 0);
          if (elect()) {
            asm volatile("fence.proxy.async.global;" ::: "memory");
#pragma unroll 1
            for (int b = 0; b < 5; b++)
              tma_load2(sb + (b < 3 ? E_KB + b * 10240 : (b == 3 ? E_VB0 : E_VB1)), b < 3 ? &tmK : &tmV, head * DH + (b % 3) * 64, (NSEG - 2) * LK,
                        sb + R_EB + 16 + (b / 3) * 8);
          }
          __syncwarp();
        }
        return;
      }
      uint32_t wot[NW1][4];
      auto wpre = [&](int i0, int i1) {
#pragma unroll
        for (int i = i0; i < i1; i++) ldsm4t(wot[i], ((i & 1) ? woB : woA) + WOFF(i >> 1));
      };
      if (w != 1) {
        vmma(std::false_type{});
        bar_arrive(7, 128);
        vout();
        bar_arrive(2, 128);
        TR(5);
        wpre(0, NW1A);
      } else {
        vmma(std::true_type{});
        bar_sync(7, 128);
        if (elect()) { mbar_expect(XBAR, 40960); tma_load3(sb + R_XT, &tmX, 0, (s + 1) * SEG, 0, XBAR); }
        __syncwarp();
        vout();
        if (XPF && s + XPF < NSEG && rF - sb < 64 && cta < 80) prefetch_l2(x + (size_t)(s + XPF) * SEG * DM + cta * 256 + (rF - sb) * 4);
        TR(5);
        m0 = hmaxabs2(m0, m1);
        const uint32_t mx = __reduce_max_sync(~0u, max((m0 << 16) & 0x7fffffffu, m0 & 0x7fff0000u));
        const float2 mi = lds64f(sb + R_MI + 8);
        wpre(0, NW1A);
        bar_sync(2, 128);
        if (elect()) {
          fence_async_smem();
          if (s > 0) {
            bulk_wait0();
            asm volatile("red.relaxed.gpu.global.add.u32 [%0], 1;" ::"l"(&g_segcnt[s - 1]) : "memory");
            asm volatile("red.relaxed.gpu.global.add.u32 [%0], 1;" ::"l"(&g_prog) : "memory");
          }
          tma_store2(&tmK, sb + R_KT, D0, s * LK);
          tma_store2(&tmV, sb + R_VT, D0, s * LK);
          bulk_commit();
        }
        __syncwarp();
        float wb = mi.x, xm = mi.y;
        if (s == 0) {
          const uint32_t epoch = lds32(sb + R_MI);
          uint32_t av_ = 0, ao = 0, xi = 0;
#pragma unroll 1
          for (int j = 0; j < 3; j++) {
            uint2 r;
            int n = 0;
#pragma unroll 1
            while (true) {
              r = ldg_rlx64(&g_rec[j * 32 + ((rF - sb) >> 4)]);
              if (((r.x ^ epoch) & 0xffffu) == 0) break;
              if (++n > SPIN_MAX) { g_err = 6; break; }
            }
            av_ = max(av_, r.y & 0xffff0000u); ao = max(ao, r.y << 16); xi = max(xi, r.x & 0xffff0000u);
          }
          av_ = __reduce_max_sync(~0u, av_); ao = __reduce_max_sync(~0u, ao); xi = __reduce_max_sync(~0u, xi);
          wb = __uint_as_float(av_) * __uint_as_float(ao) * 33.f; xm = __uint_as_float(xi);
          if (rF == sb) {
            sts64f(sb + R_MI + 8, wb, xm);
            asm volatile("fence.acq_rel.gpu;\nred.relaxed.gpu.global.add.u32 [%0], 1;" ::"l"(&g_cnt[C_GATE * 8]) : "memory");
          }
          __syncwarp();
        }
        const float hm = fmaxf(__uint_as_float(mx) * u, xm);
        const uint32_t eb = min(max(__float_as_uint(hm * wb) >> 23, 40u), 200u);
        if (rF == sb) sts64(sb + R_MI + 48, (280u - eb) << 23, (eb - 29u) << 23);
        if (elect()) bulk_wait_read0();
        __syncwarp();
      }
      if (NW1A < NW1) {
        bar_sync(4, 256);
        wpre(NW1A, NW1);
      }
      TR(6);
      oproj(std::true_type{}, std::integral_constant<int, NW1>{}, wot, rF, woA, woB, 0.f, 0.f, false);
    } else {
      {
        uint32_t bb[20][4];
        float ak[4][4] = {};
        ldsm4t(bb[0], rM);
        ldsm4t(bb[10], rM + 5120);
#pragma unroll
        for (int i = 0; i < 10; i++) {
          if (i + 1 < 10) { ldsm4t(bb[i + 1], rM + (i + 1) * 512); ldsm4t(bb[i + 11], rM + (i + 11) * 512); }
          mma16816(ak[0], ww[2 * i], bb[i][0], bb[i][1]);
          if (!LAST) qmma(2 * i, bb[i][0], bb[i][1]);
          mma16816(ak[1], ww[2 * i + 1], bb[i][2], bb[i][3]);
          if (!LAST) qmma(2 * i + 1, bb[i][2], bb[i][3]);
          mma16816(ak[2], ww[2 * i + 20], bb[i + 10][0], bb[i + 10][1]);
          mma16816(ak[3], ww[2 * i + 21], bb[i + 10][2], bb[i + 10][3]);
        }
#pragma unroll
        for (int q = 0; q < 4; q++) { ak[0][q] += ak[2][q]; ak[1][q] += ak[3][q]; }
        stsm4t(rS, pack2(aq[0][0] + aq[1][0], aq[0][1] + aq[1][1]), pack2(aq[0][2] + aq[1][2], aq[0][3] + aq[1][3]),
               pack2((ak[0][0] + ak[1][0]) * u, (ak[0][1] + ak[1][1]) * u), pack2((ak[0][2] + ak[1][2]) * u, (ak[0][3] + ak[1][3]) * u));
      }
      if (LAST) return;
      bar_sync(1, 256);
      if (!B5LATE) bar_arrive(5, 256);
      TR(2);
      if (w != 3) {
        uint32_t qa[4][4], kk[4][4];
        float x[4][4] = {};
#pragma unroll
        for (int i = 0; i < 4; i++) { ldsm4(qa[i], (rP ^ (i << 5)) + R_QB); ldsm4(kk[i], ((rP ^ (i << 5)) + w * 2048) + R_KT); }
        const uint32_t dst = rF + R_SX + rank * 1536 + w * 512;
        const uint32_t e1 = mapa(dst, r1), e2 = mapa(dst, r2), s1 = mapa(SBAR, r1), s2 = mapa(SBAR, r2);
#pragma unroll
        for (int i = 0; i < 4; i++) { mma16816(x[i & 1], qa[i], kk[i][0], kk[i][1]); mma16816(x[2 + (i & 1)], qa[i], kk[i][2], kk[i][3]); }
        const uint32_t u0 = __float_as_uint((x[0][0] + x[0][2]) + (x[1][0] + x[1][2])), u1 = __float_as_uint((x[0][1] + x[0][3]) + (x[1][1] + x[1][3]));
        const uint32_t u2 = __float_as_uint((x[2][0] + x[2][2]) + (x[3][0] + x[3][2])), u3 = __float_as_uint((x[2][1] + x[2][3]) + (x[3][1] + x[3][3]));
        st_async4(e1, u0, u1, u2, u3, s1);
        st_async4(e2, u0, u1, u2, u3, s2);
        sts128(dst, u0, u1, u2, u3);
        __syncwarp();
        if (rF == sb) mbar_arrive(SBAR);
      } else if (s == NSEG - 2) {
        sts32(sb + R_MI + 4, ldg_rlx32(&g_cnt[(C_O + 240 + (head >> 1)) * 8]) - lds32(sb + R_MI) * 2);
        asm volatile("fence.acquire.gpu; fence.proxy.async.global;" ::: "memory");
        if (elect()) {
#pragma unroll 1
          for (int b = 0; b < 6; b++)
            tma_load2(sb + b * 10240, b < 3 ? &tmK : &tmV, head * DH + (b % 3) * 64, (NSEG - 4) * LK, sb + R_EB + (b / 3) * 8);
        }
        __syncwarp();
      }
      if (B5LATE) bar_arrive(5, 256);
      TR(4);
      mbar_wait(VBAR, s & 1);
      uint32_t wot[12][4], va[3][8];
      ldsm4t(va[0], rP + R_VT + 1024); ldsm4t(va[0] + 4, rP + R_VT + 3072);
#pragma unroll
      for (int q = 0; q < 4; q++) {
        if (VBULK) { ldsm4t(va[1 + (q >> 1)] + (q & 1) * 4, rP + R_V1 + q * 2048); continue; }
        const uint4 t = lds128(rF + R_V1 + w * 512 + q * 2048);
        uint32_t* v = va[1 + (q >> 1)] + (q & 1) * 4;
        v[0] = t.x; v[1] = t.y; v[2] = t.z; v[3] = t.w;
      }
      auto wpre = [&](int i0, int i1) {
        if (two) {
#pragma unroll
          for (int i = i0; i < i1; i++) ldsm4t(wot[i], ((i & 1) ? woB : woA) + WOFF(i >> 1));
        } else {
#pragma unroll
          for (int i = i0; i < i1; i++) ldsm4t(wot[i], woA + WOFF(i));
        }
      };
      wpre(0, NO_EARLY);
      const uint32_t dst = rF + (w >> 1) * 512 + (w & 1) * 8;
      const float scl = u * (0.07216878364870322f * 1.4426950408889634f);
      mbar_wait(SBAR, s & 1);
      TR(6);
      float sc[10];
      {
        const float4 a0 = lds128f(rF + R_SX), b0 = lds128f(rF + R_SX + 1536), c0 = lds128f(rF + R_SX + 3072);
        const float4 a1 = lds128f(rF + R_SX + 512), b1 = lds128f(rF + R_SX + 2048), c1 = lds128f(rF + R_SX + 3584);
        const float2 a2 = lds64f(rF + R_SX + 1024), b2 = lds64f(rF + R_SX + 2560), c2 = lds64f(rF + R_SX + 4096);
        sc[8] = a0.x + b0.x + c0.x; sc[9] = a0.y + b0.y + c0.y; sc[0] = a0.z + b0.z + c0.z; sc[1] = a0.w + b0.w + c0.w;
        sc[2] = a1.x + b1.x + c1.x; sc[3] = a1.y + b1.y + c1.y; sc[4] = a1.z + b1.z + c1.z; sc[5] = a1.w + b1.w + c1.w;
        sc[6] = a2.x + b2.x + c2.x; sc[7] = a2.y + b2.y + c2.y;
      }
      float mx = fmaxf(fmaxf(fmaxf(sc[0], sc[1]), fmaxf(sc[2], sc[3])), fmaxf(fmaxf(sc[4], sc[5]), fmaxf(sc[6], sc[7])));
      mx = fmaxf(mx, fmaxf(sc[8], sc[9]));
      mx = fmaxf(mx, __shfl_xor_sync(~0u, mx, 1));
      const bool vok = mbar_test(OBAR, s & 1);
      mx = fmaxf(mx, __shfl_xor_sync(~0u, mx, 2));
      if (NW1A < NW1) bar_arrive(4, 256);
      const float mo = mx * scl;
      uint32_t pb[5];
#pragma unroll
      for (int j = 0; j < 5; j++) pb[j] = pack2(ex2(fmaf(sc[2 * j], scl, -mo)), ex2(fmaf(sc[2 * j + 1], scl, -mo)));
      if (!vok) mbar_wait(OBAR, s & 1);
      const uint2 m0 = lds64(l8 + R_VS), m1 = lds64(l8 + R_VM), m2 = lds64(l8 + R_VM + 1024);
      const uint32_t ones[4] = {ONES, ONES, ONES, ONES};
      float o[3][4], o2[3][4], sm[4] = {0.f, 0.f, 0.f, 0.f}, sn[4] = {0.f, 0.f, 0.f, 0.f}, so[4] = {0.f, 0.f, 0.f, 0.f};
#pragma unroll
      for (int b = 0; b < 3; b++) {
        o[b][0] = o[b][1] = o[b][2] = o[b][3] = o2[b][0] = o2[b][1] = o2[b][2] = o2[b][3] = 0.f;
        mma16816(o[b], va[b], pb[0], pb[1]);
      }
#pragma unroll
      for (int b = 0; b < 3; b++) mma16816(o2[b], va[b] + 4, pb[2], pb[3]);
      mma1688(o[0], m0.x, m0.y, pb[4]);
      mma1688(o[1], m1.x, m1.y, pb[4]);
      mma1688(o[2], m2.x, m2.y, pb[4]);
      mma16816(sm, ones, pb[0], pb[1]);
      mma16816(sn, ones, pb[2], pb[3]);
      mma1688(so, ONES, ONES, pb[4]);
      wpre(NO_EARLY, NO_MID);
#pragma unroll
      for (int b = 0; b < 3; b++)
        sts64(dst + (b == 0 ? R_QB : (b == 1 ? R_QA : R_O2)), movmat(pack2(o[b][0] + o2[b][0], o[b][1] + o2[b][1])),
              movmat(pack2(o[b][2] + o2[b][2], o[b][3] + o2[b][3])));
      sm[0] += sn[0] + so[0]; sm[1] += sn[1] + so[1];
      if (rF - sb < 64) sts64f(sb + R_MI + 16 + ((rF - sb) >> 1), sm[0], sm[1]);
      wpre(NO_MID, 12);
      TR(7);
      if (two) oproj(std::true_type{}, std::integral_constant<int, 12>{}, wot, rF, woA, woB, sm[0], sm[1], true);
      else oproj(std::false_type{}, std::integral_constant<int, 12>{}, wot, rF, woA, woB, sm[0], sm[1], true);
    }
  };

  if (g == 0) {
    window(std::integral_constant<int, 0>{}, std::true_type{});
    GTR(7);
#pragma unroll 1
    for (s = 0; s < NSEG - 1; s++) {
      step(std::integral_constant<int, 0>{}, std::false_type{});
      window(std::integral_constant<int, 0>{}, std::false_type{});
    }
    step(std::integral_constant<int, 0>{}, std::true_type{});
  } else {
    window(std::integral_constant<int, 1>{}, std::true_type{});
#pragma unroll 1
    for (s = 0; s < NSEG - 1; s++) {
      step(std::integral_constant<int, 1>{}, std::false_type{});
      window(std::integral_constant<int, 1>{}, std::false_type{});
    }
    step(std::integral_constant<int, 1>{}, std::true_type{});
  }
  fence_async_smem();
  __syncthreads();
  GTR(8);
#define CG(i) do {} while (0)
  if (wid == 5) {
    if (elect()) {
      const uint32_t kd = sb + E_KB + rank * 10240 + 5120, vd = sb + (rank == 0 ? E_VB0 : (rank == 1 ? E_VB1 : E_VB2)) + 5120;
#pragma unroll 1
      for (uint32_t r = 0; r < 3; r++) bulk_s2s(mapa(kd, r), sb + R_KT, 5120, mapa(sb + R_EB + 16, r));
      tma_load2(sb + E_VB2, &tmV, head * DH + 128, (NSEG - 2) * LK, sb + R_EB + 24);
      if (rank != 2) asm volatile("mbarrier.arrive.release.cluster.shared::cluster.b64 _, [%0];" ::"r"(mapa(sb + R_EB + 40, 2)) : "memory");
      else mbar_wait_cl(sb + R_EB + 40, 0);
#pragma unroll 1
      for (uint32_t r = 0; r < 3; r++) bulk_s2s(mapa(vd, r), sb + R_VT, 5120, mapa(sb + R_EB + 24, r));
      asm volatile("red.relaxed.gpu.global.add.u32 [%0], 1;" ::"l"(&g_segcnt[NSEG - 2]) : "memory");
      asm volatile("red.relaxed.gpu.global.add.u32 [%0], 1;" ::"l"(&g_segcnt[NSEG - 1]) : "memory");
      asm volatile("red.relaxed.gpu.global.add.u32 [%0], 2;" ::"l"(&g_prog) : "memory");
    }
    __syncwarp();
  }
  {
    const uint32_t kb = sb + (g ? E_KB : E_KA);
    float sc[40] = {};
    uint32_t pf[5][4];
    mbar_wait(sb + R_EB + g * 16, 0);
    if (CT) CG(11);
    wg_fence();
#pragma unroll
    for (int ks = 0; ks < 12; ks++) wgmma_rs80(sc, wqt[ks], mk_desc(kb, 16, 1024, 1) + (((ks >> 2) * 10240 + (ks & 3) * 32) >> 4), ks);
    wg_commit();
    const AttMask am(tid, sb);
    wg_wait0();
    fence_regs<40>(sc);
    CG(12);
    att_softmax(am, sc, pf, __uint_as_float(wqp[0][0]), __uint_as_float(wqp[0][1]));
    float o[96] = {};
    mbar_wait(sb + R_EB + g * 16 + 8, 0);
    CG(13);
    wg_fence();
#pragma unroll
    for (int b = 0; b < 3; b++) {
      const Desc db = mk_desc(sb + (g ? (b == 0 ? E_VB0 : (b == 1 ? E_VB1 : E_VB2)) : E_VA + b * 10240), 1024, 1024, 1);
#pragma unroll
      for (int ks = 0; ks < 5; ks++) wgmma_rs64t(o + 32 * b, pf[ks], db + ks * 128, ks);
    }
    wg_commit();
    wg_wait0();
    fence_regs<96>(o);
    CG(14);
    uint32_t of[12][4];
#pragma unroll
    for (int i = 0; i < 48; i++) asm volatile("cvt.rn.bf16x2.f32 %0, %1, %2;" : "=r"(of[i >> 2][i & 3]) : "f"(o[2 * i + 1]), "f"(o[2 * i]));
    float y[112] = {};
    wg_fence();
#pragma unroll
    for (int j = 0; j < 3; j++) {
      const Desc db = mk_desc((sb & 0x3ffff) + R_WO + ((j + 3 - rank) % 3) * 28672, 4096, 512, 2);
#pragma unroll
      for (int ks = 0; ks < 4; ks++) wgmma_rs224t(y, of[4 * j + ks], db + ks * 64, j + ks);
    }
    wg_commit();
    wg_wait0();
    fence_regs<112>(y);
    CG(15);
    const uint32_t da = kb + (w * 16 + (lane & 15)) * 64, sx = (lane >> 1) & 3;
#pragma unroll
    for (int i = 0; i < 14; i++)
      stsm4(da + (i >> 1) * 4096 + (((2 * (i & 1) + (lane >> 4)) ^ sx) << 4), pack2(y[8 * i], y[8 * i + 1]), pack2(y[8 * i + 2], y[8 * i + 3]),
            pack2(y[8 * i + 4], y[8 * i + 5]), pack2(y[8 * i + 6], y[8 * i + 7]));
    fence_async_smem();
    bar_sync(1 + g, 128);
    if (w == 0 && elect()) {
#pragma unroll 1
      for (int i = 0; i < (rank == 1 ? 6 : 7); i++) tma_red2(&tmOut, kb + i * 4096, tile0 * 16 + i * 32, S_TOK - 128 + g * 64);
      bulk_commit();
      bulk_wait0();
    }
  }
  GTR(9);
}

enum { IT_GATE = 0, IT_QKV = 1, IT_XATT = 2, IT_OUT = 3, IT_BATT = 4, IT_Q = 5, IT_INIT = 6, IT_END = 7 };
constexpr uint32_t NONE = ~0u;
#define HP 0x1244688888888888ull
#define XD 0x4888888888999bbbull
#define KREQ 4
#define ADELAY 10000
#define LAG 0
#define W_PRO 11
#define W_SCH 8
#define W_AG1 10
#define KEARLY 1
#define CVTS 6
#define RSL 20
#define PACE 500
#define SPLITW 0
#define XPP 22
#define PP 3
__host__ __device__ constexpr uint32_t mk_item(int ty, int t, int a, int b = 0, int c = 0) { return ty | (t << 3) | (a << 8) | (b << 16) | (c << 24); }
struct ItemTab { uint32_t v[1280]; int n; };
constexpr ItemTab make_items() {
  ItemTab T{};
  int n = 0;
  for (int t = 0; t < 16; t++) for (int a = 0; a < 5; a++) T.v[n++] = mk_item(IT_QKV, t, a);
  for (int a = 0; a < 16; a++) T.v[n++] = mk_item(IT_Q, 15, a);
  for (int t = 0; t < 32; t++) T.v[n++] = mk_item(IT_BATT, t, 0);
  for (int t = 0; t < 16; t++) for (int a = 0; a < 2; a++) T.v[n++] = mk_item(IT_INIT, t, a);
  for (int t = 0; t < 15; t++) {
    const int hp = (HP >> 4 * t) & 15;
    for (int h = 0; h < 32; h += hp) for (int a = 0; a < 2; a++) T.v[n++] = mk_item(IT_OUT, t, a, h, h + hp < 32 ? h + hp : 32);
  }
  T.n = n;
  return T;
}
constexpr ItemTab k_items_host = make_items();
constexpr int NITEMS = k_items_host.n;
__constant__ ItemTab c_items = make_items();

#define AUX_GRID 36
constexpr int NST = 7, STG = 32768;
constexpr int A_FULL = NST * STG, A_EMPTY = A_FULL + 64, A_ITEM = A_EMPTY + 64, A_QBAR = A_ITEM + 32, A_QENT = A_QBAR + 128, A_MISC = A_QENT + 256,
              A_SMEM = A_MISC + 64, A_REQ = A_FULL + 56, A_RSP = A_EMPTY + 56, A_MAIL = A_MISC + 48, A_RDY = A_MISC + 32;
static_assert(A_SMEM <= 232448, "smem");
enum { OP_END = 0, OP_O = 1, OP_QKV = 2, OP_OB = 3, OP_SET = 4, OP_ADD = 5, OP_Q = 6 };

struct AuxMaps { CUtensorMap xA, wq, wqkv, wo, wob, k, v, oA, oS, obA, obS, qkvS, qkvQ, qkvK, out; };

__device__ __forceinline__ void mbar_wait_long(uint32_t b, uint32_t par) {
  int n = 0;
#pragma unroll 1
  while (!mbar_try(b, par)) { if (++n > (SPIN_MAX << 4)) { g_err = 8; break; } }
}
__device__ __forceinline__ void mbar_wait_u(uint32_t b, uint32_t par) {
  asm volatile("{.reg .pred p; .reg .u32 n;\nmov.u32 n, 0;\nLW: mbarrier.try_wait.parity.shared::cta.b64 p, [%0], %1;\n@p bra.uni LD;\n"
               "add.u32 n, n, 1;\nsetp.lt.u32 p, n, %2;\n@p bra.uni LW;\nLD:\n}" ::"r"(b), "r"(par), "n"(SPIN_MAX << 4) : "memory");
}
__global__ void __launch_bounds__(384, 1)
aux_kernel(const __grid_constant__ AuxMaps tm) {
  extern __shared__ __align__(1024) unsigned char smem[];
  const uint32_t sb = smem_u32(smem);
  const int tid = threadIdx.x, lane = tid & 31, wid = __shfl_sync(~0u, tid >> 5, 0);
  uint32_t epoch = 0, j0 = 0;
  const uint32_t c0 = clk32();
  if (tid == W_SCH * 32) GTA(0);
  if (tid >= 256) epoch = *(volatile uint32_t*)&g_epoch + 1;
  if (tid == W_SCH * 32) j0 = atomicAdd(&g_queue[32], 1u);
  if (tid == 0) {
    mbar_init(sb + A_REQ, 1); mbar_init(sb + A_RSP, 1); mbar_init(sb + A_RDY, 1);
    for (int i = 0; i < NST; i++) { mbar_init(sb + A_FULL + i * 8, 1); mbar_init(sb + A_EMPTY + i * 8, 8); }
    for (int i = 0; i < 16; i++) mbar_init(sb + A_QBAR + i * 8, 4);
    asm volatile("fence.mbarrier_init.release.cluster;" ::: "memory");
  }
  if (tid < 15) prefetch_map(&tm.xA + tid);
  if (tid == W_SCH * 32) GTA(4);
  __syncthreads();
  if (tid == W_SCH * 32) GTA(5);
  uint32_t st = 0, ph = 0;
  auto advance = [&]() { if (++st == NST) { st = 0; ph ^= 1; } };

  if (wid >= 8) {
    asm volatile("setmaxnreg.dec.sync.aligned.u32 40;");
    if (tid == W_SCH * 32) GTA(6);
    auto cnt = [&](int c, uint32_t per) -> bool { return (int)(ldg_rlx32(&g_cnt[c * 8]) - epoch * per) >= 0; };
    auto ready = [&](uint32_t item) -> int {
      const int ty = item & 7, t = (item >> 3) & 31, b = (item >> 17) & 127, n = (((item >> 24) + 1) >> 1) - b;
      int r;
      if (ty == IT_OUT) {
        const int c = C_O + t * 16 + b;
        const bool r0 = cnt(c, 2), r1 = cnt(c + (n > 1), 2), r2 = cnt(c + (n > 2) * 2, 2), r3 = cnt(c + (n > 3) * 3, 2);
        r = r0 & cnt(C_ACC + t, 4) ? (r1 ? (r2 ? (r3 ? 4 : 3) : 2) : 1) : 0;
      } else if (ty == IT_XATT) {
        const uint4 v = ldg_rlx128(&g_segcnt[4 * t]);
        const uint32_t e = epoch * 96;
        r = ((int)(v.x - e) >= 0) & ((int)(v.y - e) >= 0) & ((int)(v.z - e) >= 0) & ((int)(v.w - e) >= 0);
      } else if (ty == IT_BATT) {
        r = cnt(C_GATE, NGATE) & cnt(C_QKV + (t >> 1), 10) & cnt(C_QKV + (max(t - 1, 0) >> 1), 10);
      } else {
        r = ty <= IT_QKV || ty == IT_Q || cnt(C_OB + t, 8);
      }
      asm volatile("fence.acquire.gpu; fence.proxy.async.global;" ::: "memory");
      return r;
    };
    if (wid == W_SCH && lane == 0) {
      uint32_t pend = j0 < (uint32_t)NITEMS ? c_items.v[j0] : (uint32_t)IT_END;
      bool xleft = true;
      uint32_t nidx = 0, pidx = j0;
      GTA(1);
      if (j0 < 64) spin_until(c0, ADELAY);
      if (pend != 12345) GTA(2);
#pragma unroll 1
      for (uint32_t e = 0;; e++) {
        if (e) mbar_wait_long(sb + A_REQ, (e - 1) & 1);
        uint32_t item = NONE;
        int rdy = 0, spins = 0;
#pragma unroll 1
        while (true) {
          const bool fresh = pend == NONE;
          uint4 c;
          uint32_t pr = 0;
          bool gates = false;
          if (xleft) {
            c = ldg_rlx128(&g_queue[0]);
            pr = ldg_rlx32(&g_prog) - (epoch - 1) * (96 * NSEG);
            gates = cnt(C_GATE, NGATE);
          }
          auto need = [&]() { return (pend & 7) == IT_OUT && xleft ? (((pend >> 24) + 1) >> 1) - ((pend >> 17) & 127) : 1; };
          if (!fresh) rdy = ready(pend);
          if (xleft && (fresh || pend == IT_END || rdy < need())) {
            auto full = [](uint32_t v) { v = (v | (v >> 2)) & 0x30303030u; return __popc((v | (v >> 1)) & 0x10101010u); };
            const int t = full(c.x) + full(c.y) + full(c.z) + full(c.w);
            xleft = t < 15;
            if (xleft && gates && (int)pr >= 96 * (4 * t - 8 + (int)((XD >> 4 * t) & 15))) {
              const uint32_t j = (atomicAdd(&g_queue[t >> 2], 1u << (t & 3) * 8) >> (t & 3) * 8) & 255;
              if (j < 16) { item = mk_item(IT_XATT, t, j); rdy = 0; nidx = NITEMS + 132 + t * 16 + j; }
            }
          }
          if (item == NONE) {
            if (fresh) {
              pidx = atomicAdd(&g_queue[32], 1u);
              pend = pidx < (uint32_t)NITEMS ? c_items.v[pidx] : (uint32_t)IT_END;
              rdy = ready(pend);
            }
            if (pend == IT_END ? !xleft : rdy >= need()) { item = pend; pend = NONE; nidx = pidx; }
          }
          if (item != NONE) break;
          if (++spins > SPIN_MAX) { g_err = 10; item = IT_END; break; }
          __nanosleep(50);
        }
        if (e == 0) GTA(3);
        sts128(sb + A_MAIL, item, rdy, nidx, xleft ? PACE : 0);
        mbar_arrive(sb + A_RSP);
        if (item == IT_END) break;
        if ((item & 7) == IT_XATT) {
#pragma unroll 1
          for (spins = 0; !ready(item); __nanosleep(RSL))
            if (++spins > SPIN_MAX) { g_err = 11; break; }
          mbar_arrive(sb + A_RDY);
        }
      }
      if (atomicAdd(&g_queue[64], 1u) == gridDim.x - 1) { *(uint4*)g_queue = make_uint4(0, 0, 0, 0); g_queue[32] = 0; g_queue[64] = 0; g_epoch = epoch; }
      asm volatile("griddepcontrol.wait;" ::: "memory");
    } else if (wid == W_PRO) {
      uint32_t xph = 0, tl = 0;
      int pace = 0;
      auto arm = [&](uint32_t bytes) -> uint32_t {
        mbar_wait_u(sb + A_EMPTY + st * 8, ph ^ 1);
        if (PACE && bytes) { spin_until(tl, pace); tl = clk32(); }
        return sb + st * STG;
      };
#pragma unroll 1
      for (uint32_t e = 0;; e++) {
        mbar_wait_long(sb + A_RSP, e & 1);
        const uint4 mail = lds128(sb + A_MAIL);
        asm volatile("fence.proxy.async.global;" ::: "memory");
        const uint32_t item = __shfl_sync(~0u, mail.x, 0);
        pace = mail.w;
        const int ty = item & 7, t = (item >> 3) & 31, a = (item >> 8) & 255;
        arm(0);
        if (elect()) {
          sts32(sb + A_ITEM + st * 4, item);
        }
        if (ty == IT_OUT || ty == IT_INIT) {
          const bool out_ = ty == IT_OUT;
          const CUtensorMap *pa = out_ ? &tm.oA : &tm.obA, *pb = out_ ? &tm.wo : &tm.wob;
          int k = out_ ? ((item >> 16) & 255) * 6 : 0;
          const int k1 = out_ ? (item >> 24) * 6 : 20, kreq = max(k1 - KREQ, k);
          int kdep = out_ ? (((item >> 17) & 127) + __shfl_sync(~0u, mail.y, 0)) * 12 : 20;
#pragma unroll 1
          for (; k < k1; k++) {
            if (k >= kdep) {
              int n = 0;
#pragma unroll 1
              while (k >= (kdep = (((item >> 17) & 127) + __shfl_sync(~0u, ready(item), 0)) * 12)) {
                if (++n > SPIN_MAX) { g_err = 7; break; }
                __nanosleep(20);
              }
            }
            PTR((item & 255) == PT && lane == 0, 0, k & 63);
            const uint32_t d = arm(1), fb = sb + A_FULL + st * 8;
            PTR((item & 255) == PT && lane == 0, 1, k & 63);
            if (elect()) {
              mbar_expect(fb, 28672);
              tma_load2(d, pa, k * 32, t * 128, fb);
              tma_load3(d + 8192, pb, 0, k * 32, a * 5, fb);
              if (k == kreq) mbar_arrive(sb + A_REQ);
            }
            PTR((item & 255) == PT && lane == 0, 2, k & 63);
            advance();
          }
        } else if (ty == IT_QKV || ty == IT_XATT || ty == IT_Q) {
          const CUtensorMap* pb = ty == IT_QKV ? &tm.wqkv : &tm.wq;
          const int kreq = ty == IT_XATT ? 28 - KREQ : 20 - KREQ;
#pragma unroll 1
          for (int k = 0; k < 20; k++) {
            PTR((item & 255) == PT && lane == 0, 0, k & 63);
            const uint32_t d = arm(1), fb = sb + A_FULL + st * 8;
            PTR((item & 255) == PT && lane == 0, 1, k & 63);
            if (elect()) {
              mbar_expect(fb, 32768);
              tma_load2(d, &tm.xA, k * 32, t * 128, fb);
              tma_load3(d + 8192, pb, 0, k * 32, a * 6, fb);
              if (k == kreq) mbar_arrive(sb + A_REQ);
            }
            PTR((item & 255) == PT && lane == 0, 2, k & 63);
            advance();
          }
          if (ty == IT_XATT) {
            mbar_wait_long(sb + A_RDY, xph);
            xph ^= 1;
            asm volatile("fence.proxy.async.global;" ::: "memory");
#pragma unroll 1
            for (int k = 20; k < 28; k++) {
              PTR((item & 255) == PT && lane == 0, 0, k & 63);
              const uint32_t d = arm(1), fb = sb + A_FULL + st * 8;
              PTR((item & 255) == PT && lane == 0, 1, k & 63);
              if (elect()) {
                mbar_expect(fb, 30720);
                tma_load3(d, k < 24 ? &tm.k : &tm.v, 0, (4 * t + (k & 2)) * LK, (2 * a + (k & 1)) * 3, fb);
                if (k == kreq) mbar_arrive(sb + A_REQ);
              }
              PTR((item & 255) == PT && lane == 0, 2, k & 63);
              advance();
            }
          }
        } else if (ty == IT_BATT) {
#pragma unroll 1
          for (int k = 0, j = 0, c = 0; k < 12; k++) {
            PTR((item & 255) == PT && lane == 0, 0, k & 63);
            const uint32_t d = arm(1), fb = sb + A_FULL + st * 8;
            PTR((item & 255) == PT && lane == 0, 1, k & 63);
            if (elect()) {
              mbar_expect(fb, c ? 25600 : 20480);
              tma_load3(d, c ? &tm.qkvK : &tm.qkvQ, 0, t * 32 - (c ? 8 : 0), (j & 1) * 30 + (j >> 1) * 5 + c, fb);
              if (k == 6) mbar_arrive(sb + A_REQ);
            }
            PTR((item & 255) == PT && lane == 0, 2, k & 63);
            if (c == 20) { c = 0; j++; } else c += 10;
            advance();
          }
        } else {
          if (elect()) { mbar_arrive(sb + A_FULL + st * 8); mbar_arrive(sb + A_REQ); }
          advance();
        }
        if (item == IT_END) break;
        if ((0x6a >> ty) & 1) {
#pragma unroll 1
          for (int k = 0; k < 4; k++) {
            arm(0);
            if (elect()) mbar_arrive(sb + A_FULL + st * 8);
            advance();
          }
        }
      }
    } else if (lane == 0) {
      const uint32_t qb = sb + A_QBAR + (wid == W_AG1) * 64, qe = sb + A_QENT + (wid == W_AG1) * 128;
      for (uint32_t e = 0;; e++) {
        mbar_wait_long(qb + (e & 7) * 8, (e >> 3) & 1);
        const uint4 en = lds128(qe + (e & 7) * 16);
        const int op = en.x & 15, sg = (en.x >> 4) & 15, rel = (en.x >> 8) & 15, nb = (en.x >> 12) & 15;
        if (op == OP_END) break;
        const uint32_t src = sb + sg * STG;
        if (op == OP_OB) tma_store3(&tm.obS, src, 0, en.y, en.z);
        else if (op == OP_Q) asm volatile("cp.async.bulk.global.shared::cta.bulk_group [%0], [%1], 24576;" ::"l"(g_Ql + en.y * 1536), "r"(src) : "memory");
        else {
          const CUtensorMap* pm = op == OP_O ? &tm.oS : (op == OP_QKV ? &tm.qkvS : &tm.out);
#pragma unroll 1
          for (int i = 0; i < nb; i++) {
            if (op == OP_ADD) tma_red3(pm, src + i * 8192, 0, en.y, en.z + i); else tma_store3(pm, src + i * 8192, 0, en.y, en.z + i);
            if (SPLITW && i + 1 < nb) { bulk_commit(); bulk_wait_read0(); }
          }
        }
        bulk_commit();
        bulk_wait_read0();
        asm volatile("mbarrier.arrive.shared::cta.b64 _, [%0], %1;" ::"r"(sb + A_EMPTY + sg * 8), "r"(rel) : "memory");
        if (en.w) {
          bulk_wait0();
          asm volatile("red.relaxed.gpu.global.add.u32 [%0], %1;" ::"l"(&g_cnt[(en.w - 1) * 8]), "r"(1) : "memory");
        }
      }
      bulk_wait0();
      if (wid == W_AG1) GTA(7);
    }
  } else {
    asm volatile("setmaxnreg.inc.sync.aligned.u32 232;");
    const int g = wid >> 2, w = wid & 3;
    uint32_t qn = 0;
    auto wait_full = [&]() { mbar_wait_u(sb + A_FULL + st * 8, ph); };
    auto release = [&](uint32_t s_) { if (lane == 0) mbar_arrive(sb + A_EMPTY + s_ * 8); };
    auto take_pair = [&]() -> uint32_t {
      wait_full();
      const uint32_t s0 = st; advance();
      wait_full();
      const uint32_t s1 = st; advance();
      release(g ? s0 : s1);
      return g ? s1 : s0;
    };
    auto push = [&](uint32_t w0, uint32_t w1, uint32_t w2, uint32_t w3) {
      fence_async_smem();
      if (w == 0 && lane == 0) sts128(sb + A_QENT + g * 128 + (qn & 7) * 16, w0, w1, w2, w3);
      __syncwarp();
      if (lane == 0) mbar_arrive(sb + A_QBAR + g * 64 + (qn & 7) * 8);
      qn++;
    };
    const uint32_t stm = (16 * w + (lane & 7) + (lane & 8)) * 128, stx = lane & 7, sth = lane >> 4;
    auto stage_bf16 = [&](uint32_t dst, const float* d, int nks = 12) {
#pragma unroll
      for (int ks = 0; ks < nks; ks++)
        stsm4(dst + (ks >> 2) * 8192 + stm + (((2 * (ks & 3) + sth) ^ stx) << 4), pack2(d[8 * ks], d[8 * ks + 1]), pack2(d[8 * ks + 2], d[8 * ks + 3]),
              pack2(d[8 * ks + 4], d[8 * ks + 5]), pack2(d[8 * ks + 6], d[8 * ks + 7]));
    };
#pragma unroll 1
    while (true) {
      wait_full();
      const uint32_t item = lds32(sb + A_ITEM + st * 4);
      const int ty = item & 7, t = (item >> 3) & 31, a = (item >> 8) & 255;
      if (ty == IT_QKV || ty == IT_XATT || ty == IT_Q) {
        float acc[192] = {};
        uint32_t prev = 0;
#define XG(i) do {} while (0)
#pragma unroll 1
        for (int k = 0; k < 20; k++) {
          if (k) wait_full();
          PTR((item & 255) == PT && tid == 32, 3, k);
          if (LAG && k == (g ? 0 : LAG)) { if (g) bar_sync(7, 256); else bar_arrive(7, 256); }
          const uint32_t s_ = sb + st * STG;
          const Desc da = mk_desc(s_, 16, 512, 2), db = mk_desc(s_ + 8192 + g * 12288, 4096, 1024, 1);
          wg_fence();
          wgmma_ss192t(acc, da, db, k);
          wgmma_ss192t(acc + 96, da + 256, db, k);
          wgmma_ss192t(acc, da + 2, db + 128, 1);
          wgmma_ss192t(acc + 96, da + 258, db + 128, 1);
          wg_commit();
          if (k) { wg_wait1(); release(prev); }
          prev = st; advance();
        }
        uint32_t kst[2];
        if (KEARLY && ty == IT_XATT) { kst[0] = take_pair(); kst[1] = take_pair(); }
        wg_wait0();
        fence_regs<192>(acc);
        release(prev);
        XG(0);
        if (ty == IT_QKV) {
#pragma unroll
          for (int q = 0; q < 2; q++) {
            const uint32_t m = take_pair();
            stage_bf16(sb + m * STG, acc + q * 96);
            push(OP_QKV | (m << 4) | (4 << 8) | (3 << 12), t * 128 + q * 64, a * 6 + g * 3, q ? C_QKV + t + 1 : 0);
          }
        } else if (ty == IT_Q) {
#pragma unroll
          for (int q = 0; q < 2; q++) {
            const uint32_t m = take_pair();
#pragma unroll
            for (int ks = 0; ks < 12; ks++) {
              const float* d = acc + q * 96 + ks * 8;
              sts128(sb + m * STG + (w * 12 + ks) * 512 + lane * 16, pack2(d[0], d[1]), pack2(d[2], d[3]), pack2(d[4], d[5]), pack2(d[6], d[7]));
            }
            push(OP_Q | (m << 4) | (4 << 8), (2 * a + g) * 2 + q, 0, q ? C_O + 240 + a + 1 : 0);
          }
        } else {
          uint32_t qf[24][4];
          float sc[2][40], gt[4];
#pragma unroll
          for (int q = 0; q < 2; q++) {
#pragma unroll
            for (int ks = 23; ks >= 0; ks--)
#pragma unroll
              for (int j = 0; j < 4; j++)
                if ((ks >= 12 && ks < 12 + CVTS) == (q == 1))
                  asm volatile("cvt.rn.bf16x2.f32 %0, %1, %2;" : "=r"(qf[ks][j]) : "f"(acc[8 * ks + 2 * j + 1]), "f"(acc[8 * ks + 2 * j]));
            if (!KEARLY) kst[q] = take_pair();
            if (q == 0) XG(1);
            if (q == 0 && XPP && g == 1) bar_sync(6, 256);
            if (q == 1) {
              const float* gp = g_gate + t * 128 + 16 * w + (lane >> 2);
              gt[0] = ldg_cg(gp); gt[1] = ldg_cg(gp + 8); gt[2] = ldg_cg(gp + 64); gt[3] = ldg_cg(gp + 72);
            }
#pragma unroll
            for (int i = 0; i < 40; i++) sc[q][i] = 0.f;
            const Desc db = mk_desc(sb + kst[q] * STG, 16, 1024, 1);
            wg_fence();
#pragma unroll
            for (int ks = 0; ks < 12; ks++) {
              if (XPP && g == 0 && q * 12 + ks == XPP) bar_arrive(6, 256);
              wgmma_rs80(sc[q], qf[q * 12 + ks], db + (((ks >> 2) * 10240 + (ks & 3) * 32) >> 4), ks);
            }
            wg_commit();
          }
          uint32_t pf[2][5][4];
          const AttMask am(tid, sb);
          wg_wait1();
          fence_regs<40>(sc[0]);
          XG(2);
          release(kst[0]);
          sched_fence(sb);
          att_softmax(am, sc[0], pf[0], gt[0], gt[1]);
          XG(3);
          float o[96] = {};
          auto pv = [&](int q, uint32_t m) {
            const Desc db = mk_desc(sb + m * STG, 10240, 1024, 1);
            wg_fence();
#pragma unroll
            for (int ks = 0; ks < 5; ks++) wgmma_rs192t(o, pf[q][ks], db + ks * 128, ks);
            wg_commit();
          };
          PTR((item & 255) == PT && tid == 32, 3, 24);
          const uint32_t m0 = take_pair();
          PTR((item & 255) == PT && tid == 32, 3, 25);
          pv(0, m0);
          wg_wait1();
          fence_regs<40>(sc[1]);
          release(kst[1]);
          att_softmax(am, sc[1], pf[1], gt[2], gt[3]);
          PTR((item & 255) == PT && tid == 32, 3, 26);
          const uint32_t m1 = take_pair();
          PTR((item & 255) == PT && tid == 32, 3, 27);
          wg_wait0();
          fence_regs<96>(o);
          XG(4);
#pragma unroll
          for (int i = 0; i < 48; i++) asm volatile("cvt.rn.bf16x2.f32 %0, %1, %2;" : "=r"(qf[i >> 2][i & 3]) : "f"(o[2 * i + 1]), "f"(o[2 * i]));
          pv(1, m1);
          bar_sync(1 + g, 128);
#pragma unroll
          for (int ks = 0; ks < 12; ks++)
            stsm4(sb + m0 * STG + (ks >> 2) * 8192 + stm + (((2 * (ks & 3) + sth) ^ stx) << 4), qf[ks][0], qf[ks][1], qf[ks][2], qf[ks][3]);
          push(OP_O | (m0 << 4) | (4 << 8) | (3 << 12), t * 128, a * 6 + g * 3, 0);
          XG(5);
          wg_wait0();
          fence_regs<96>(o);
          XG(6);
          bar_sync(1 + g, 128);
          stage_bf16(sb + m1 * STG, o);
          push(OP_O | (m1 << 4) | (4 << 8) | (3 << 12), t * 128 + 64, a * 6 + g * 3, C_O + t * 16 + a + 1);
          XG(7);
        }
      } else if (ty == IT_OUT || ty == IT_INIT) {
        float acc[160] = {};
        const int hb = (item >> 16) & 255, nh = (item >> 24) - hb, nk = ty == IT_OUT ? nh * 6 : 20, jh = a & 1;
        const uint32_t ln = pin(lane), ao = (g * 64 + 16 * w + (ln & 15)) * 64 + (((ln >> 4) ^ ((ln >> 1) & 3)) << 4);
        if (PP && g == 1) bar_arrive(4, 256);
#pragma unroll 1
        for (int k = 0; k < nk; k += 2) {
          uint32_t af[4][4], sg[2];
#pragma unroll
          for (int e = 0; e < 2; e++) {
            if (k + e) wait_full();
            sg[e] = st;
            ldsm4(af[2 * e], sb + st * STG + ao);
            ldsm4(af[2 * e + 1], sb + st * STG + (ao ^ 32));
            advance();
          }
          if (PP) bar_sync(4 + g, 256);
          wg_fence();
#pragma unroll
          for (int e = 0; e < 4; e++) {
            const Desc db = mk_desc(sb + sg[e >> 1] * STG + 8192 + (e & 1) * 2048, 4096, 1024, 1);
            if (PP == 2 && e == 3 && (g == 0 || k + 2 < nk)) bar_arrive(5 - g, 256);
            wgmma_rs192t(acc, af[e], db, 1);
            if (PP == 3 && e == 3 && (g == 0 || k + 2 < nk)) bar_arrive(5 - g, 256);
            wgmma_rs128t(acc + 96, af[e], db + 768, 1);
          }
          wg_commit();
          if (PP == 1 && (g == 0 || k + 2 < nk)) bar_arrive(5 - g, 256);
          wg_wait0();
          release(sg[0]); release(sg[1]);
        }
        fence_regs<160>(acc);
        const uint32_t row = t * 128 + g * 64;
#pragma unroll
        for (int q = 0; q < 2; q++) {
          const uint32_t m = take_pair();
          stage_bf16(sb + m * STG, acc + q * 96, q ? 8 : 12);
          push((ty == IT_OUT || t == 15 ? OP_ADD : OP_SET) | (m << 4) | (4 << 8) | ((3 - q) << 12), row, jh * 5 + q * 3, q && ty == IT_INIT ? C_ACC + t + 1 : 0);
        }
      } else if (ty == IT_BATT) {
        const int q4 = lane & 3, r8 = lane >> 2;
        const bool lo = q4 < 2, m0 = 2 * q4 > r8, m1 = 2 * q4 + 1 > r8;
        const uint32_t mk = (m0 ? 0xffffu : 0u) | (m1 ? 0xffff0000u : 0u);
        uint32_t aq[5], ak[5];
#pragma unroll
        for (int i = 0; i < 5; i++) {
          const int c = 5 * wid + i;
          aq[i] = (c >> 3) * 4096 + lane * 128 + (((c ^ lane) & 7) << 4);
          ak[i] = aq[i] + (c >> 3) * 1024;
        }
        const int c4 = 5 * wid + (lane >> 3);
        const uint32_t ak4 = (c4 >> 3) * 5120 + (32 + (lane & 7)) * 128 + (((c4 ^ lane) & 7) << 4), ak5 = ak[4] + (32 + (lane & 7) - lane) * 128;
#pragma unroll 1
        for (int j = 0; j < 4; j++) {
          float gt[4];
#pragma unroll
          for (int i = 0; i < 4; i++) gt[i] = ldg_cg(g_gate + S_TOK + t * 64 + (j & 1) + 2 * r8 + i * 16);
          if (j) wait_full();
          PTR((item & 255) == PT && tid == 32, 3, j * 3);
          const uint32_t sq = st; advance();
          uint32_t qf[5][4], kf[7][4], vf[7][4], pa[4], pb[4];
          float sc[4][3][4] = {}, o[4][3][4] = {}, l[4][4], xa[4], xb[4];
#pragma unroll
          for (int i = 0; i < 5; i++) ldsm4(qf[i], sb + sq * STG + aq[i]);
          wait_full();
          PTR((item & 255) == PT && tid == 32, 3, j * 3 + 1);
          const uint32_t sk = st; advance();
#pragma unroll
          for (int i = 0; i < 7; i++) ldsm4(kf[i], sb + sk * STG + (i < 5 ? ak[i] : (i == 5 ? ak4 : ak5)));
          auto frag = [](uint32_t (*f)[4], int c, int n) { return n < 4 ? f[c][n] : (c < 4 ? f[5][c] : f[6][0]); };
#pragma unroll
          for (int u = 0; u < 4; u++) {
            const int c = (u >> 1) * 3, b = u & 1;
            const uint32_t x[4] = {qf[c][2 * b], qf[c][2 * b + 1], qf[c + 1][2 * b], qf[c + 1][2 * b + 1]};
#pragma unroll
            for (int n = 0; n < 3; n++) mma16816(sc[u][n], x, frag(kf, c, 2 * b + n), frag(kf, c + 1, 2 * b + n));
          }
#pragma unroll
          for (int u = 0; u < 4; u++) {
            const int b = u & 1;
            const uint32_t x0 = lo == (u < 2) ? qf[2][2 * b] : 0u, x1 = lo == (u < 2) ? qf[2][2 * b + 1] : 0u;
#pragma unroll
            for (int n = 0; n < 3; n++) mma1688(sc[u][n], x0, x1, frag(kf, 2, 2 * b + n));
          }
          wait_full();
          PTR((item & 255) == PT && tid == 32, 3, j * 3 + 2);
          const uint32_t sv = st; advance();
#pragma unroll
          for (int i = 0; i < 7; i++) ldsm4t(vf[i], sb + sv * STG + (i < 5 ? ak[i] : (i == 5 ? ak4 : ak5)));
          if (t == 0) sc[0][0][0] = sc[0][0][1] = sc[2][0][0] = sc[2][0][1] = -INFINITY;
          constexpr float SCL = 0.22360679774997896f * 1.4426950408889634f;
#pragma unroll
          for (int u = 0; u < 4; u++) {
            l[u][0] = m0 ? sc[u][0][0] : sc[u][1][0]; l[u][1] = m1 ? sc[u][0][1] : sc[u][1][1];
            l[u][2] = m0 ? sc[u][1][2] : sc[u][2][2]; l[u][3] = m1 ? sc[u][1][3] : sc[u][2][3];
            xa[u] = fmaxf(l[u][0], l[u][1]); xb[u] = fmaxf(l[u][2], l[u][3]);
          }
          release(sk);
#pragma unroll
          for (int d = 1; d < 4; d *= 2)
#pragma unroll
            for (int u = 0; u < 4; u++) { xa[u] = fmaxf(xa[u], __shfl_xor_sync(~0u, xa[u], d)); xb[u] = fmaxf(xb[u], __shfl_xor_sync(~0u, xb[u], d)); }
#pragma unroll
          for (int u = 0; u < 4; u++) {
            xa[u] *= SCL; xb[u] *= SCL;
#pragma unroll
            for (int i = 0; i < 4; i++) l[u][i] = ex2(fmaf(l[u][i], SCL, -(i < 2 ? xa[u] : xb[u])));
            xa[u] = l[u][0] + l[u][1]; xb[u] = l[u][2] + l[u][3];
          }
#pragma unroll
          for (int d = 1; d < 4; d *= 2)
#pragma unroll
            for (int u = 0; u < 4; u++) { xa[u] += __shfl_xor_sync(~0u, xa[u], d); xb[u] += __shfl_xor_sync(~0u, xb[u], d); }
#pragma unroll
          for (int u = 0; u < 4; u++) {
            const int c = (u >> 1) * 3, b = u & 1;
            xa[u] = gt[2 * b] * rcp(xa[u]); xb[u] = gt[2 * b + 1] * rcp(xb[u]);
            pa[u] = pack2(l[u][0] * xa[u], l[u][1] * xa[u]); pb[u] = pack2(l[u][2] * xb[u], l[u][3] * xb[u]);
            const uint32_t pf[4] = {pa[u] & mk, 0u, pa[u] & ~mk, pb[u] & mk};
#pragma unroll
            for (int n = 0; n < 3; n++) mma16816(o[u][n], pf, vf[n < 2 ? c + n : 2][2 * b], vf[n < 2 ? c + n : 2][2 * b + 1]);
          }
#pragma unroll
          for (int u = 0; u < 4; u++)
#pragma unroll
            for (int n = 0; n < 3; n++) mma1688(o[u][n], 0u, pb[u] & ~mk, frag(vf, n < 2 ? (u >> 1) * 3 + n : 2, 2 * (u & 1) + 2));
          release(sv);
#pragma unroll
          for (int i = 0; i < 5; i++) {
            float y[8];
#pragma unroll
            for (int e = 0; e < 8; e++) y[e] = i == 2 ? (lo ? o[e >> 2][2][e & 3] : o[2 + (e >> 2)][2][e & 3]) : o[(i > 2) * 2 + (e >> 2)][i % 3][e & 3];
            stsm4(sb + sq * STG + aq[i], pack2(y[0], y[1]), pack2(y[2], y[3]), pack2(y[4], y[5]), pack2(y[6], y[7]));
          }
          PTR((item & 255) == PT && tid == 32, 3, 12 + j * 2);
          fence_async_smem();
          bar_sync(3, 256);
          PTR((item & 255) == PT && tid == 32, 3, 13 + j * 2);
          if (g == (j & 1)) push(OP_OB | (sq << 4) | (8 << 8), t * 32, (j & 1) * 10 + (j >> 1) * 5, C_OB + (t >> 1) + 1);
        }
      } else {
        release(st);
        push(OP_END, 0, 0, 0);
        break;
      }
    }
  }
}

typedef CUresult (*EncFn)(CUtensorMap*, CUtensorMapDataType, cuuint32_t, void*, const cuuint64_t*, const cuuint64_t*, const cuuint32_t*,
                          const cuuint32_t*, CUtensorMapInterleave, CUtensorMapSwizzle, CUtensorMapL2promotion, CUtensorMapFloatOOBfill);

#define PROMO CU_TENSOR_MAP_L2_PROMOTION_L2_128B
void make_map(EncFn enc, CUtensorMap* tm, const void* base, int rank, const cuuint64_t* dims, const cuuint64_t* strides, const cuuint32_t* box,
              CUtensorMapSwizzle sw = CU_TENSOR_MAP_SWIZZLE_128B, CUtensorMapDataType dt = CU_TENSOR_MAP_DATA_TYPE_BFLOAT16) {
  const cuuint32_t es[5] = {1, 1, 1, 1, 1};
  enc(tm, dt, rank, const_cast<void*>(base), dims, strides, box, es, CU_TENSOR_MAP_INTERLEAVE_NONE, sw, PROMO,
      CU_TENSOR_MAP_FLOAT_OOB_FILL_NONE);
}
void map_blk(EncFn enc, CUtensorMap* tm, const void* base, int rows, int cols, int brows, int bblk) {
  const cuuint64_t d[3] = {64, (cuuint64_t)rows, (cuuint64_t)cols / 64}, st[2] = {(cuuint64_t)cols * 2, 128};
  const cuuint32_t b[3] = {64, (cuuint32_t)brows, (cuuint32_t)bblk};
  make_map(enc, tm, base, 3, d, st, b);
}
void map_2d(EncFn enc, CUtensorMap* tm, const void* base, int rows, int cols, int brows, int bcols, CUtensorMapSwizzle sw) {
  const cuuint64_t d[2] = {(cuuint64_t)cols, (cuuint64_t)rows}, st[1] = {(cuuint64_t)cols * 2};
  const cuuint32_t b[2] = {(cuuint32_t)bcols, (cuuint32_t)brows};
  make_map(enc, tm, base, 2, d, st, b, sw);
}

}

extern "C" void kernel_launch(void* const* d_in, const int* in_sizes, int n_in, void* d_out, int out_size) {
  const bf16* x = (const bf16*)d_in[0];
  const bf16* mem0 = (const bf16*)d_in[1];
  const bf16* Wq = (const bf16*)d_in[2];
  const bf16* Wk = (const bf16*)d_in[3];
  const bf16* Wv = (const bf16*)d_in[4];
  const bf16* Wo = (const bf16*)d_in[5];
  const bf16* wqkv = (const bf16*)d_in[8];
  const bf16* wob = (const bf16*)d_in[9];
  const bf16* gate_w = (const bf16*)d_in[10];
  static EncFn enc = nullptr;
  static void *pR = nullptr, *pK = nullptr, *pV = nullptr, *pO = nullptr, *pQ = nullptr, *pB = nullptr;
  if (!enc) {
    void* fn = nullptr;
    cudaDriverEntryPointQueryResult qr;
    cudaGetDriverEntryPoint("cuTensorMapEncodeTiled", &fn, cudaEnableDefault, &qr);
    enc = (EncFn)fn;
    cudaGetSymbolAddress(&pR, g_red);
    cudaGetSymbolAddress(&pK, g_K);
    cudaGetSymbolAddress(&pV, g_V);
    cudaGetSymbolAddress(&pO, g_O);
    cudaGetSymbolAddress(&pQ, g_qkv);
    cudaGetSymbolAddress(&pB, g_Ob);
    cudaFuncSetAttribute(rec_kernel, cudaFuncAttributeMaxDynamicSharedMemorySize, R_SMEM_ALLOC);
    cudaFuncSetAttribute(aux_kernel, cudaFuncAttributeMaxDynamicSharedMemorySize, A_SMEM);
  }
  CUtensorMap tmX, tmK, tmV, tmWq, tmWq2, tmWk, tmWv, tmWo, tmOut;
  map_2d(enc, &tmOut, d_out, S_TOK, DM, 64, 32, CU_TENSOR_MAP_SWIZZLE_64B);
  map_2d(enc, &tmWq, Wq, DM, HD, 144, 64, CU_TENSOR_MAP_SWIZZLE_128B);
  map_2d(enc, &tmWq2, Wq, DM, HD, 32, 64, CU_TENSOR_MAP_SWIZZLE_128B);
  map_2d(enc, &tmWk, Wk, DM, HD, 128, 64, CU_TENSOR_MAP_SWIZZLE_128B);
  map_2d(enc, &tmWv, Wv, DM, HD, 128, 64, CU_TENSOR_MAP_SWIZZLE_128B);
  {
    const cuuint64_t d[3] = {32, HD, 20}, st[2] = {DM * 2, 64};
    const cuuint32_t b[3] = {32, 64, 7};
    make_map(enc, &tmWo, Wo, 3, d, st, b, CU_TENSOR_MAP_SWIZZLE_64B);
  }
  map_blk(enc, &tmX, x, S_TOK, DM, 32, 10);
  map_2d(enc, &tmK, pK, NSEG * LK, HD, LK, 64, CU_TENSOR_MAP_SWIZZLE_128B);
  map_2d(enc, &tmV, pV, NSEG * LK, HD, LK, 64, CU_TENSOR_MAP_SWIZZLE_128B);
  AuxMaps am;
  map_2d(enc, &am.xA, x, S_TOK, DM, 128, 32, CU_TENSOR_MAP_SWIZZLE_64B);
  map_blk(enc, &am.wq, Wq, DM, HD, 32, 6);
  map_blk(enc, &am.wqkv, wqkv, DM, 3 * DM, 32, 6);
  map_blk(enc, &am.wo, Wo, HD, DM, 32, 5);
  map_blk(enc, &am.wob, wob, DM, DM, 32, 5);
  map_blk(enc, &am.k, pK, NSEG * LK, HD, 80, 3);
  map_blk(enc, &am.v, pV, NSEG * LK, HD, 80, 3);
  map_2d(enc, &am.oA, pO, S_TOK, HD, 128, 32, CU_TENSOR_MAP_SWIZZLE_64B);
  map_blk(enc, &am.oS, pO, S_TOK, HD, 64, 1);
  map_2d(enc, &am.obA, pB, S_TOK, DM, 128, 32, CU_TENSOR_MAP_SWIZZLE_64B);
  map_blk(enc, &am.obS, pB, S_TOK / 2, 2 * DM, 32, 5);
  map_blk(enc, &am.qkvS, pQ, S_TOK, 3 * DM, 64, 1);
  map_blk(enc, &am.qkvQ, pQ, S_TOK / 2, 6 * DM, 32, 5);
  map_blk(enc, &am.qkvK, pQ, S_TOK / 2, 6 * DM, 40, 5);
  map_blk(enc, &am.out, d_out, S_TOK, DM, 64, 1);
  rec_kernel<<<96, 256, R_SMEM_ALLOC, cudaStreamPerThread>>>(tmX, tmK, tmV, tmWq, tmWq2, tmWk, tmWv, tmWo, tmOut, mem0, Wq, Wk, Wv, Wo, x, gate_w, (bf16*)d_out,
                                                               (unsigned char*)(((uintptr_t)pR + 0x1fffff) & ~(uintptr_t)0x1fffff));
  cudaLaunchConfig_t cfg = {};
  cfg.gridDim = dim3(AUX_GRID); cfg.blockDim = dim3(384); cfg.dynamicSmemBytes = A_SMEM; cfg.stream = cudaStreamPerThread;
  cudaLaunchAttribute at[1];
  at[0].id = cudaLaunchAttributeProgrammaticStreamSerialization;
  at[0].val.programmaticStreamSerializationAllowed = 1;
  cfg.attrs = at;
  cfg.numAttrs = 1;
  cudaLaunchKernelEx(&cfg, aux_kernel, am);
}
```

```cpp
#include <cuda_runtime.h>
#include <cuda_bf16.h>
#include <cuda.h>
#include <stdint.h>
#include <type_traits>

typedef __nv_bfloat16 bf16;

namespace {

constexpr int S_TOK = 2048, DM = 640, NH = 32, DH = 192, HD = NH * DH, SEG = 32, NSEG = 64, MT = 8, LK = 40;
constexpr int SPIN_MAX = 1 << 20, NGATE = 96;

__device__ __align__(4096) unsigned char g_red[(2 << 20) + (640 << 10)];
__host__ __device__ constexpr uint32_t rb_q(int q) { return (q < 5 ? q : q - 5) * 131072 + (uint32_t)((0x3122120330ull >> 4 * q) & 15) * 2048; }
__host__ __device__ constexpr uint32_t rb_j(int j) { return (j & 1) * 256 + (j & 2) * 512 + (j & 12) * 2048; }
__host__ __device__ constexpr uint32_t rb_b(int b) { return (b & 1) * 128 + (b & 2) * 256; }
__device__ unsigned long long g_rec[96];
__device__ uint32_t g_epoch;
__device__ uint32_t g_err;
__device__ __align__(16) uint32_t g_segcnt[NSEG];
__device__ __align__(1024) bf16 g_K[NSEG * LK * HD];
__device__ __align__(1024) bf16 g_V[NSEG * LK * HD];
__device__ __align__(1024) bf16 g_O[S_TOK * HD];
__device__ __align__(1024) uint4 g_Ql[NH * 2 * 4 * 12 * 32];
__device__ __align__(1024) bf16 g_qkv[S_TOK * 3 * DM];
__device__ __align__(1024) bf16 g_Ob[S_TOK * DM];
__device__ float g_gate[2 * S_TOK];
__device__ uint32_t g_cnt[512 * 8];
constexpr int C_GATE = 0, C_QKV = 16, C_OB = 32, C_ACC = 48, C_O = 80;
__device__ __align__(128) uint32_t g_queue[3 * 32];
__device__ uint32_t g_prog;
#define GTR(i) do {} while (0)
#define GTA(i) do {} while (0)
#define PTR(c, r, k) do {} while (0)

__device__ __forceinline__ uint32_t smem_u32(const void* p) { return (uint32_t)__cvta_generic_to_shared(p); }
__device__ __forceinline__ uint32_t clk32() { uint32_t t; asm volatile("mov.u32 %0, %%clock;" : "=r"(t)::"memory"); return t; }
__device__ __forceinline__ uint32_t mapa(uint32_t a, uint32_t r) { uint32_t o; asm("mapa.shared::cluster.u32 %0, %1, %2;" : "=r"(o) : "r"(a), "r"(r)); return o; }
__device__ __forceinline__ void mbar_init(uint32_t b, uint32_t c) { asm volatile("mbarrier.init.shared::cta.b64 [%0], %1;" ::"r"(b), "r"(c) : "memory"); }
__device__ __forceinline__ void mbar_expect(uint32_t b, uint32_t bytes) { asm volatile("mbarrier.arrive.expect_tx.shared::cta.b64 _, [%0], %1;" ::"r"(b), "r"(bytes) : "memory"); }
__device__ __forceinline__ void mbar_arrive(uint32_t b) { asm volatile("mbarrier.arrive.shared::cta.b64 _, [%0];" ::"r"(b) : "memory"); }
__device__ __forceinline__ bool mbar_try(uint32_t b, uint32_t par) {
  uint32_t p;
  asm volatile("{.reg .pred p; mbarrier.try_wait.parity.shared::cta.b64 p, [%1], %2; selp.u32 %0,1,0,p;}" : "=r"(p) : "r"(b), "r"(par) : "memory");
  return p;
}
__device__ __forceinline__ bool mbar_test(uint32_t b, uint32_t par) {
  uint32_t p;
  asm volatile("{.reg .pred p; mbarrier.test_wait.parity.shared::cta.b64 p, [%1], %2; selp.u32 %0,1,0,p;}" : "=r"(p) : "r"(b), "r"(par) : "memory");
  return p;
}
__device__ __forceinline__ bool mbar_try_cl(uint32_t b, uint32_t par) {
  uint32_t p;
  asm volatile("{.reg .pred p; mbarrier.try_wait.parity.acquire.cluster.shared::cta.b64 p, [%1], %2; selp.u32 %0,1,0,p;}" : "=r"(p) : "r"(b), "r"(par) : "memory");
  return p;
}
__device__ __forceinline__ void mbar_wait(uint32_t b, uint32_t par) {
  int n = 0;
#pragma unroll 1
  while (!mbar_try(b, par)) { if (++n > SPIN_MAX) { g_err = 1; break; } }
}
__device__ __forceinline__ void mbar_wait_cl(uint32_t b, uint32_t par) {
  int n = 0;
#pragma unroll 1
  while (!mbar_try_cl(b, par)) { if (++n > SPIN_MAX) { g_err = 2; break; } }
}
__device__ __forceinline__ void cluster_sync() { asm volatile("barrier.cluster.arrive.release.aligned; barrier.cluster.wait.acquire.aligned;" ::: "memory"); }
__device__ __forceinline__ void bar_sync(int id, int n) { asm volatile("bar.sync %0, %1;" ::"r"(id), "r"(n) : "memory"); }
__device__ __forceinline__ void bar_arrive(int id, int n) { asm volatile("bar.arrive %0, %1;" ::"r"(id), "r"(n) : "memory"); }
__device__ __forceinline__ void fence_async_smem() { asm volatile("fence.proxy.async.shared::cta;" ::: "memory"); }
__device__ __forceinline__ void ldsm4(uint32_t* r, uint32_t a) {
  asm volatile("ldmatrix.sync.aligned.m8n8.x4.shared.b16 {%0,%1,%2,%3}, [%4];" : "=r"(r[0]), "=r"(r[1]), "=r"(r[2]), "=r"(r[3]) : "r"(a) : "memory");
}
__device__ __forceinline__ void ldsm4t(uint32_t* r, uint32_t a) {
  asm volatile("ldmatrix.sync.aligned.m8n8.x4.trans.shared.b16 {%0,%1,%2,%3}, [%4];" : "=r"(r[0]), "=r"(r[1]), "=r"(r[2]), "=r"(r[3]) : "r"(a) : "memory");
}
__device__ __forceinline__ void ldsm2t(uint32_t* r, uint32_t a) {
  asm volatile("ldmatrix.sync.aligned.m8n8.x2.trans.shared.b16 {%0,%1}, [%2];" : "=r"(r[0]), "=r"(r[1]) : "r"(a) : "memory");
}
__device__ __forceinline__ void stsm4t(uint32_t a, uint32_t r0, uint32_t r1, uint32_t r2, uint32_t r3) {
  asm volatile("stmatrix.sync.aligned.m8n8.x4.trans.shared.b16 [%0], {%1,%2,%3,%4};" ::"r"(a), "r"(r0), "r"(r1), "r"(r2), "r"(r3) : "memory");
}
__device__ __forceinline__ void stsm2t(uint32_t a, uint32_t r0, uint32_t r1) {
  asm volatile("stmatrix.sync.aligned.m8n8.x2.trans.shared.b16 [%0], {%1,%2};" ::"r"(a), "r"(r0), "r"(r1) : "memory");
}
__device__ __forceinline__ uint32_t movmat(uint32_t a) { uint32_t d; asm volatile("movmatrix.sync.aligned.m8n8.trans.b16 %0, %1;" : "=r"(d) : "r"(a)); return d; }
__device__ __forceinline__ void mma16816(float* d, const uint32_t* a, uint32_t b0, uint32_t b1) {
  asm volatile("mma.sync.aligned.m16n8k16.row.col.f32.bf16.bf16.f32 {%0,%1,%2,%3}, {%4,%5,%6,%7}, {%8,%9}, {%0,%1,%2,%3};"
               : "+f"(d[0]), "+f"(d[1]), "+f"(d[2]), "+f"(d[3]) : "r"(a[0]), "r"(a[1]), "r"(a[2]), "r"(a[3]), "r"(b0), "r"(b1));
}
__device__ __forceinline__ void mma1688(float* d, uint32_t a0, uint32_t a1, uint32_t b0) {
  asm volatile("mma.sync.aligned.m16n8k8.row.col.f32.bf16.bf16.f32 {%0,%1,%2,%3}, {%4,%5}, {%6}, {%0,%1,%2,%3};"
               : "+f"(d[0]), "+f"(d[1]), "+f"(d[2]), "+f"(d[3]) : "r"(a0), "r"(a1), "r"(b0));
}
__device__ __forceinline__ uint32_t pack2(float lo, float hi) { uint32_t r; asm("cvt.rn.bf16x2.f32 %0, %1, %2;" : "=r"(r) : "f"(hi), "f"(lo)); return r; }
__device__ __forceinline__ float bf_lo(uint32_t w) { return __uint_as_float(w << 16); }
__device__ __forceinline__ float bf_hi(uint32_t w) { return __uint_as_float(w & 0xffff0000u); }
__device__ __forceinline__ float ex2(float x) { float y; asm("ex2.approx.ftz.f32 %0, %1;" : "=f"(y) : "f"(x)); return y; }
__device__ __forceinline__ void sts128(uint32_t a, uint32_t x, uint32_t y, uint32_t z, uint32_t w) { asm volatile("st.shared.v4.b32 [%0], {%1,%2,%3,%4};" ::"r"(a), "r"(x), "r"(y), "r"(z), "r"(w) : "memory"); }
__device__ __forceinline__ void sts128f(uint32_t a, float x, float y, float z, float w) { asm volatile("st.shared.v4.f32 [%0], {%1,%2,%3,%4};" ::"r"(a), "f"(x), "f"(y), "f"(z), "f"(w) : "memory"); }
__device__ __forceinline__ void sts64f(uint32_t a, float x, float y) { asm volatile("st.shared.v2.f32 [%0], {%1,%2};" ::"r"(a), "f"(x), "f"(y) : "memory"); }
__device__ __forceinline__ void sts32(uint32_t a, uint32_t x) { asm volatile("st.shared.b32 [%0], %1;" ::"r"(a), "r"(x) : "memory"); }
__device__ __forceinline__ void smax32(uint32_t a, uint32_t x) { asm volatile("red.shared.max.u32 [%0], %1;" ::"r"(a), "r"(x) : "memory"); }
__device__ __forceinline__ uint32_t lds32(uint32_t a) { uint32_t v; asm volatile("ld.shared.b32 %0, [%1];" : "=r"(v) : "r"(a) : "memory"); return v; }
__device__ __forceinline__ float4 lds128f(uint32_t a) { float4 v; asm volatile("ld.shared.v4.f32 {%0,%1,%2,%3}, [%4];" : "=f"(v.x), "=f"(v.y), "=f"(v.z), "=f"(v.w) : "r"(a) : "memory"); return v; }
__device__ __forceinline__ uint4 lds128(uint32_t a) { uint4 v; asm volatile("ld.shared.v4.b32 {%0,%1,%2,%3}, [%4];" : "=r"(v.x), "=r"(v.y), "=r"(v.z), "=r"(v.w) : "r"(a) : "memory"); return v; }
__device__ __forceinline__ float2 lds64f(uint32_t a) { float2 v; asm volatile("ld.shared.v2.f32 {%0,%1}, [%2];" : "=f"(v.x), "=f"(v.y) : "r"(a) : "memory"); return v; }
__device__ __forceinline__ void st_async2(uint32_t a, uint32_t x, uint32_t y, uint32_t bar) {
  asm volatile("st.async.weak.shared::cluster.mbarrier::complete_tx::bytes.v2.b32 [%0], {%1,%2}, [%3];" ::"r"(a), "r"(x), "r"(y), "r"(bar) : "memory");
}
__device__ __forceinline__ void st_async4(uint32_t a, uint32_t x, uint32_t y, uint32_t z, uint32_t w, uint32_t bar) {
  asm volatile("st.async.weak.shared::cluster.mbarrier::complete_tx::bytes.v4.b32 [%0], {%1,%2,%3,%4}, [%5];" ::"r"(a), "r"(x), "r"(y), "r"(z), "r"(w), "r"(bar) : "memory");
}
__device__ __forceinline__ void sts64(uint32_t a, uint32_t x, uint32_t y) { asm volatile("st.shared.v2.b32 [%0], {%1,%2};" ::"r"(a), "r"(x), "r"(y) : "memory"); }
__device__ __forceinline__ bool bar_red_or(int id, int n, bool q) {
  uint32_t r;
  asm volatile("{.reg .pred p, q; setp.ne.u32 q, %3, 0; barrier.cta.red.or.aligned.pred p, %1, %2, q; selp.u32 %0,1,0,p;}" : "=r"(r) : "r"(id), "r"(n), "r"((uint32_t)q) : "memory");
  return r;
}
__device__ __forceinline__ float rcp(float x) { float y; asm("rcp.approx.ftz.f32 %0, %1;" : "=f"(y) : "f"(x)); return y; }
__device__ __forceinline__ uint32_t hadd2(uint32_t a, uint32_t b) { uint32_t r; asm("add.rn.bf16x2 %0, %1, %2;" : "=r"(r) : "r"(a), "r"(b)); return r; }
__device__ __forceinline__ uint32_t pin(uint32_t v) { asm volatile("" : "+r"(v)); return v; }
template <int ID> __device__ __forceinline__ void sched_fence_(uint32_t a) {
  asm volatile("{.reg .pred p;\nsetp.eq.u32 p, %0, %1;\nSF: @p pmevent 0;\n@p bra.uni SF;}" ::"r"(a), "n"(0x40000000 + ID) : "memory");
}
#define sched_fence(a) sched_fence_<__LINE__>(a)
__device__ __forceinline__ bool elect() {
  uint32_t p;
  asm volatile("{.reg .pred p; elect.sync _|p, 0xffffffff; selp.u32 %0,1,0,p;}" : "=r"(p));
  return p;
}
__device__ __forceinline__ uint32_t opaque(uint32_t v) { return __shfl_sync(~0u, v, threadIdx.x & 31); }
__device__ __forceinline__ uint4 ldg_rlx128(const void* p) {
  uint4 v; asm volatile("ld.relaxed.gpu.global.v4.b32 {%0,%1,%2,%3}, [%4];" : "=r"(v.x), "=r"(v.y), "=r"(v.z), "=r"(v.w) : "l"(p) : "memory"); return v;
}
__device__ __forceinline__ uint2 ldg_rlx64(const void* p) {
  uint2 v; asm volatile("{.reg .b64 t; ld.relaxed.gpu.global.b64 t, [%2]; mov.b64 {%0,%1}, t;}" : "=r"(v.x), "=r"(v.y) : "l"(p) : "memory"); return v;
}
__device__ __forceinline__ uint32_t hmaxabs2(uint32_t a, uint32_t b) { uint32_t r; asm("max.xorsign.abs.bf16x2 %0, %1, %2;" : "=r"(r) : "r"(a), "r"(b)); return r; }
__device__ __forceinline__ uint32_t ldg_rlx32(const void* p) {
  uint32_t v; asm volatile("ld.relaxed.gpu.global.b32 %0, [%1];" : "=r"(v) : "l"(p) : "memory"); return v;
}
__device__ __forceinline__ float ldg_cg(const float* p) { float v; asm volatile("ld.global.cg.f32 %0, [%1];" : "=f"(v) : "l"(p) : "memory"); return v; }
__device__ __forceinline__ void spin_until(uint32_t t0, int d) {
#pragma unroll 1
  while (clk32() - t0 < (uint32_t)d) {}
}
__device__ __forceinline__ void stg_rlx64(void* p, uint32_t a, uint32_t b) {
  asm volatile("{.reg .b64 t; mov.b64 t, {%1,%2}; st.relaxed.gpu.global.b64 [%0], t;}" ::"l"(p), "r"(a), "r"(b) : "memory");
}
__device__ __forceinline__ uint32_t ldg_acq32(const void* p) { uint32_t v; asm volatile("ld.acquire.gpu.global.b32 %0, [%1];" : "=r"(v) : "l"(p) : "memory"); return v; }
__device__ __forceinline__ void stg_rel32(void* p, uint32_t v) { asm volatile("st.release.gpu.global.b32 [%0], %1;" ::"l"(p), "r"(v) : "memory"); }
__device__ __forceinline__ void cp_async16(uint32_t dst, const void* src) { asm volatile("cp.async.cg.shared.global [%0], [%1], 16;" ::"r"(dst), "l"(src) : "memory"); }
__device__ __forceinline__ void cp_async_wait_all() { asm volatile("cp.async.wait_all;" ::: "memory"); }
__device__ __forceinline__ void prefetch_l2(const void* p) { asm volatile("prefetch.global.L2 [%0];" ::"l"(p)); }
__device__ __forceinline__ void tma_load3(uint32_t dst, const CUtensorMap* tm, int c0, int c1, int c2, uint32_t bar) {
  asm volatile("cp.async.bulk.tensor.3d.shared::cluster.global.mbarrier::complete_tx::bytes [%0], [%1, {%3,%4,%5}], [%2];"
               ::"r"(dst), "l"(tm), "r"(bar), "r"(c0), "r"(c1), "r"(c2) : "memory");
}
__device__ __forceinline__ void tma_load2(uint32_t dst, const CUtensorMap* tm, int c0, int c1, uint32_t bar) {
  asm volatile("cp.async.bulk.tensor.2d.shared::cluster.global.mbarrier::complete_tx::bytes [%0], [%1, {%3,%4}], [%2];"
               ::"r"(dst), "l"(tm), "r"(bar), "r"(c0), "r"(c1) : "memory");
}
__device__ __forceinline__ void bulk_load(uint32_t dst, const void* src, uint32_t bytes, uint32_t bar) {
  asm volatile("cp.async.bulk.shared::cluster.global.mbarrier::complete_tx::bytes [%0], [%1], %2, [%3];" ::"r"(dst), "l"(src), "r"(bytes), "r"(bar) : "memory");
}
__device__ __forceinline__ void bulk_s2s(uint32_t dst, uint32_t src, uint32_t bytes, uint32_t bar) {
  asm volatile("cp.async.bulk.shared::cluster.shared::cta.mbarrier::complete_tx::bytes [%0], [%1], %2, [%3];" ::"r"(dst), "r"(src), "r"(bytes), "r"(bar) : "memory");
}
__device__ __forceinline__ void prefetch_map(const CUtensorMap* tm) { asm volatile("prefetch.tensormap [%0];" ::"l"(tm) : "memory"); }
__device__ __forceinline__ void tma_store2(const CUtensorMap* tm, uint32_t src, int c0, int c1) {
  asm volatile("cp.async.bulk.tensor.2d.global.shared::cta.bulk_group [%0, {%2,%3}], [%1];" ::"l"(tm), "r"(src), "r"(c0), "r"(c1) : "memory");
}
__device__ __forceinline__ void bulk_commit() { asm volatile("cp.async.bulk.commit_group;" ::: "memory"); }
__device__ __forceinline__ void bulk_wait0() { asm volatile("cp.async.bulk.wait_group 0;" ::: "memory"); }
__device__ __forceinline__ void bulk_wait_read0() { asm volatile("cp.async.bulk.wait_group.read 0;" ::: "memory"); }
__device__ __forceinline__ void wg_fence() { asm volatile("wgmma.fence.sync.aligned;" ::: "memory"); }
__device__ __forceinline__ void wg_commit() { asm volatile("wgmma.commit_group.sync.aligned;" ::: "memory"); }
__device__ __forceinline__ void wg_wait0() { asm volatile("wgmma.wait_group.sync.aligned 0;" ::: "memory"); }
__device__ __forceinline__ uint64_t desc_sw128(uint32_t addr) {
  return (uint64_t)((addr & 0x3FFFF) >> 4) | ((uint64_t)1 << 16) | ((uint64_t)64 << 32) | ((uint64_t)1 << 62);
}
template <int ACC>
__device__ __forceinline__ void wgmma_rs32(float* d, const uint32_t* a, uint64_t db) {
  asm volatile("{.reg .pred p; setp.ne.b32 p, %21, 0;\n"
               "wgmma.mma_async.sync.aligned.m64n32k16.f32.bf16.bf16 {%0,%1,%2,%3,%4,%5,%6,%7,%8,%9,%10,%11,%12,%13,%14,%15}, {%16,%17,%18,%19}, %20, p, 1, 1, 0;}"
               : "+f"(d[0]), "+f"(d[1]), "+f"(d[2]), "+f"(d[3]), "+f"(d[4]), "+f"(d[5]), "+f"(d[6]), "+f"(d[7]), "+f"(d[8]), "+f"(d[9]),
                 "+f"(d[10]), "+f"(d[11]), "+f"(d[12]), "+f"(d[13]), "+f"(d[14]), "+f"(d[15])
               : "r"(a[0]), "r"(a[1]), "r"(a[2]), "r"(a[3]), "l"(db), "n"(ACC));
}

template <int N> __device__ __forceinline__ void fence_regs(float* d) {
#pragma unroll
  for (int i = 0; i < N; i++) asm volatile("" : "+f"(d[i])::"memory");
}
__device__ __forceinline__ void wg_wait1() { asm volatile("wgmma.wait_group.sync.aligned 1;" ::: "memory"); }
__device__ __forceinline__ void tma_store3(const CUtensorMap* tm, uint32_t src, int c0, int c1, int c2) {
  asm volatile("cp.async.bulk.tensor.3d.global.shared::cta.bulk_group [%0, {%2,%3,%4}], [%1];" ::"l"(tm), "r"(src), "r"(c0), "r"(c1), "r"(c2) : "memory");
}
__device__ __forceinline__ void tma_red3(const CUtensorMap* tm, uint32_t src, int c0, int c1, int c2) {
  asm volatile("cp.reduce.async.bulk.tensor.3d.global.shared::cta.add.bulk_group [%0, {%2,%3,%4}], [%1];" ::"l"(tm), "r"(src), "r"(c0), "r"(c1), "r"(c2) : "memory");
}
__device__ __forceinline__ void tma_red2(const CUtensorMap* tm, uint32_t src, int c0, int c1) {
  asm volatile("cp.reduce.async.bulk.tensor.2d.global.shared::cta.add.bulk_group [%0, {%2,%3}], [%1];" ::"l"(tm), "r"(src), "r"(c0), "r"(c1) : "memory");
}
__device__ __forceinline__ void stsm4(uint32_t a, uint32_t r0, uint32_t r1, uint32_t r2, uint32_t r3) {
  asm volatile("stmatrix.sync.aligned.m8n8.x4.shared.b16 [%0], {%1,%2,%3,%4};" ::"r"(a), "r"(r0), "r"(r1), "r"(r2), "r"(r3) : "memory");
}
__device__ __forceinline__ uint2 lds64(uint32_t a) { uint2 v; asm volatile("ld.shared.v2.b32 {%0,%1}, [%2];" : "=r"(v.x), "=r"(v.y) : "r"(a) : "memory"); return v; }
__device__ __forceinline__ uint32_t hmul2(uint32_t a, uint32_t b) { uint32_t r; asm("mul.rn.bf16x2 %0, %1, %2;" : "=r"(r) : "r"(a), "r"(b)); return r; }
__device__ __forceinline__ void wgmma_ss192t(float* d, uint64_t da, uint64_t db, int acc) {
  asm volatile("{.reg .pred p; setp.ne.b32 p, %98, 0;\n"
    "wgmma.mma_async.sync.aligned.m64n192k16.f32.bf16.bf16 "
    "{%0,%1,%2,%3,%4,%5,%6,%7,%8,%9,%10,%11,%12,%13,%14,%15,%16,%17,%18,%19,%20,%21,%22,%23,%24,%25,%26,%27,%28,%29,%30,%31,%32,%33,%34,%35,%36,%37,%38,%39,%40,%41,%42,%43,%44,%45,%46,%47,%48,%49,%50,%51,%52,%53,%54,%55,%56,%57,%58,%59,%60,%61,%62,%63,%64,%65,%66,%67,%68,%69,%70,%71,%72,%73,%74,%75,%76,%77,%78,%79,%80,%81,%82,%83,%84,%85,%86,%87,%88,%89,%90,%91,%92,%93,%94,%95}, %96, %97, p, 1, 1, 0, 1;}"
    : "+f"(d[0]), "+f"(d[1]), "+f"(d[2]), "+f"(d[3]), "+f"(d[4]), "+f"(d[5]), "+f"(d[6]), "+f"(d[7]), "+f"(d[8]), "+f"(d[9]), "+f"(d[10]), "+f"(d[11]),
      "+f"(d[12]), "+f"(d[13]), "+f"(d[14]), "+f"(d[15]), "+f"(d[16]), "+f"(d[17]), "+f"(d[18]), "+f"(d[19]), "+f"(d[20]), "+f"(d[21]), "+f"(d[22]),
      "+f"(d[23]), "+f"(d[24]), "+f"(d[25]), "+f"(d[26]), "+f"(d[27]), "+f"(d[28]), "+f"(d[29]), "+f"(d[30]), "+f"(d[31]), "+f"(d[32]), "+f"(d[33]),
      "+f"(d[34]), "+f"(d[35]), "+f"(d[36]), "+f"(d[37]), "+f"(d[38]), "+f"(d[39]), "+f"(d[40]), "+f"(d[41]), "+f"(d[42]), "+f"(d[43]), "+f"(d[44]),
      "+f"(d[45]), "+f"(d[46]), "+f"(d[47]), "+f"(d[48]), "+f"(d[49]), "+f"(d[50]), "+f"(d[51]), "+f"(d[52]), "+f"(d[53]), "+f"(d[54]), "+f"(d[55]),
      "+f"(d[56]), "+f"(d[57]), "+f"(d[58]), "+f"(d[59]), "+f"(d[60]), "+f"(d[61]), "+f"(d[62]), "+f"(d[63]), "+f"(d[64]), "+f"(d[65]), "+f"(d[66]),
      "+f"(d[67]), "+f"(d[68]), "+f"(d[69]), "+f"(d[70]), "+f"(d[71]), "+f"(d[72]), "+f"(d[73]), "+f"(d[74]), "+f"(d[75]), "+f"(d[76]), "+f"(d[77]),
      "+f"(d[78]), "+f"(d[79]), "+f"(d[80]), "+f"(d[81]), "+f"(d[82]), "+f"(d[83]), "+f"(d[84]), "+f"(d[85]), "+f"(d[86]), "+f"(d[87]), "+f"(d[88]),
      "+f"(d[89]), "+f"(d[90]), "+f"(d[91]), "+f"(d[92]), "+f"(d[93]), "+f"(d[94]), "+f"(d[95])
    : "l"(da), "l"(db), "r"(acc));
}
__device__ __forceinline__ void wgmma_rs128t(float* d, const uint32_t* a, uint64_t db, int acc) {
  asm volatile("{.reg .pred p; setp.ne.b32 p, %69, 0;\n"
    "wgmma.mma_async.sync.aligned.m64n128k16.f32.bf16.bf16 "
    "{%0,%1,%2,%3,%4,%5,%6,%7,%8,%9,%10,%11,%12,%13,%14,%15,%16,%17,%18,%19,%20,%21,%22,%23,%24,%25,%26,%27,%28,%29,%30,%31,%32,%33,%34,%35,%36,%37,%38,%39,%40,%41,%42,%43,%44,%45,%46,%47,%48,%49,%50,%51,%52,%53,%54,%55,%56,%57,%58,%59,%60,%61,%62,%63}, {%64,%65,%66,%67}, %68, p, 1, 1, 1;}"
    : "+f"(d[0]), "+f"(d[1]), "+f"(d[2]), "+f"(d[3]), "+f"(d[4]), "+f"(d[5]), "+f"(d[6]), "+f"(d[7]), "+f"(d[8]), "+f"(d[9]), "+f"(d[10]), "+f"(d[11]),
      "+f"(d[12]), "+f"(d[13]), "+f"(d[14]), "+f"(d[15]), "+f"(d[16]), "+f"(d[17]), "+f"(d[18]), "+f"(d[19]), "+f"(d[20]), "+f"(d[21]), "+f"(d[22]),
      "+f"(d[23]), "+f"(d[24]), "+f"(d[25]), "+f"(d[26]), "+f"(d[27]), "+f"(d[28]), "+f"(d[29]), "+f"(d[30]), "+f"(d[31]), "+f"(d[32]), "+f"(d[33]),
      "+f"(d[34]), "+f"(d[35]), "+f"(d[36]), "+f"(d[37]), "+f"(d[38]), "+f"(d[39]), "+f"(d[40]), "+f"(d[41]), "+f"(d[42]), "+f"(d[43]), "+f"(d[44]),
      "+f"(d[45]), "+f"(d[46]), "+f"(d[47]), "+f"(d[48]), "+f"(d[49]), "+f"(d[50]), "+f"(d[51]), "+f"(d[52]), "+f"(d[53]), "+f"(d[54]), "+f"(d[55]),
      "+f"(d[56]), "+f"(d[57]), "+f"(d[58]), "+f"(d[59]), "+f"(d[60]), "+f"(d[61]), "+f"(d[62]), "+f"(d[63])
    : "r"(a[0]), "r"(a[1]), "r"(a[2]), "r"(a[3]), "l"(db), "r"(acc));
}
__device__ __forceinline__ void wgmma_rs80(float* d, const uint32_t* a, uint64_t db, int acc) {
  asm volatile("{.reg .pred p; setp.ne.b32 p, %45, 0;\n"
    "wgmma.mma_async.sync.aligned.m64n80k16.f32.bf16.bf16 "
    "{%0,%1,%2,%3,%4,%5,%6,%7,%8,%9,%10,%11,%12,%13,%14,%15,%16,%17,%18,%19,%20,%21,%22,%23,%24,%25,%26,%27,%28,%29,%30,%31,%32,%33,%34,%35,%36,%37,%38,%39}, {%40,%41,%42,%43}, %44, p, 1, 1, 0;}"
    : "+f"(d[0]), "+f"(d[1]), "+f"(d[2]), "+f"(d[3]), "+f"(d[4]), "+f"(d[5]), "+f"(d[6]), "+f"(d[7]), "+f"(d[8]), "+f"(d[9]), "+f"(d[10]), "+f"(d[11]),
      "+f"(d[12]), "+f"(d[13]), "+f"(d[14]), "+f"(d[15]), "+f"(d[16]), "+f"(d[17]), "+f"(d[18]), "+f"(d[19]), "+f"(d[20]), "+f"(d[21]), "+f"(d[22]),
      "+f"(d[23]), "+f"(d[24]), "+f"(d[25]), "+f"(d[26]), "+f"(d[27]), "+f"(d[28]), "+f"(d[29]), "+f"(d[30]), "+f"(d[31]), "+f"(d[32]), "+f"(d[33]),
      "+f"(d[34]), "+f"(d[35]), "+f"(d[36]), "+f"(d[37]), "+f"(d[38]), "+f"(d[39])
    : "r"(a[0]), "r"(a[1]), "r"(a[2]), "r"(a[3]), "l"(db), "r"(acc));
}
__device__ __forceinline__ void wgmma_rs64t(float* d, const uint32_t* a, uint64_t db, int acc) {
  asm volatile("{.reg .pred p; setp.ne.b32 p, %37, 0;\n"
    "wgmma.mma_async.sync.aligned.m64n64k16.f32.bf16.bf16 "
    "{%0,%1,%2,%3,%4,%5,%6,%7,%8,%9,%10,%11,%12,%13,%14,%15,%16,%17,%18,%19,%20,%21,%22,%23,%24,%25,%26,%27,%28,%29,%30,%31}, {%32,%33,%34,%35}, %36, p, 1, 1, 1;}"
    : "+f"(d[0]), "+f"(d[1]), "+f"(d[2]), "+f"(d[3]), "+f"(d[4]), "+f"(d[5]), "+f"(d[6]), "+f"(d[7]), "+f"(d[8]), "+f"(d[9]), "+f"(d[10]), "+f"(d[11]),
      "+f"(d[12]), "+f"(d[13]), "+f"(d[14]), "+f"(d[15]), "+f"(d[16]), "+f"(d[17]), "+f"(d[18]), "+f"(d[19]), "+f"(d[20]), "+f"(d[21]), "+f"(d[22]),
      "+f"(d[23]), "+f"(d[24]), "+f"(d[25]), "+f"(d[26]), "+f"(d[27]), "+f"(d[28]), "+f"(d[29]), "+f"(d[30]), "+f"(d[31])
    : "r"(a[0]), "r"(a[1]), "r"(a[2]), "r"(a[3]), "l"(db), "r"(acc));
}
__device__ __forceinline__ void wgmma_rs224t(float* d, const uint32_t* a, uint64_t db, int acc) {
  asm volatile("{.reg .pred p; setp.ne.b32 p, %117, 0;\n"
    "wgmma.mma_async.sync.aligned.m64n224k16.f32.bf16.bf16 "
    "{%0,%1,%2,%3,%4,%5,%6,%7,%8,%9,%10,%11,%12,%13,%14,%15,%16,%17,%18,%19,%20,%21,%22,%23,%24,%25,%26,%27,%28,%29,%30,%31,%32,%33,%34,%35,%36,%37,%38,%39,%40,%41,%42,%43,%44,%45,%46,%47,%48,%49,%50,%51,%52,%53,%54,%55,%56,%57,%58,%59,%60,%61,%62,%63,%64,%65,%66,%67,%68,%69,%70,%71,%72,%73,%74,%75,%76,%77,%78,%79,%80,%81,%82,%83,%84,%85,%86,%87,%88,%89,%90,%91,%92,%93,%94,%95,%96,%97,%98,%99,%100,%101,%102,%103,%104,%105,%106,%107,%108,%109,%110,%111}, {%112,%113,%114,%115}, %116, p, 1, 1, 1;}"
    : "+f"(d[0]), "+f"(d[1]), "+f"(d[2]), "+f"(d[3]), "+f"(d[4]), "+f"(d[5]), "+f"(d[6]), "+f"(d[7]), "+f"(d[8]), "+f"(d[9]), "+f"(d[10]), "+f"(d[11]),
      "+f"(d[12]), "+f"(d[13]), "+f"(d[14]), "+f"(d[15]), "+f"(d[16]), "+f"(d[17]), "+f"(d[18]), "+f"(d[19]), "+f"(d[20]), "+f"(d[21]), "+f"(d[22]),
      "+f"(d[23]), "+f"(d[24]), "+f"(d[25]), "+f"(d[26]), "+f"(d[27]), "+f"(d[28]), "+f"(d[29]), "+f"(d[30]), "+f"(d[31]), "+f"(d[32]), "+f"(d[33]),
      "+f"(d[34]), "+f"(d[35]), "+f"(d[36]), "+f"(d[37]), "+f"(d[38]), "+f"(d[39]), "+f"(d[40]), "+f"(d[41]), "+f"(d[42]), "+f"(d[43]), "+f"(d[44]),
      "+f"(d[45]), "+f"(d[46]), "+f"(d[47]), "+f"(d[48]), "+f"(d[49]), "+f"(d[50]), "+f"(d[51]), "+f"(d[52]), "+f"(d[53]), "+f"(d[54]), "+f"(d[55]),
      "+f"(d[56]), "+f"(d[57]), "+f"(d[58]), "+f"(d[59]), "+f"(d[60]), "+f"(d[61]), "+f"(d[62]), "+f"(d[63]), "+f"(d[64]), "+f"(d[65]), "+f"(d[66]),
      "+f"(d[67]), "+f"(d[68]), "+f"(d[69]), "+f"(d[70]), "+f"(d[71]), "+f"(d[72]), "+f"(d[73]), "+f"(d[74]), "+f"(d[75]), "+f"(d[76]), "+f"(d[77]),
      "+f"(d[78]), "+f"(d[79]), "+f"(d[80]), "+f"(d[81]), "+f"(d[82]), "+f"(d[83]), "+f"(d[84]), "+f"(d[85]), "+f"(d[86]), "+f"(d[87]), "+f"(d[88]),
      "+f"(d[89]), "+f"(d[90]), "+f"(d[91]), "+f"(d[92]), "+f"(d[93]), "+f"(d[94]), "+f"(d[95]), "+f"(d[96]), "+f"(d[97]), "+f"(d[98]), "+f"(d[99]),
      "+f"(d[100]), "+f"(d[101]), "+f"(d[102]), "+f"(d[103]), "+f"(d[104]), "+f"(d[105]), "+f"(d[106]), "+f"(d[107]), "+f"(d[108]), "+f"(d[109]),
      "+f"(d[110]), "+f"(d[111])
    : "r"(a[0]), "r"(a[1]), "r"(a[2]), "r"(a[3]), "l"(db), "r"(acc));
}
__device__ __forceinline__ void wgmma_rs192t(float* d, const uint32_t* a, uint64_t db, int acc) {
  asm volatile("{.reg .pred p; setp.ne.b32 p, %101, 0;\n"
    "wgmma.mma_async.sync.aligned.m64n192k16.f32.bf16.bf16 "
    "{%0,%1,%2,%3,%4,%5,%6,%7,%8,%9,%10,%11,%12,%13,%14,%15,%16,%17,%18,%19,%20,%21,%22,%23,%24,%25,%26,%27,%28,%29,%30,%31,%32,%33,%34,%35,%36,%37,%38,%39,%40,%41,%42,%43,%44,%45,%46,%47,%48,%49,%50,%51,%52,%53,%54,%55,%56,%57,%58,%59,%60,%61,%62,%63,%64,%65,%66,%67,%68,%69,%70,%71,%72,%73,%74,%75,%76,%77,%78,%79,%80,%81,%82,%83,%84,%85,%86,%87,%88,%89,%90,%91,%92,%93,%94,%95}, {%96,%97,%98,%99}, %100, p, 1, 1, 1;}"
    : "+f"(d[0]), "+f"(d[1]), "+f"(d[2]), "+f"(d[3]), "+f"(d[4]), "+f"(d[5]), "+f"(d[6]), "+f"(d[7]), "+f"(d[8]), "+f"(d[9]), "+f"(d[10]), "+f"(d[11]),
      "+f"(d[12]), "+f"(d[13]), "+f"(d[14]), "+f"(d[15]), "+f"(d[16]), "+f"(d[17]), "+f"(d[18]), "+f"(d[19]), "+f"(d[20]), "+f"(d[21]), "+f"(d[22]),
      "+f"(d[23]), "+f"(d[24]), "+f"(d[25]), "+f"(d[26]), "+f"(d[27]), "+f"(d[28]), "+f"(d[29]), "+f"(d[30]), "+f"(d[31]), "+f"(d[32]), "+f"(d[33]),
      "+f"(d[34]), "+f"(d[35]), "+f"(d[36]), "+f"(d[37]), "+f"(d[38]), "+f"(d[39]), "+f"(d[40]), "+f"(d[41]), "+f"(d[42]), "+f"(d[43]), "+f"(d[44]),
      "+f"(d[45]), "+f"(d[46]), "+f"(d[47]), "+f"(d[48]), "+f"(d[49]), "+f"(d[50]), "+f"(d[51]), "+f"(d[52]), "+f"(d[53]), "+f"(d[54]), "+f"(d[55]),
      "+f"(d[56]), "+f"(d[57]), "+f"(d[58]), "+f"(d[59]), "+f"(d[60]), "+f"(d[61]), "+f"(d[62]), "+f"(d[63]), "+f"(d[64]), "+f"(d[65]), "+f"(d[66]),
      "+f"(d[67]), "+f"(d[68]), "+f"(d[69]), "+f"(d[70]), "+f"(d[71]), "+f"(d[72]), "+f"(d[73]), "+f"(d[74]), "+f"(d[75]), "+f"(d[76]), "+f"(d[77]),
      "+f"(d[78]), "+f"(d[79]), "+f"(d[80]), "+f"(d[81]), "+f"(d[82]), "+f"(d[83]), "+f"(d[84]), "+f"(d[85]), "+f"(d[86]), "+f"(d[87]), "+f"(d[88]),
      "+f"(d[89]), "+f"(d[90]), "+f"(d[91]), "+f"(d[92]), "+f"(d[93]), "+f"(d[94]), "+f"(d[95])
    : "r"(a[0]), "r"(a[1]), "r"(a[2]), "r"(a[3]), "l"(db), "r"(acc));
}

struct Desc {
  uint32_t lo, hi;
  __device__ __forceinline__ Desc operator+(uint32_t o) const { return {lo + o, hi}; }
  __device__ __forceinline__ operator uint64_t() const { return ((uint64_t)hi << 32) | lo; }
};
__device__ __forceinline__ Desc mk_desc(uint32_t addr, uint32_t lbo, uint32_t sbo, uint32_t mode) {
  return {(addr >> 4) | ((lbo >> 4) << 16), (sbo >> 4) | (mode << 30)};
}

struct AttMask {
  uint32_t hi, z;
  float c0, c1, mb[10];
  __device__ __forceinline__ AttMask(uint32_t tid, uint32_t sb) {
    constexpr float SCL = 0.07216878364870322f * 1.4426950408889634f;
    hi = pin(tid & 64); z = sb >> 31;
    c0 = hi ? 0.f : SCL; c1 = hi ? SCL : 0.f;
    const int tt = (int)pin(((tid >> 1) & 16) + ((tid >> 2) & 7) - 2 * (tid & 3));
#pragma unroll
    for (int i = 0; i < 10; i++) mb[i] = 8 * ((i >> 1) - 1) + (i & 1) > tt ? -INFINITY : 0.f;
  }
};
__device__ __forceinline__ void att_softmax(const AttMask& m, const float* s_, uint32_t (&p)[5][4], float g0, float g1) {
  const uint32_t hi = m.hi;
  const float c0 = m.c0, c1 = m.c1;
  const float* mb = m.mb;
  float v[20], mx[2], sum[2];
#pragma unroll
  for (int i = 0; i < 20; i++)
    if (i != 16 && i != 17) v[i] = fmaf(s_[20 + i], c1, i < 4 ? s_[i] * c0 : fmaf(s_[i], c0, mb[2 * ((i >> 2) - ((i >> 1) & 1)) + (i & 1)]));
  mx[0] = fmaxf(fmaxf(fmaxf(v[0], v[1]), fmaxf(v[4], v[5])), fmaxf(fmaxf(v[8], v[9]), fmaxf(v[12], v[13])));
  mx[1] = fmaxf(fmaxf(fmaxf(v[2], v[3]), fmaxf(v[6], v[7])), fmaxf(fmaxf(v[10], v[11]), fmaxf(v[14], v[15])));
  mx[1] = fmaxf(mx[1], fmaxf(v[18], v[19]));
  {
    const float ni = __uint_as_float(0xff800000u | m.z), a_ = fminf(mx[0], ni), b_ = fminf(mx[1], ni);
    mx[0] = fmaxf(mx[0], b_); mx[1] = fmaxf(mx[1], a_);
  }
#pragma unroll
  for (int o = 1; o < 4; o <<= 1)
#pragma unroll
    for (int h = 0; h < 2; h++) mx[h] = fmaxf(mx[h], __shfl_xor_sync(~0u, mx[h], o));
#pragma unroll
  for (int i = 0; i < 20; i++) v[i] = i == 16 || i == 17 ? 0.f : ex2(v[i] - mx[(i >> 1) & 1]);
  sum[0] = ((v[0] + v[1]) + (v[4] + v[5])) + ((v[8] + v[9]) + (v[12] + v[13]));
  sum[1] = ((v[2] + v[3]) + (v[6] + v[7])) + ((v[10] + v[11]) + (v[14] + v[15])) + (v[18] + v[19]);
  {
    const float z = __uint_as_float(m.z), a_ = sum[0];
    sum[0] = fmaf(sum[1], z, a_); sum[1] = fmaf(a_, z, sum[1]);
  }
  sum[0] += __shfl_xor_sync(~0u, sum[0], 1);
  sum[1] += __shfl_xor_sync(~0u, sum[1], 1);
  {
    const float z = __uint_as_float(m.z), a_ = sum[0];
    sum[0] = fmaf(sum[1], z, a_); sum[1] = fmaf(a_, z, sum[1]);
  }
  sum[0] += __shfl_xor_sync(~0u, sum[0], 2);
  sum[1] += __shfl_xor_sync(~0u, sum[1], 2);
  const float r0 = g0 * rcp(sum[0]), r1 = g1 * rcp(sum[1]);
#pragma unroll
  for (int j = 0; j < 5; j++)
#pragma unroll
    for (int h = 0; h < 2; h++) {
      const uint32_t pt = j == 4 && h == 0 ? 0u : pack2(v[4 * j + 2 * h] * (h ? r1 : r0), v[4 * j + 2 * h + 1] * (h ? r1 : r0));
      p[j >> 1][(j & 1) * 2 + h] = hi ? 0u : pt;
      p[(j + 5) >> 1][((j + 5) & 1) * 2 + h] = hi ? pt : 0u;
    }
#pragma unroll
  for (int i = 0; i < 20; i++) asm volatile("" : "+r"(p[i >> 2][i & 3]));
}

constexpr int NPQ = 2;
#define NQ 12
#define NQ_WIN 8
#define NO_EARLY 6
#define NO_MID 9
#define NW1 16
#define NW1A 10
#define VLD 6
#define VB 0
#define XPF 3
#define WSPLIT 8
#define PEARLY 0
#define NQ_W1 8
#define B5LATE 0
#define WD 700
#define DFENCE 0
#define PDS 300
#define PDT 50
#define LDEP 1
#define LDT 6000
#define CT 999
#define ZF 1
#define GS 1
#define PFD 1
#define PFK 0
#define TLD 0
#define PFN 2
#define PFB 8000
#define WARM 0
#define WDEL 24000
#define QE 0
#define VBULK 1
#define VBW 3
#define PD 780
constexpr int R_WQ = 0;
constexpr int R_WO = R_WQ + 8 * (20 - NPQ) * 512;
constexpr int R_XT = R_WO + 14 * 12 * 512;
constexpr int R_MEM = R_XT;
constexpr int R_QB = R_XT + 40960;
constexpr int R_QA = R_QB + 1024;
constexpr int R_O2 = R_QA + 1024;
constexpr int R_VS = R_O2 + 1024;
constexpr int R_KT = R_VS + 1024;
constexpr int R_VT = R_KT + 5120;
constexpr int R_V1 = R_VT + 5120;
constexpr int R_SX = R_V1 + 8192;
constexpr int R_VM = R_SX + 4608;
constexpr int R_BAR = R_VM + 2048;
constexpr int R_MI = R_BAR + 64;
constexpr int R_EB = R_MI + 64;
constexpr int R_SMEM = R_EB + 64 + 96;
constexpr int E_KA = 0, E_VA = 30720, E_KB = R_XT + 10240, E_VB0 = 61440, E_VB1 = R_V1, E_VB2 = R_XT;
static_assert(R_V1 + 10240 <= R_BAR && E_VB0 + 10240 <= R_WO, "chunks");
static_assert(NPQ == 2 && R_XT % 1024 == 0 && R_KT % 1024 == 0 && R_VT % 1024 == 0 && R_V1 % 1024 == 0 && R_WO % 1024 == 0, "align");
constexpr int R_SMEM_ALLOC = R_SMEM;
static_assert(R_SMEM_ALLOC <= 232448, "smem");

#define TR(i) do {} while (0)

__device__ __forceinline__ void red_pair(unsigned char* p, float lo, float hi) {
  const int b = __float2int_rn(lo), a = __float2int_rn(hi);
  asm volatile("{.reg .b64 t; mov.b64 t, {%1,%2}; red.relaxed.gpu.global.add.u64 [%0], t;}" ::"l"(p), "r"(b + ((1 << 29) + (1 << 23))), "r"(a * 8) : "memory");
}
__device__ __forceinline__ unsigned long long swap0(unsigned char* p) {
  unsigned long long r;
  asm volatile("atom.relaxed.gpu.global.exch.b64 %0, [%1], 0;" : "=l"(r) : "l"(p) : "memory");
  return r;
}
__device__ __forceinline__ uint32_t dec_pair(uint32_t lo, uint32_t hi, uint32_t bias) { return pack2((float)(int)(lo * 8u + bias), (float)(int)hi); }

__global__ void __cluster_dims__(3, 1, 1) __launch_bounds__(256, 1)
rec_kernel(const __grid_constant__ CUtensorMap tmX, const __grid_constant__ CUtensorMap tmK, const __grid_constant__ CUtensorMap tmV,
           const __grid_constant__ CUtensorMap tmWq, const __grid_constant__ CUtensorMap tmWq2, const __grid_constant__ CUtensorMap tmWk,
           const __grid_constant__ CUtensorMap tmWv, const __grid_constant__ CUtensorMap tmWo, const __grid_constant__ CUtensorMap tmOut,
           const bf16* __restrict__ mem0,
           const bf16* __restrict__ Wq, const bf16* __restrict__ Wk, const bf16* __restrict__ Wv, const bf16* __restrict__ Wo, const bf16* __restrict__ x, const bf16* __restrict__ gate_w,
           bf16* __restrict__ out, unsigned char* __restrict__ red) {
  extern __shared__ __align__(1024) unsigned char smem[];
  const uint32_t sb = smem_u32(smem);
  const int tid = threadIdx.x, lane = tid & 31, wid = __shfl_sync(~0u, tid >> 5, 0), g = wid >> 2, w = wid & 3;
  const int cta = blockIdx.x, head = cta / 3, rank = cta % 3;
  const int D0 = head * DH + rank * 64;
  const int tile0 = rank == 0 ? 0 : (rank == 1 ? 14 : 26);
  const uint32_t XBAR = sb + R_BAR, SBAR = XBAR + 8, OBAR = XBAR + 16, VBAR = XBAR + 24, FBAR = XBAR + 32, WBAR = XBAR + 40;
  constexpr uint32_t ONES = 0x3F803F80u;
  if (LDEP == 0) asm volatile("griddepcontrol.launch_dependents;" ::: "memory");
  const bool dry = WARM && cta >= 96;
  uint32_t ww[40][4], wqp[NPQ][4];
  if (dry) spin_until(clk32(), WDEL);
  if (!dry) {
  GTR(0);
  if (PFK == 1) {
#pragma unroll
    for (int i = 0; i < 5; i++) { const int l = tid + i * 256; prefetch_l2((l < 640 ? Wk : Wv - 40960) + (size_t)cta * 40960 + l * 64); }
  }
  if (PFK >= 2 && wid == 7 && lane < (PFK == 2 ? 10 : 20)) {
    const bf16* b = lane < 5 ? Wk : (lane < 10 ? Wv : (lane < 15 ? Wq : Wo));
    asm volatile("cp.async.bulk.prefetch.L2.global [%0], 16384;" ::"l"(b + (size_t)cta * 40960 + (lane % 5) * 8192) : "memory");
  }
  if (wid == 0) {
    if (lane == 0) {
      mbar_init(XBAR, 1); mbar_init(SBAR, 4); mbar_init(OBAR, 5); mbar_init(VBAR, 1); mbar_init(FBAR, 2);
      mbar_init(WBAR, 1); mbar_init(WBAR + 8, 1); mbar_init(WBAR + 16, 1);
      for (int i = 0; i < 6; i++) mbar_init(sb + R_EB + i * 8, i < 4 ? 1 : 2);
      asm volatile("fence.mbarrier_init.release.cluster;" ::: "memory");
      mbar_expect(WBAR, 81920); mbar_expect(WBAR + 8, 81920 + 2 * NPQ * 2048); mbar_expect(XBAR, 40960);
      mbar_expect(SBAR, 3072); mbar_expect(OBAR, 2048); mbar_expect(VBAR, 8192);
      for (int i = 0; i < 4; i++) mbar_expect(sb + R_EB + i * 8, 30720);
      sts128(sb + R_MI + 48, 0, 0, 0, 0);
      sts32(sb + R_MI, *(volatile uint32_t*)&g_epoch + 1);
    }
    __syncwarp();
    if (TLD) spin_until(clk32(), TLD);
    if (lane < 5) tma_load2(sb + lane * 16384, &tmWk, D0, lane * 128, WBAR);
    if (lane == 5) tma_load3(sb + R_XT, &tmX, 0, 0, 0, XBAR);
    if (lane < 5) tma_load2(lane < 4 ? sb + 81920 + lane * 16384 : sb + R_QB, &tmWv, D0, lane * 128, WBAR + 8);
    if (lane < 2) tma_load2(sb + R_QB + 16384 + lane * 4096, &tmWq2, D0, lane * 320, WBAR + 8);
  }
  if (tid == 32) { prefetch_map(&tmWq); prefetch_map(&tmWo); prefetch_map(&tmK); prefetch_map(&tmV); prefetch_map(&tmOut); }
  if (tid >= 64 && tid < 144) prefetch_l2(mem0 + (tid - 64) * 64);
  __syncthreads();
  GTR(1);
  if (LDEP == 1) asm volatile("griddepcontrol.launch_dependents;" ::: "memory");
  if (LDEP == 4 && wid == 7) { spin_until(clk32(), LDT); asm volatile("griddepcontrol.launch_dependents;" ::: "memory"); }
  const uint32_t c0 = clk32();
  auto pfw = [&]() {
#pragma unroll
    for (int i = 0; i < 5; i++) { const int l = tid + i * 256; prefetch_l2((l < 640 ? Wq : Wo - 40960) + (size_t)cta * 40960 + l * 64); }
  };
  if (PFD == 0) pfw();
  {
    uint32_t xm = 0;
    {
      const int row = cta * 8 + wid;
      uint4 gw[3], v[3][3];
#pragma unroll
      for (int r = 0; r < 3; r++)
#pragma unroll
        for (int i = 0; i < 3; i++)
          v[r][i] = (i < 2 || lane < 16) && (r < 2 || row < 512) ? __ldg((const uint4*)(x + (size_t)(row + r * 768) * DM) + lane + 32 * i) : make_uint4(0, 0, 0, 0);
#pragma unroll
      for (int i = 0; i < 3; i++) gw[i] = (i < 2 || lane < 16) ? __ldg((const uint4*)gate_w + lane + 32 * i) : make_uint4(0, 0, 0, 0);
      if (PFD > 1) { spin_until(c0, PFD); pfw(); }
      if (PFN && wid == 7) {
        spin_until(c0, PFB);
        if (lane < 4 && lane < PFN)
          asm volatile("cp.async.bulk.prefetch.tensor.2d.L2.global [%0, {%1,%2}];" ::"l"(&tmWq), "r"(D0), "r"((lane >> 1) * 320 + 32 + (lane & 1) * 144) : "memory");
        else if (lane < PFN)
          asm volatile("cp.async.bulk.prefetch.tensor.3d.L2.global [%0, {%1,%2,%3}];" ::"l"(&tmWo), "r"(0), "r"(head * DH + (lane - 4) * 64), "r"(tile0 >> 1) : "memory");
      }
      if (cta < 80 && tid < 128) ((uint4*)(out + (S_TOK - 128) * DM))[cta * 128 + tid] = make_uint4(0, 0, 0, 0);
      float z = 0.f;
#pragma unroll
      for (int r = 0; r < 3; r++) {
        float s_ = 0.f;
#pragma unroll
        for (int i = 0; i < 3; i++) {
          const uint4 q = v[r][i];
          xm = hmaxabs2(hmaxabs2(xm, hmaxabs2(q.x, q.y)), hmaxabs2(q.z, q.w));
          const uint32_t p0 = hmul2(q.x, gw[i].x), p1 = hmul2(q.y, gw[i].y), p2 = hmul2(q.z, gw[i].z), p3 = hmul2(q.w, gw[i].w);
          s_ += ((bf_lo(p0) + bf_hi(p0)) + (bf_lo(p1) + bf_hi(p1))) + ((bf_lo(p2) + bf_hi(p2)) + (bf_lo(p3) + bf_hi(p3)));
        }
#pragma unroll
        for (int o = 16; o; o >>= 1) s_ += __shfl_xor_sync(~0u, s_, o);
        if (lane == r) z = s_;
      }
      z = bf_lo(pack2(z, 0.f));
      const float gv = bf_lo(pack2(1.f / (1.f + __expf(-z)), 0.f));
      if (!GS) { if (lane < (row < 512 ? 3 : 2)) { g_gate[row + lane * 768] = gv; g_gate[S_TOK + row + lane * 768] = bf_lo(pack2(1.f - gv, 0.f)); } }
      else if (lane < 3) sts32(sb + R_EB + 64 + lane * 32 + wid * 4, __float_as_uint(gv));
      if (ZF) asm volatile("fence.proxy.async.global;" ::: "memory");
    }
    xm = __reduce_max_sync(~0u, max((xm << 16) & 0x7fffffffu, xm & 0x7fff0000u));
    const uint32_t p = sb + (lane >> 4) * 1024 + (lane & 7) * 128 + (((2 * w + ((lane >> 3) & 1)) ^ (lane & 7)) << 4);
    if (LDEP == 2) asm volatile("griddepcontrol.launch_dependents;" ::: "memory");
    mbar_wait(WBAR + 8 * g, 0);
    GTR(2);
#pragma unroll
    for (int f = 0; f < 40; f++) ldsm4t(ww[f], (f >= 32 && g == 1) ? p + R_QB + (f - 32) * 2048 : p + g * 81920 + f * 2048);
    mbar_wait(WBAR + 8, 0);
    GTR(3);
#pragma unroll
    for (int f = 0; f < NPQ; f++) ldsm4t(wqp[f], p + R_QB + 16384 + g * 4096 + f * 2048);
    __syncthreads();
    GTR(5);
    asm volatile("barrier.cluster.arrive.relaxed.aligned;" ::: "memory");
    if (GS && wid == 3 && lane < (cta < 64 ? 24 : 16)) {
      const float gv = __uint_as_float(lds32(sb + R_EB + 64 + lane * 4));
      float* gp = g_gate + cta * 8 + (lane >> 3) * 768 + (lane & 7);
      gp[0] = gv; gp[S_TOK] = bf_lo(pack2(1.f - gv, 0.f));
    }
    if (wid == 0) {
      if (lane == 0) mbar_expect(WBAR + 16, 18 * 4096 + 21 * 4096);
      __syncwarp();
      if (lane < 4) tma_load2(sb + R_WQ + lane * 18432, &tmWq, D0, (lane >> 1) * 320 + 32 + (lane & 1) * 144, WBAR + 16);
      else if (lane < 7) tma_load3(sb + R_WO + ((lane - 1 - rank) % 3) * 28672, &tmWo, 0, head * DH + (lane - 4) * 64, tile0 >> 1, WBAR + 16);
      __syncwarp();
    }
    GTR(6);
    float nv[4] = {0.f, 0.f, 0.f, 0.f};
#pragma unroll
    for (int f = 0; f < 40; f++) {
      const uint32_t a[4] = {ww[f][0] & 0x7fff7fffu, ww[f][1] & 0x7fff7fffu, ww[f][2] & 0x7fff7fffu, ww[f][3] & 0x7fff7fffu};
      mma16816(nv, a, ONES, ONES);
    }
    const uint32_t mv = __reduce_max_sync(~0u, __float_as_uint(fmaxf(nv[0], nv[2])));
    if (lane == 0) { if (g == 1) smax32(sb + R_MI + 48, mv); smax32(sb + R_MI + 52, xm); }
  }
  GTR(4);
  if (LDEP == 3) asm volatile("griddepcontrol.launch_dependents;" ::: "memory");
  }

  const uint32_t rF_ = opaque(sb + lane * 16);
  const uint32_t rP_ = opaque(sb + (lane >> 4) * 1024 + (lane & 7) * 128 + (((2 * w + ((lane >> 3) & 1)) ^ (lane & 7)) << 4));
  const int tA = g == 1 ? 2 * w : (rank != 1 ? (w < 2 ? 8 + 2 * w : 10 + w) : 8 + w);
  const bool two = g == 1 || (w < 2 && rank != 1);
  const uint32_t r1 = rank == 2 ? 0 : rank + 1, r2 = rank == 0 ? 2 : rank - 1;
  const uint32_t rW_ = opaque(sb + R_WO + (tA >> 1) * 4096 + ((lane >> 4) * 8 + (lane & 7)) * 64 +
                             (((2 * (tA & 1) + ((lane >> 3) & 1)) ^ ((lane >> 1) & 3)) << 4));
  const uint32_t toff = rb_q((tile0 + tA) >> 2) + rb_j(4 * (tile0 + tA)), zoff = rb_q((cta % 20) >> 1) + rb_j((cta % 20) * 8);
  uint32_t wqt[NQ][4];
  float u = 1.f;
  uint32_t t0 = 0;
  int s = -1;

#define WOFF(ks) (((ks) >> 2) * 28672 + ((ks) & 3) * 1024)
#define XDESC(j) (((uint64_t)0x40000040 << 32) | (dlo + ((((j) >> 2) * 4096 + ((j) & 3) * 32) >> 4)))

  auto vsend = [&]() {
    if (elect()) {
      if (VBULK != 1) fence_async_smem();
      bulk_s2s(mapa(sb + R_V1 + 4096, r1), sb + R_VT + 1024, 4096, mapa(VBAR, r1));
      bulk_s2s(mapa(sb + R_V1, r2), sb + R_VT + 1024, 4096, mapa(VBAR, r2));
    }
    __syncwarp();
  };
  auto window = [&](auto G_, auto KIND_) {
    constexpr int G = decltype(G_)::value;
    constexpr bool FIRST = decltype(KIND_)::value == 0;
    const uint32_t rF = pin(rF_), rP = pin(rP_);
    float d[16];
    const uint32_t dlo = pin(((sb + R_XT) >> 4) | 0x10000);
    const uint32_t wqS = rP + R_WQ + G * (20 - NPQ) * 2048;
    uint4 y[5];
    unsigned long long zr = 0;
    const uint32_t t = w * 32 + ((rF - sb) >> 4);
    if (G == 0) zr = swap0(red + (rb_b(s + 2) + zoff + rb_j(t >> 4) + (t & 15) * 8));
    if (G == 0) {
      if (!FIRST && w == 3) {
        if (elect()) {
          mbar_expect(SBAR, 3072); mbar_expect(OBAR, 2048); mbar_expect(VBAR, 8192);
          asm volatile("mbarrier.arrive.relaxed.cluster.shared::cluster.b64 _, [%0];" ::"r"(mapa(FBAR, r1)) : "memory");
          asm volatile("mbarrier.arrive.relaxed.cluster.shared::cluster.b64 _, [%0];" ::"r"(mapa(FBAR, r2)) : "memory");
        }
        __syncwarp();
      }
    }
    auto qpre = [&]() {
      const uint4* qp = g_Ql + ((head * 2 + G) * 4 + w) * 384 + ((rF - sb) >> 4);
#pragma unroll
      for (int f = 0; f < QE; f++)
        asm volatile("{.reg .pred p; setp.eq.s32 p, %5, %6; @p ld.relaxed.gpu.global.v4.u32 {%0,%1,%2,%3}, [%4];}"
                     : "+r"(wqt[f][0]), "+r"(wqt[f][1]), "+r"(wqt[f][2]), "+r"(wqt[f][3]) : "l"(qp + f * 32), "r"(s), "n"(NSEG - 2) : "memory");
    };
    const unsigned char* yp = red + (rb_b(s) + rb_j(t >> 3) + (t & 7) * 16);
    auto poll = [&]() {
      TR(10);
      spin_until(t0, PD);
#pragma unroll
      for (int q = 0; q < 5; q++) y[q] = ldg_rlx128(yp + rb_q(G * 5 + q));
      TR(9);
      sched_fence(sb);
    };
    constexpr int WS = FIRST || G == 1 ? 40 : WSPLIT;
    if (!FIRST && G == 0) {
#pragma unroll
      for (int f = 0; f < NQ_WIN; f++) ldsm4t(wqt[f], wqS + f * 2048);
      qpre();
      asm volatile("" : "+l"(yp));
      mbar_wait(XBAR, (s + 1) & 1);
      if (WS) spin_until(t0, WD);
    } else {
      mbar_wait(XBAR, (s + 1) & 1);
    }
    TR(11);
    if (WS == 0) { poll(); spin_until(t0, WD); }
    wg_fence();
    wgmma_rs32<0>(d, ww[0], XDESC(0));
#pragma unroll
    for (int j = 1; j < WS; j++) wgmma_rs32<1>(d, ww[j], XDESC(j));
    if (FIRST) {
      const unsigned short* m = (const unsigned short*)mem0 + (t & 1) * 4 * DM + G * 320 + (t >> 1);
#pragma unroll
      for (int q = 0; q < 5; q++) y[q] = make_uint4(m[q * 64], m[q * 64 + DM], m[q * 64 + 2 * DM], m[q * 64 + 3 * DM]);
    } else if (G == 0 && WS) {
      poll();
    }
#pragma unroll
    for (int j = WS ? WS : 1; j < 40; j++) wgmma_rs32<1>(d, ww[j], XDESC(j));
    wg_commit();
    if (!FIRST && G == 1) {
      asm volatile("" : "+l"(yp));
      if (PEARLY && (VBULK != 4 || w != VBW)) poll();
      mbar_wait(FBAR, s & 1);
#pragma unroll
      for (int f = 0; f < NQ_W1; f++) ldsm4t(wqt[f], wqS + f * 2048);
      qpre();
      if (w == 1) {
        if (elect()) {
          bulk_wait0();
          asm volatile("red.relaxed.gpu.global.add.u32 [%0], 1;" ::"l"(&g_segcnt[s]) : "memory");
          asm volatile("red.relaxed.gpu.global.add.u32 [%0], 1;" ::"l"(&g_prog) : "memory");
          if (s == NSEG - 2) {
            asm volatile("fence.proxy.async.global;" ::: "memory");
#pragma unroll 1
            for (int b = 0; b < 6; b++)
              tma_load2(sb + b * 10240 + 5120, b < 3 ? &tmK : &tmV, head * DH + (b % 3) * 64, (NSEG - 3) * LK, sb + R_EB + (b / 3) * 8);
          }
        }
        __syncwarp();
      }
    }
    if (FIRST) asm volatile("barrier.cluster.wait.acquire.aligned;" ::: "memory");
    wg_wait0();
    fence_regs<16>(d);
    TR(13);
    bar_arrive(8 + G, 256);
    if (!FIRST && G == 1 && !PEARLY && (VBULK != 4 || w != VBW)) poll();
    {
      uint32_t pk[8];
#pragma unroll
      for (int q = 0; q < 8; q++) pk[q] = pack2(d[2 * q], d[2 * q + 1]);
      stsm4t(rP + (G == 1 ? R_VT : R_KT) + 1024, pk[0], pk[1], pk[2], pk[3]);
      stsm4t(rP + (G == 1 ? R_VT : R_KT) + 3072, pk[4], pk[5], pk[6], pk[7]);
      if (G == 1 && VBULK) {
        if (VBULK == 1) fence_async_smem();
        if (VBULK == 1 || VBULK == 4) {
          if (w != VBW) bar_arrive(6, 128);
          else {
            bar_sync(6, 128);
            vsend();
            if (VBULK == 4 && !FIRST) poll();
          }
        }
      } else if (G == 1) {
        const uint32_t e1 = mapa(rF + R_V1 + 4096 + w * 512, r1), e2 = mapa(rF + R_V1 + w * 512, r2), b1 = mapa(VBAR, r1), b2 = mapa(VBAR, r2);
        st_async4(e1, pk[0], pk[1], pk[2], pk[3], b1);
        st_async4(e2, pk[0], pk[1], pk[2], pk[3], b2);
        st_async4(e1 + 2048, pk[4], pk[5], pk[6], pk[7], b1);
        st_async4(e2 + 2048, pk[4], pk[5], pk[6], pk[7], b2);
      }
    }
    if (FIRST) {
      mbar_wait(WBAR + 16, 0);
      if (G == 0 && cta) GTR(11);
      const uint32_t woA = rW_;
      float na[4] = {0.f, 0.f, 0.f, 0.f}, nb[4] = {0.f, 0.f, 0.f, 0.f};
#pragma unroll
      for (int ks = 0; ks < 12; ks++) {
        uint32_t a[4], b[4];
        ldsm4t(a, woA + WOFF(ks));
        ldsm4t(b, (two ? woA ^ 32 : woA) + WOFF(ks));
#pragma unroll
        for (int q = 0; q < 4; q++) { a[q] &= 0x7fff7fffu; b[q] &= 0x7fff7fffu; }
        mma16816(na, a, ONES, ONES);
        mma16816(nb, b, ONES, ONES);
      }
      const uint32_t mo = __reduce_max_sync(~0u, __float_as_uint(fmaxf(fmaxf(na[0], na[2]), fmaxf(nb[0], nb[2]))));
      if (rF == sb) smax32(sb + R_MI + 56, mo);
      __syncthreads();
      if (G == 1 && w == 2) {
        const uint4 r = lds128(sb + R_MI + 48);
        const uint32_t epoch = lds32(sb + R_MI);
        if (rF == sb) stg_rlx64(&g_rec[cta], (r.y & 0xffff0000u) | (epoch & 0xffffu), ((r.x + 0xffffu) & 0xffff0000u) | ((r.z + 0xffffu) >> 16));
      }
    }
#pragma unroll
    for (int f = FIRST ? 0 : (G == 1 ? NQ_W1 : NQ_WIN); f < NQ; f++) ldsm4t(wqt[f], wqS + f * 2048);
    if (FIRST || DFENCE) sched_fence(sb);
    TR(14);
    const uint32_t ma = sb + R_MEM + G * 5120 + t * 8;
    if (FIRST) {
      bar_sync(9 - G, 256);
#pragma unroll
      for (int j = 0; j < 5; j++) sts64(ma + j * 1024, y[j].x | (y[j].y << 16), y[j].z | (y[j].w << 16));
    } else {
      int n = 0;
#pragma unroll 1
      while (!__all_sync(~0u, (y[0].y & y[0].w & y[1].y) & (y[1].w & y[2].y & y[2].w) & (y[3].y & y[3].w & y[4].y) & (y[4].w & 4))) {
#pragma unroll
        for (int j = 0; j < 5; j++) if (!(y[j].y & y[j].w & 4)) y[j] = ldg_rlx128(yp + rb_q(G * 5 + j));
        if (++n > SPIN_MAX) { g_err = 5; break; }
      }
      const uint32_t bias = 0x80000000u + (sb >> 31);
      bar_sync(9 - G, 256);
#pragma unroll
      for (int j = 0; j < 5; j++) sts64(ma + j * 1024, dec_pair(y[j].x, y[j].y, bias), dec_pair(y[j].z, y[j].w, bias));
    }
    if (G == 0 && zr == ~0ull) g_err = 9;
    TR(0);
  };

  auto oproj = [&](auto TWO_, auto NPRE_, auto& wot, const uint32_t rF, const uint32_t woA, const uint32_t woB,
                   float sm0, float sm1, bool have_sums) {
    constexpr bool TWO = decltype(TWO_)::value;
    constexpr int NPRE = decltype(NPRE_)::value;
    float c[4][4];
#pragma unroll
    for (int q = 0; q < 4; q++) c[q][0] = c[q][1] = c[q][2] = c[q][3] = 0.f;
    unsigned char* sp = red + (rb_b(s) + toff + ((rF - sb) & 256) + (((rF - sb) >> 1) & 120));
    bar_sync(3, 256);
    TR(8);
    uint4 ob[6];
    ob[0] = lds128(rF + R_QB); ob[1] = lds128(rF + R_QB + 512);
    const float2 su = lds64f(sb + R_MI + 48);
    if (!have_sums) { const float2 t = lds64f(sb + R_MI + 16 + (((rF - sb) >> 1) & 24)); sm0 = t.x; sm1 = t.y; }
#pragma unroll
    for (int p = 0; p < 6; p++) {
      if (p + 2 < 6) ob[p + 2] = lds128(rF + (p < 2 ? R_QA : R_O2) + (p & 1) * 512);
#pragma unroll
      for (int e = 0; e < 2; e++) {
        const int ks = 2 * p + e;
        const uint32_t b0 = e ? ob[p].z : ob[p].x, b1 = e ? ob[p].w : ob[p].y;
        if (TWO) {
          const int iA = 2 * ks, iB = iA + 1;
          mma16816(c[e], wot[iA % NPRE], b0, b1);
          if (iA + NPRE < 24) ldsm4t(wot[iA % NPRE], woA + WOFF((iA + NPRE) >> 1));
          mma16816(c[2 + e], wot[iB % NPRE], b0, b1);
          if (iB + NPRE < 24) ldsm4t(wot[iB % NPRE], woB + WOFF((iB + NPRE) >> 1));
        } else {
          mma16816(c[ks & 3], wot[ks], b0, b1);
        }
      }
    }
    const float f0 = su.x * rcp(sm0), f1 = su.x * rcp(sm1);
    t0 = clk32() + (TWO ? (have_sums ? -PDT : 0) : PDS);
    u = su.y;
    if (TWO) {
      red_pair(sp, (c[0][0] + c[1][0]) * f0, (c[0][1] + c[1][1]) * f1);
      red_pair(sp + rb_j(2), (c[0][2] + c[1][2]) * f0, (c[0][3] + c[1][3]) * f1);
      red_pair(sp + rb_j(4), (c[2][0] + c[3][0]) * f0, (c[2][1] + c[3][1]) * f1);
      red_pair(sp + rb_j(6), (c[2][2] + c[3][2]) * f0, (c[2][3] + c[3][3]) * f1);
    } else {
      red_pair(sp, ((c[0][0] + c[1][0]) + (c[2][0] + c[3][0])) * f0, ((c[0][1] + c[1][1]) + (c[2][1] + c[3][1])) * f1);
      red_pair(sp + rb_j(2), ((c[0][2] + c[1][2]) + (c[2][2] + c[3][2])) * f0, ((c[0][3] + c[1][3]) + (c[2][3] + c[3][3])) * f1);
    }
    TR(15);
  };

  auto step = [&](auto G_, auto LAST_) {
    constexpr int G = decltype(G_)::value;
    constexpr bool LAST = decltype(LAST_)::value;
    __syncthreads();
    const uint32_t rF = pin(rF_), rP = pin(rP_);
    TR(1);
    if (LAST) {
      const uint32_t l = (rF - sb) >> 4;
      uint4* qp = g_Ql + ((head * 2 + G) * 4 + w) * 384 + l;
      if (!dry && (int)lds32(sb + R_MI + 4) < 0) {
#pragma unroll 1
        for (int i = 0; i < 48; i++) {
          const bf16* xr = x + (size_t)(S_TOK - 128 + G * 64 + w * 16 + (l >> 2) + (i & 1) * 8) * DM;
          const uint32_t* wr = (const uint32_t*)(Wq + head * DH + (i >> 2) * 16 + (l & 3) * 2 + (i & 2) * 4);
          float a0 = 0.f, a1 = 0.f;
#pragma unroll 1
          for (int k = 0; k < DM; k++) {
            const float xv = __bfloat162float(xr[k]);
            const uint32_t wv = wr[k * (HD / 2)];
            a0 = fmaf(xv, bf_lo(wv), a0); a1 = fmaf(xv, bf_hi(wv), a1);
          }
          ((uint32_t*)(qp + (i >> 2) * 32))[i & 3] = pack2(a0, a1);
        }
#pragma unroll
        for (int f = 0; f < QE; f++) { const uint4 t = ldg_rlx128(qp + f * 32); wqt[f][0] = t.x; wqt[f][1] = t.y; wqt[f][2] = t.z; wqt[f][3] = t.w; }
      }
#pragma unroll
      for (int f = QE; f < 12; f++) { const uint4 t = ldg_rlx128(qp + f * 32); wqt[f][0] = t.x; wqt[f][1] = t.y; wqt[f][2] = t.z; wqt[f][3] = t.w; }
      const float* gp = g_gate + (S_TOK - 128) + G * 64 + w * 16 + ((rF - sb) >> 6);
      wqp[0][0] = ldg_rlx32(gp); wqp[0][1] = ldg_rlx32(gp + 8);
      if (G == 1 && w == 1) {
        if (!dry) mbar_wait(VBAR, (NSEG - 1) & 1);
        if (!dry && elect()) {
          asm volatile("mbarrier.arrive.relaxed.cluster.shared::cluster.b64 _, [%0];" ::"r"(mapa(sb + R_EB + 32, r1)) : "memory");
          asm volatile("mbarrier.arrive.relaxed.cluster.shared::cluster.b64 _, [%0];" ::"r"(mapa(sb + R_EB + 32, r2)) : "memory");
          asm volatile("fence.proxy.async.global;" ::: "memory");
#pragma unroll 1
          for (int b = 0; b < 5; b++)
            tma_load2(sb + (b < 3 ? E_KB + b * 10240 : (b == 3 ? E_VB0 : E_VB1)), b < 3 ? &tmK : &tmV, head * DH + (b % 3) * 64, (NSEG - 2) * LK,
                      sb + R_EB + 16 + (b / 3) * 8);
        }
        __syncwarp();
      }
    }
    const uint32_t wqS = rP + R_WQ + G * (20 - NPQ) * 2048, rM = rF + R_MEM;
    const uint32_t l8 = sb + ((rF - sb) >> 1) + w * 256;
    const uint32_t woA = pin(rW_), woB = woA ^ 32;
    float aq[2][4] = {};
    const uint32_t ln = (rF - sb) >> 4;
    const uint32_t rS = sb + (ln & 7) * 128 + (ln < 16 ? R_QB + (ln & 8) * 128 + (((2 * w + G) ^ (ln & 7)) << 4) : R_KT + (((2 * w + ((ln >> 3) & 1)) ^ (ln & 7)) << 4));
    auto qmma = [&](int f, uint32_t b0, uint32_t b1) {
      if (f < NPQ) mma16816(aq[f & 1], wqp[f], b0, b1);
      else {
        const int slot = (f - NPQ) % NQ;
        mma16816(aq[f & 1], wqt[slot], b0, b1);
        if (f + NQ < 20) ldsm4t(wqt[slot], wqS + (f - NPQ + NQ) * 2048);
      }
    };
    if constexpr (G == 1) {
      uint32_t bb[20][4];
      if (!LAST) {
        if (VBULK == 2 && w == VBW) vsend();
        ldsm4t(bb[10], rM + 5120);
        ldsm4t(bb[11], rM + 5632);
#pragma unroll
        for (int i = 10; i < 20; i++) {
          if (i + 2 < 20) ldsm4t(bb[i + 2], rM + (i + 2) * 512);
          qmma(2 * i - 20, bb[i][0], bb[i][1]);
          qmma(2 * i - 19, bb[i][2], bb[i][3]);
        }
        stsm2t(rS, pack2(aq[0][0] + aq[1][0], aq[0][1] + aq[1][1]), pack2(aq[0][2] + aq[1][2], aq[0][3] + aq[1][3]));
        bar_arrive(1, 256);
        if (VBULK == 3 && w == VBW) vsend();
      }
      TR(2);
      float av[4][4] = {};
      uint32_t m0 = 0, m1 = 0;
      auto vmma = [&](auto MAX_) {
#pragma unroll
        for (int n = 0; n < 20; n++) {
          const int i = (n + 10) % 20;
          if (LAST && n < 8) ldsm4t(bb[(n + 10) % 20], rM + ((n + 10) % 20) * 512);
          if (LAST && n == 0) { ldsm4t(bb[18], rM + 18 * 512); ldsm4t(bb[19], rM + 19 * 512); }
          if (n == VB && !LAST) { bar_sync(5, 256); sched_fence(sb); }
          if (n == VLD) {
            if (VB != VLD && !LAST) sched_fence(sb);
#pragma unroll
            for (int q = 0; q < 10; q++) ldsm4t(bb[q], rM + q * 512);
            if (!LAST) sched_fence(sb);
          }
          mma16816(av[(2 * n) & 3], ww[2 * i], bb[i][0], bb[i][1]);
          mma16816(av[(2 * n + 1) & 3], ww[2 * i + 1], bb[i][2], bb[i][3]);
          if (decltype(MAX_)::value) { m0 = hmaxabs2(m0, hmaxabs2(bb[i][0], bb[i][1])); m1 = hmaxabs2(m1, hmaxabs2(bb[i][2], bb[i][3])); }
        }
      };
      auto vout = [&]() {
        const uint32_t vm0 = pack2(((av[0][0] + av[1][0]) + (av[2][0] + av[3][0])) * u, ((av[0][1] + av[1][1]) + (av[2][1] + av[3][1])) * u);
        const uint32_t vm1 = pack2(((av[0][2] + av[1][2]) + (av[2][2] + av[3][2])) * u, ((av[0][3] + av[1][3]) + (av[2][3] + av[3][3])) * u);
        if (!LAST) {
          st_async2(mapa(l8 + R_VM + 1024, r1), vm0, vm1, mapa(OBAR, r1));
          st_async2(mapa(l8 + R_VM, r2), vm0, vm1, mapa(OBAR, r2));
          sts64(l8 + R_VS, vm0, vm1);
          __syncwarp();
          if (rF == sb) mbar_arrive(OBAR);
        }
        stsm2t(rP + R_VT, vm0, vm1);
      };
      if (LAST) {
        vmma(std::false_type{});
        vout();
        return;
      }
      uint32_t wot[NW1][4];
      auto wpre = [&](int i0, int i1) {
#pragma unroll
        for (int i = i0; i < i1; i++) ldsm4t(wot[i], ((i & 1) ? woB : woA) + WOFF(i >> 1));
      };
      if (w != 1) {
        vmma(std::false_type{});
        bar_arrive(7, 128);
        vout();
        bar_arrive(2, 128);
        TR(5);
        wpre(0, NW1A);
      } else {
        vmma(std::true_type{});
        bar_sync(7, 128);
        if (elect()) { mbar_expect(XBAR, 40960); tma_load3(sb + R_XT, &tmX, 0, (s + 1) * SEG, 0, XBAR); }
        __syncwarp();
        vout();
        if (XPF && s + XPF < NSEG && rF - sb < 64 && cta < 80) prefetch_l2(x + (size_t)(s + XPF) * SEG * DM + cta * 256 + (rF - sb) * 4);
        TR(5);
        m0 = hmaxabs2(m0, m1);
        const uint32_t mx = __reduce_max_sync(~0u, max((m0 << 16) & 0x7fffffffu, m0 & 0x7fff0000u));
        const float2 mi = lds64f(sb + R_MI + 8);
        wpre(0, NW1A);
        bar_sync(2, 128);
        if (elect()) {
          fence_async_smem();
          tma_store2(&tmK, sb + R_KT, D0, s * LK);
          tma_store2(&tmV, sb + R_VT, D0, s * LK);
          bulk_commit();
        }
        __syncwarp();
        float wb = mi.x, xm = mi.y;
        if (s == 0) {
          const uint32_t epoch = lds32(sb + R_MI);
          uint32_t av_ = 0, ao = 0, xi = 0;
#pragma unroll 1
          for (int j = 0; j < 3; j++) {
            uint2 r;
            int n = 0;
#pragma unroll 1
            while (true) {
              r = ldg_rlx64(&g_rec[j * 32 + ((rF - sb) >> 4)]);
              if (((r.x ^ epoch) & 0xffffu) == 0) break;
              if (++n > SPIN_MAX) { g_err = 6; break; }
            }
            av_ = max(av_, r.y & 0xffff0000u); ao = max(ao, r.y << 16); xi = max(xi, r.x & 0xffff0000u);
          }
          av_ = __reduce_max_sync(~0u, av_); ao = __reduce_max_sync(~0u, ao); xi = __reduce_max_sync(~0u, xi);
          wb = __uint_as_float(av_) * __uint_as_float(ao) * 33.f; xm = __uint_as_float(xi);
          if (rF == sb) {
            sts64f(sb + R_MI + 8, wb, xm);
            asm volatile("fence.acq_rel.gpu;\nred.relaxed.gpu.global.add.u32 [%0], 1;" ::"l"(&g_cnt[C_GATE * 8]) : "memory");
          }
          __syncwarp();
        }
        const float hm = fmaxf(__uint_as_float(mx) * u, xm);
        const uint32_t eb = min(max(__float_as_uint(hm * wb) >> 23, 40u), 200u);
        if (rF == sb) sts64(sb + R_MI + 48, (280u - eb) << 23, (eb - 29u) << 23);
        if (elect()) bulk_wait_read0();
        __syncwarp();
      }
      if (NW1A < NW1) {
        bar_sync(4, 256);
        wpre(NW1A, NW1);
      }
      TR(6);
      oproj(std::true_type{}, std::integral_constant<int, NW1>{}, wot, rF, woA, woB, 0.f, 0.f, false);
    } else {
      {
        uint32_t bb[20][4];
        float ak[4][4] = {};
        ldsm4t(bb[0], rM);
        ldsm4t(bb[10], rM + 5120);
#pragma unroll
        for (int i = 0; i < 10; i++) {
          if (i + 1 < 10) { ldsm4t(bb[i + 1], rM + (i + 1) * 512); ldsm4t(bb[i + 11], rM + (i + 11) * 512); }
          mma16816(ak[0], ww[2 * i], bb[i][0], bb[i][1]);
          if (!LAST) qmma(2 * i, bb[i][0], bb[i][1]);
          mma16816(ak[1], ww[2 * i + 1], bb[i][2], bb[i][3]);
          if (!LAST) qmma(2 * i + 1, bb[i][2], bb[i][3]);
          mma16816(ak[2], ww[2 * i + 20], bb[i + 10][0], bb[i + 10][1]);
          mma16816(ak[3], ww[2 * i + 21], bb[i + 10][2], bb[i + 10][3]);
        }
#pragma unroll
        for (int q = 0; q < 4; q++) { ak[0][q] += ak[2][q]; ak[1][q] += ak[3][q]; }
        stsm4t(rS, pack2(aq[0][0] + aq[1][0], aq[0][1] + aq[1][1]), pack2(aq[0][2] + aq[1][2], aq[0][3] + aq[1][3]),
               pack2((ak[0][0] + ak[1][0]) * u, (ak[0][1] + ak[1][1]) * u), pack2((ak[0][2] + ak[1][2]) * u, (ak[0][3] + ak[1][3]) * u));
      }
      if (LAST) return;
      bar_sync(1, 256);
      if (!B5LATE) bar_arrive(5, 256);
      TR(2);
      if (w != 3) {
        uint32_t qa[4][4], kk[4][4];
        float x[4][4] = {};
#pragma unroll
        for (int i = 0; i < 4; i++) { ldsm4(qa[i], (rP ^ (i << 5)) + R_QB); ldsm4(kk[i], ((rP ^ (i << 5)) + w * 2048) + R_KT); }
        const uint32_t dst = rF + R_SX + rank * 1536 + w * 512;
        const uint32_t e1 = mapa(dst, r1), e2 = mapa(dst, r2), s1 = mapa(SBAR, r1), s2 = mapa(SBAR, r2);
#pragma unroll
        for (int i = 0; i < 4; i++) { mma16816(x[i & 1], qa[i], kk[i][0], kk[i][1]); mma16816(x[2 + (i & 1)], qa[i], kk[i][2], kk[i][3]); }
        const uint32_t u0 = __float_as_uint((x[0][0] + x[0][2]) + (x[1][0] + x[1][2])), u1 = __float_as_uint((x[0][1] + x[0][3]) + (x[1][1] + x[1][3]));
        const uint32_t u2 = __float_as_uint((x[2][0] + x[2][2]) + (x[3][0] + x[3][2])), u3 = __float_as_uint((x[2][1] + x[2][3]) + (x[3][1] + x[3][3]));
        st_async4(e1, u0, u1, u2, u3, s1);
        st_async4(e2, u0, u1, u2, u3, s2);
        sts128(dst, u0, u1, u2, u3);
        __syncwarp();
        if (rF == sb) mbar_arrive(SBAR);
      } else if (s == NSEG - 2) {
        sts32(sb + R_MI + 4, ldg_rlx32(&g_cnt[(C_O + 240 + (head >> 1)) * 8]) - lds32(sb + R_MI) * 2);
        asm volatile("fence.acquire.gpu; fence.proxy.async.global;" ::: "memory");
        if (elect()) {
#pragma unroll 1
          for (int b = 0; b < 6; b++)
            tma_load2(sb + b * 10240, b < 3 ? &tmK : &tmV, head * DH + (b % 3) * 64, (NSEG - 4) * LK, sb + R_EB + (b / 3) * 8);
        }
        __syncwarp();
      }
      if (B5LATE) bar_arrive(5, 256);
      TR(4);
      mbar_wait(VBAR, s & 1);
      uint32_t wot[12][4], va[3][8];
      ldsm4t(va[0], rP + R_VT + 1024); ldsm4t(va[0] + 4, rP + R_VT + 3072);
#pragma unroll
      for (int q = 0; q < 4; q++) {
        if (VBULK) { ldsm4t(va[1 + (q >> 1)] + (q & 1) * 4, rP + R_V1 + q * 2048); continue; }
        const uint4 t = lds128(rF + R_V1 + w * 512 + q * 2048);
        uint32_t* v = va[1 + (q >> 1)] + (q & 1) * 4;
        v[0] = t.x; v[1] = t.y; v[2] = t.z; v[3] = t.w;
      }
      auto wpre = [&](int i0, int i1) {
        if (two) {
#pragma unroll
          for (int i = i0; i < i1; i++) ldsm4t(wot[i], ((i & 1) ? woB : woA) + WOFF(i >> 1));
        } else {
#pragma unroll
          for (int i = i0; i < i1; i++) ldsm4t(wot[i], woA + WOFF(i));
        }
      };
      wpre(0, NO_EARLY);
      const uint32_t dst = rF + (w >> 1) * 512 + (w & 1) * 8;
      const float scl = u * (0.07216878364870322f * 1.4426950408889634f);
      mbar_wait(SBAR, s & 1);
      TR(6);
      float sc[10];
      {
        const float4 a0 = lds128f(rF + R_SX), b0 = lds128f(rF + R_SX + 1536), c0 = lds128f(rF + R_SX + 3072);
        const float4 a1 = lds128f(rF + R_SX + 512), b1 = lds128f(rF + R_SX + 2048), c1 = lds128f(rF + R_SX + 3584);
        const float2 a2 = lds64f(rF + R_SX + 1024), b2 = lds64f(rF + R_SX + 2560), c2 = lds64f(rF + R_SX + 4096);
        sc[8] = a0.x + b0.x + c0.x; sc[9] = a0.y + b0.y + c0.y; sc[0] = a0.z + b0.z + c0.z; sc[1] = a0.w + b0.w + c0.w;
        sc[2] = a1.x + b1.x + c1.x; sc[3] = a1.y + b1.y + c1.y; sc[4] = a1.z + b1.z + c1.z; sc[5] = a1.w + b1.w + c1.w;
        sc[6] = a2.x + b2.x + c2.x; sc[7] = a2.y + b2.y + c2.y;
      }
      float mx = fmaxf(fmaxf(fmaxf(sc[0], sc[1]), fmaxf(sc[2], sc[3])), fmaxf(fmaxf(sc[4], sc[5]), fmaxf(sc[6], sc[7])));
      mx = fmaxf(mx, fmaxf(sc[8], sc[9]));
      mx = fmaxf(mx, __shfl_xor_sync(~0u, mx, 1));
      const bool vok = mbar_test(OBAR, s & 1);
      mx = fmaxf(mx, __shfl_xor_sync(~0u, mx, 2));
      if (NW1A < NW1) bar_arrive(4, 256);
      const float mo = mx * scl;
      uint32_t pb[5];
#pragma unroll
      for (int j = 0; j < 5; j++) pb[j] = pack2(ex2(fmaf(sc[2 * j], scl, -mo)), ex2(fmaf(sc[2 * j + 1], scl, -mo)));
      if (!vok) mbar_wait(OBAR, s & 1);
      const uint2 m0 = lds64(l8 + R_VS), m1 = lds64(l8 + R_VM), m2 = lds64(l8 + R_VM + 1024);
      const uint32_t ones[4] = {ONES, ONES, ONES, ONES};
      float o[3][4], o2[3][4], sm[4] = {0.f, 0.f, 0.f, 0.f}, sn[4] = {0.f, 0.f, 0.f, 0.f}, so[4] = {0.f, 0.f, 0.f, 0.f};
#pragma unroll
      for (int b = 0; b < 3; b++) {
        o[b][0] = o[b][1] = o[b][2] = o[b][3] = o2[b][0] = o2[b][1] = o2[b][2] = o2[b][3] = 0.f;
        mma16816(o[b], va[b], pb[0], pb[1]);
      }
#pragma unroll
      for (int b = 0; b < 3; b++) mma16816(o2[b], va[b] + 4, pb[2], pb[3]);
      mma1688(o[0], m0.x, m0.y, pb[4]);
      mma1688(o[1], m1.x, m1.y, pb[4]);
      mma1688(o[2], m2.x, m2.y, pb[4]);
      mma16816(sm, ones, pb[0], pb[1]);
      mma16816(sn, ones, pb[2], pb[3]);
      mma1688(so, ONES, ONES, pb[4]);
      wpre(NO_EARLY, NO_MID);
#pragma unroll
      for (int b = 0; b < 3; b++)
        sts64(dst + (b == 0 ? R_QB : (b == 1 ? R_QA : R_O2)), movmat(pack2(o[b][0] + o2[b][0], o[b][1] + o2[b][1])),
              movmat(pack2(o[b][2] + o2[b][2], o[b][3] + o2[b][3])));
      sm[0] += sn[0] + so[0]; sm[1] += sn[1] + so[1];
      if (rF - sb < 64) sts64f(sb + R_MI + 16 + ((rF - sb) >> 1), sm[0], sm[1]);
      wpre(NO_MID, 12);
      TR(7);
      if (two) oproj(std::true_type{}, std::integral_constant<int, 12>{}, wot, rF, woA, woB, sm[0], sm[1], true);
      else oproj(std::false_type{}, std::integral_constant<int, 12>{}, wot, rF, woA, woB, sm[0], sm[1], true);
    }
  };

  if (g == 0) {
    if (!dry) {
    window(std::integral_constant<int, 0>{}, std::integral_constant<int, 0>{});
    GTR(7);
#pragma unroll 1
    for (s = 0; s < NSEG - 1; s++) {
      step(std::integral_constant<int, 0>{}, std::false_type{});
      window(std::integral_constant<int, 0>{}, std::integral_constant<int, 1>{});
    }
    }
    step(std::integral_constant<int, 0>{}, std::true_type{});
  } else {
    if (!dry) {
    window(std::integral_constant<int, 1>{}, std::integral_constant<int, 0>{});
#pragma unroll 1
    for (s = 0; s < NSEG - 1; s++) {
      step(std::integral_constant<int, 1>{}, std::false_type{});
      window(std::integral_constant<int, 1>{}, std::integral_constant<int, 1>{});
    }
    }
    step(std::integral_constant<int, 1>{}, std::true_type{});
  }
  fence_async_smem();
  __syncthreads();
  if (!dry) GTR(8);
#define CG(i) do {} while (0)
  if (wid == 5) {
    if (elect()) {
      const uint32_t kd = sb + E_KB + rank * 10240 + 5120, vd = sb + (rank == 0 ? E_VB0 : (rank == 1 ? E_VB1 : E_VB2)) + 5120;
      if (rank != 2 && !dry) asm volatile("mbarrier.arrive.relaxed.cluster.shared::cluster.b64 _, [%0];" ::"r"(mapa(sb + R_EB + 40, 2)) : "memory");
      if (!dry) mbar_wait(sb + R_EB + 32, 0);
#pragma unroll 1
      for (uint32_t r = 0; r < 3; r++) if (!dry) bulk_s2s(mapa(kd, r), sb + R_KT, 5120, mapa(sb + R_EB + 16, r));
      if (!dry) tma_load2(sb + E_VB2, &tmV, head * DH + 128, (NSEG - 2) * LK, sb + R_EB + 24);
      if (rank == 2 && !dry) mbar_wait(sb + R_EB + 40, 0);
#pragma unroll 1
      for (uint32_t r = 0; r < 3; r++) if (!dry) bulk_s2s(mapa(vd, r), sb + R_VT, 5120, mapa(sb + R_EB + 24, r));
      if (!dry) asm volatile("red.relaxed.gpu.global.add.u32 [%0], 1;" ::"l"(&g_prog) : "memory");
    }
    __syncwarp();
  }
  {
    const uint32_t kb = sb + (g ? E_KB : E_KA);
    float sc[40] = {};
    uint32_t pf[5][4];
    if (!dry) mbar_wait(sb + R_EB + g * 16, 0);
    CG(11);
    wg_fence();
#pragma unroll
    for (int ks = 0; ks < 12; ks++) wgmma_rs80(sc, wqt[ks], mk_desc(kb, 16, 1024, 1) + (((ks >> 2) * 10240 + (ks & 3) * 32) >> 4), ks);
    wg_commit();
    const AttMask am(tid, sb);
    wg_wait0();
    fence_regs<40>(sc);
    CG(12);
    att_softmax(am, sc, pf, __uint_as_float(wqp[0][0]), __uint_as_float(wqp[0][1]));
    float o[96] = {};
    if (!dry) mbar_wait(sb + R_EB + g * 16 + 8, 0);
    CG(13);
    wg_fence();
#pragma unroll
    for (int b = 0; b < 3; b++) {
      const Desc db = mk_desc(sb + (g ? (b == 0 ? E_VB0 : (b == 1 ? E_VB1 : E_VB2)) : E_VA + b * 10240), 1024, 1024, 1);
#pragma unroll
      for (int ks = 0; ks < 5; ks++) wgmma_rs64t(o + 32 * b, pf[ks], db + ks * 128, ks);
    }
    wg_commit();
    wg_wait0();
    fence_regs<96>(o);
    CG(14);
    uint32_t of[12][4];
#pragma unroll
    for (int i = 0; i < 48; i++) asm volatile("cvt.rn.bf16x2.f32 %0, %1, %2;" : "=r"(of[i >> 2][i & 3]) : "f"(o[2 * i + 1]), "f"(o[2 * i]));
    float y[112] = {};
    wg_fence();
#pragma unroll
    for (int j = 0; j < 3; j++) {
      const Desc db = mk_desc((sb & 0x3ffff) + R_WO + ((j + 3 - rank) % 3) * 28672, 4096, 512, 2);
#pragma unroll
      for (int ks = 0; ks < 4; ks++) wgmma_rs224t(y, of[4 * j + ks], db + ks * 64, j + ks);
    }
    wg_commit();
    wg_wait0();
    fence_regs<112>(y);
    CG(15);
    const uint32_t da = kb + (w * 16 + (lane & 15)) * 64, sx = (lane >> 1) & 3;
#pragma unroll
    for (int i = 0; i < 14; i++)
      stsm4(da + (i >> 1) * 4096 + (((2 * (i & 1) + (lane >> 4)) ^ sx) << 4), pack2(y[8 * i], y[8 * i + 1]), pack2(y[8 * i + 2], y[8 * i + 3]),
            pack2(y[8 * i + 4], y[8 * i + 5]), pack2(y[8 * i + 6], y[8 * i + 7]));
    fence_async_smem();
    bar_sync(1 + g, 128);
    if (w == 0 && elect()) {
#pragma unroll 1
      for (int i = 0; i < (rank == 1 ? 6 : 7); i++) if (!dry) tma_red2(&tmOut, kb + i * 4096, tile0 * 16 + i * 32, S_TOK - 128 + g * 64);
      bulk_commit();
      bulk_wait0();
    }
  }
  if (!dry) GTR(9);
}

enum { IT_GATE = 0, IT_QKV = 1, IT_XATT = 2, IT_OUT = 3, IT_BATT = 4, IT_Q = 5, IT_INIT = 6, IT_END = 7 };
constexpr uint32_t NONE = ~0u;
#define HP 0x1224468888888888ull
#define XD 0x4888888888888999ull
#define KREQ 4
#define ADELAY 5000
#define LAG 0
#define W_PRO 11
#define W_SCH 8
#define W_AG1 10
#define KEARLY 1
#define CVTS 6
#define RSL 20
#define PACE 500
#define SPLITW 0
#define XPP 22
#define PEEK 0
#define XFT 16
#define PP 3
__host__ __device__ constexpr uint32_t mk_item(int ty, int t, int a, int b = 0, int c = 0) { return ty | (t << 3) | (a << 8) | (b << 16) | (c << 24); }
struct ItemTab { uint32_t v[1280]; int n; };
constexpr ItemTab make_items() {
  ItemTab T{};
  int n = 0;
  for (int a = 0; a < 16; a++) T.v[n++] = mk_item(IT_Q, 15, a);
  for (int t = 0; t < 16; t++) for (int a = 0; a < 5; a++) T.v[n++] = mk_item(IT_QKV, t, a);
  for (int t = 0; t < 32; t++) T.v[n++] = mk_item(IT_BATT, t, 0);
  for (int t = 0; t < 16; t++) for (int a = 0; a < 2; a++) T.v[n++] = mk_item(IT_INIT, t, a);
#define NOOUT 15
  for (int t = 0; t < NOOUT; t++) {
    const int hp = (HP >> 4 * t) & 15;
    for (int h = 0; h < 32; h += hp) for (int a = 0; a < 2; a++) T.v[n++] = mk_item(IT_OUT, t, a, h, h + hp < 32 ? h + hp : 32);
  }
  T.n = n;
  return T;
}
constexpr ItemTab k_items_host = make_items();
constexpr int NITEMS = k_items_host.n;
__constant__ ItemTab c_items = make_items();

#define AUX_GRID 36
constexpr int NST = 7, STG = 32768;
constexpr int A_FULL = NST * STG, A_EMPTY = A_FULL + 64, A_ITEM = A_EMPTY + 64, A_QBAR = A_ITEM + 32, A_QENT = A_QBAR + 128, A_MISC = A_QENT + 256,
              A_SMEM = A_MISC + 64, A_REQ = A_FULL + 56, A_RSP = A_EMPTY + 56, A_MAIL = A_MISC + 48, A_RDY = A_MISC + 32;
static_assert(A_SMEM <= 232448, "smem");
enum { OP_END = 0, OP_O = 1, OP_QKV = 2, OP_OB = 3, OP_SET = 4, OP_ADD = 5, OP_Q = 6 };

struct AuxMaps { CUtensorMap xA, wq, wqkv, wo, wob, k, v, oA, oS, obA, obS, qkvS, qkvQ, qkvK, out; };

__device__ __forceinline__ void mbar_wait_long(uint32_t b, uint32_t par) {
  int n = 0;
#pragma unroll 1
  while (!mbar_try(b, par)) { if (++n > (SPIN_MAX << 4)) { g_err = 8; break; } }
}
__device__ __forceinline__ void mbar_wait_u(uint32_t b, uint32_t par) {
  asm volatile("{.reg .pred p; .reg .u32 n;\nmov.u32 n, 0;\nLW: mbarrier.try_wait.parity.shared::cta.b64 p, [%0], %1;\n@p bra.uni LD;\n"
               "add.u32 n, n, 1;\nsetp.lt.u32 p, n, %2;\n@p bra.uni LW;\nLD:\n}" ::"r"(b), "r"(par), "n"(SPIN_MAX << 4) : "memory");
}
__global__ void __launch_bounds__(384, 1)
aux_kernel(const __grid_constant__ AuxMaps tm) {
  extern __shared__ __align__(1024) unsigned char smem[];
  const uint32_t sb = smem_u32(smem);
  const int tid = threadIdx.x, lane = tid & 31, wid = __shfl_sync(~0u, tid >> 5, 0);
  uint32_t epoch = 0;
  const uint32_t c0 = clk32();
  if (tid == W_SCH * 32) GTA(0);
  if (tid >= 256) epoch = *(volatile uint32_t*)&g_epoch + 1;
  if (tid == 0) {
    mbar_init(sb + A_REQ, 1); mbar_init(sb + A_RSP, 1); mbar_init(sb + A_RDY, 1);
    for (int i = 0; i < NST; i++) { mbar_init(sb + A_FULL + i * 8, 1); mbar_init(sb + A_EMPTY + i * 8, 8); }
    for (int i = 0; i < 16; i++) mbar_init(sb + A_QBAR + i * 8, 4);
    asm volatile("fence.mbarrier_init.release.cluster;" ::: "memory");
    const uint32_t b = blockIdx.x;
    sts128(sb + A_MAIL, b < 16 ? mk_item(IT_Q, 15, b) : mk_item(IT_QKV, (b - 16) / 5, (b - 16) % 5), 1, b, PACE);
    mbar_arrive(sb + A_RSP);
  }
  if (tid < 15) prefetch_map(&tm.xA + tid);
  if (tid == W_SCH * 32) GTA(4);
  __syncthreads();
  if (tid == W_SCH * 32) GTA(5);
  uint32_t st = 0, ph = 0;
  auto advance = [&]() { if (++st == NST) { st = 0; ph ^= 1; } };

  if (wid >= 8) {
    asm volatile("setmaxnreg.dec.sync.aligned.u32 40;");
    if (tid == W_SCH * 32) GTA(6);
    auto cnt = [&](int c, uint32_t per) -> bool { return (int)(ldg_rlx32(&g_cnt[c * 8]) - epoch * per) >= 0; };
    auto ready = [&](uint32_t item) -> int {
      const int ty = item & 7, t = (item >> 3) & 31, b = (item >> 17) & 127, n = (((item >> 24) + 1) >> 1) - b;
      int r;
      if (ty == IT_OUT) {
        const int c = C_O + t * 16 + b;
        const bool r0 = cnt(c, 2), r1 = cnt(c + (n > 1), 2), r2 = cnt(c + (n > 2) * 2, 2), r3 = cnt(c + (n > 3) * 3, 2);
        r = r0 & cnt(C_ACC + t, 4) ? (r1 ? (r2 ? (r3 ? 4 : 3) : 2) : 1) : 0;
      } else if (ty == IT_XATT) {
        const uint4 v = ldg_rlx128(&g_segcnt[4 * t]);
        const uint32_t e = epoch * 96;
        r = ((int)(v.x - e) >= 0) & ((int)(v.y - e) >= 0) & ((int)(v.z - e) >= 0) & ((int)(v.w - e) >= 0);
      } else if (ty == IT_BATT) {
        r = cnt(C_GATE, NGATE) & cnt(C_QKV + (t >> 1), 10) & cnt(C_QKV + (max(t - 1, 0) >> 1), 10);
      } else {
        r = ty <= IT_QKV || ty == IT_Q || cnt(C_OB + t, 8);
      }
      asm volatile("fence.acquire.gpu; fence.proxy.async.global;" ::: "memory");
      return r;
    };
    if (wid == W_SCH && lane == 0) {
      uint32_t pend = NONE;
      bool xleft = true;
      uint32_t nidx = 0, pidx = 0;
#pragma unroll 1
      for (uint32_t e = 1;; e++) {
        mbar_wait_long(sb + A_REQ, (e - 1) & 1);
        uint32_t item = NONE;
        int rdy = 0, spins = 0;
#pragma unroll 1
        while (true) {
          const bool fresh = pend == NONE;
          uint4 c;
          uint32_t pr = 0, head = 0, cand = pend;
          bool gates = false;
          if (xleft) {
            c = ldg_rlx128(&g_queue[0]);
            pr = ldg_rlx32(&g_prog) - (epoch - 1) * (96 * NSEG);
            gates = cnt(C_GATE, NGATE);
            if (PEEK && fresh) { head = ldg_rlx32(&g_queue[32]) + gridDim.x; cand = head < (uint32_t)NITEMS ? c_items.v[head] : (uint32_t)IT_END; }
          }
          auto need = [&](uint32_t it) { return (it & 7) == IT_OUT && xleft ? (((it >> 24) + 1) >> 1) - ((it >> 17) & 127) : 1; };
          if (cand != NONE) rdy = ready(cand);
          int t = 0;
          if (xleft) {
            auto full = [](uint32_t v) { v = (v | (v >> 2)) & 0x30303030u; return __popc((v | (v >> 1)) & 0x10101010u); };
            t = full(c.x) + full(c.y) + full(c.z) + full(c.w);
          }
          if (xleft && (t >= XFT || fresh || pend == IT_END || rdy < need(pend))) {
            xleft = t < 15;
            if (xleft && gates && (int)pr >= 96 * (4 * t - 8 + (int)((XD >> 4 * t) & 15))) {
              const uint32_t j = (atomicAdd(&g_queue[t >> 2], 1u << (t & 3) * 8) >> (t & 3) * 8) & 255;
              if (j < 16) { item = mk_item(IT_XATT, t, j); rdy = 0; nidx = NITEMS + 132 + t * 16 + j; }
            }
          }
          if (item == NONE) {
            if (fresh && (!PEEK || !xleft || rdy >= need(cand))) {
              pidx = atomicAdd(&g_queue[32], 1u) + gridDim.x;
              pend = pidx < (uint32_t)NITEMS ? c_items.v[pidx] : (uint32_t)IT_END;
              if (pend != cand) rdy = ready(pend);
            }
            if (pend != NONE && (pend == IT_END ? !xleft : rdy >= need(pend))) { item = pend; pend = NONE; nidx = pidx; }
          }
          if (item != NONE) break;
          if (++spins > SPIN_MAX) { g_err = 10; item = IT_END; break; }
          __nanosleep(50);
        }
        sts128(sb + A_MAIL, item, rdy, nidx, xleft ? PACE : 0);
        mbar_arrive(sb + A_RSP);
        if (item == IT_END) break;
        if ((item & 7) == IT_XATT) {
#pragma unroll 1
          for (spins = 0; !ready(item); __nanosleep(RSL))
            if (++spins > SPIN_MAX) { g_err = 11; break; }
          mbar_arrive(sb + A_RDY);
        }
      }
      if (atomicAdd(&g_queue[64], 1u) == gridDim.x - 1) { *(uint4*)g_queue = make_uint4(0, 0, 0, 0); g_queue[32] = 0; g_queue[64] = 0; g_epoch = epoch; }
      asm volatile("griddepcontrol.wait;" ::: "memory");
    } else if (wid == W_PRO) {
      uint32_t xph = 0, tl = 0;
      int pace = 0;
      if (ADELAY) spin_until(c0, ADELAY);
      auto arm = [&](uint32_t bytes) -> uint32_t {
        mbar_wait_u(sb + A_EMPTY + st * 8, ph ^ 1);
        if (PACE && bytes) { spin_until(tl, pace); tl = clk32(); }
        return sb + st * STG;
      };
#pragma unroll 1
      for (uint32_t e = 0;; e++) {
        mbar_wait_long(sb + A_RSP, e & 1);
        const uint4 mail = lds128(sb + A_MAIL);
        asm volatile("fence.proxy.async.global;" ::: "memory");
        const uint32_t item = __shfl_sync(~0u, mail.x, 0);
        pace = mail.w;
        const int ty = item & 7, t = (item >> 3) & 31, a = (item >> 8) & 255;
        arm(0);
        if (elect()) {
          sts32(sb + A_ITEM + st * 4, item);
        }
        if (ty == IT_OUT || ty == IT_INIT) {
          const bool out_ = ty == IT_OUT;
          const CUtensorMap *pa = out_ ? &tm.oA : &tm.obA, *pb = out_ ? &tm.wo : &tm.wob;
          int k = out_ ? ((item >> 16) & 255) * 6 : 0;
          const int k1 = out_ ? (item >> 24) * 6 : 20, kreq = max(k1 - KREQ, k);
          int kdep = out_ ? (((item >> 17) & 127) + __shfl_sync(~0u, mail.y, 0)) * 12 : 20;
#pragma unroll 1
          for (; k < k1; k++) {
            if (k >= kdep) {
              int n = 0;
#pragma unroll 1
              while (k >= (kdep = (((item >> 17) & 127) + __shfl_sync(~0u, ready(item), 0)) * 12)) {
                if (++n > SPIN_MAX) { g_err = 7; break; }
                __nanosleep(20);
              }
            }
            PTR((item & 255) == PT && lane == 0, 0, k & 63);
            const uint32_t d = arm(1), fb = sb + A_FULL + st * 8;
            PTR((item & 255) == PT && lane == 0, 1, k & 63);
            if (elect()) {
              mbar_expect(fb, 28672);
              tma_load2(d, pa, k * 32, t * 128, fb);
              tma_load3(d + 8192, pb, 0, k * 32, a * 5, fb);
              if (k == kreq) mbar_arrive(sb + A_REQ);
            }
            PTR((item & 255) == PT && lane == 0, 2, k & 63);
            advance();
          }
        } else if (ty == IT_QKV || ty == IT_XATT || ty == IT_Q) {
          const CUtensorMap* pb = ty == IT_QKV ? &tm.wqkv : &tm.wq;
          const int kreq = ty == IT_XATT ? 28 - KREQ : 20 - KREQ;
#pragma unroll 1
          for (int k = 0; k < 20; k++) {
            PTR((item & 255) == PT && lane == 0, 0, k & 63);
            const uint32_t d = arm(1), fb = sb + A_FULL + st * 8;
            PTR((item & 255) == PT && lane == 0, 1, k & 63);
            if (elect()) {
              mbar_expect(fb, 32768);
              tma_load2(d, &tm.xA, k * 32, t * 128, fb);
              tma_load3(d + 8192, pb, 0, k * 32, a * 6, fb);
              if (k == kreq) mbar_arrive(sb + A_REQ);
            }
            PTR((item & 255) == PT && lane == 0, 2, k & 63);
            advance();
          }
          if (ty == IT_XATT) {
            mbar_wait_long(sb + A_RDY, xph);
            xph ^= 1;
            asm volatile("fence.proxy.async.global;" ::: "memory");
#pragma unroll 1
            for (int k = 20; k < 28; k++) {
              PTR((item & 255) == PT && lane == 0, 0, k & 63);
              const uint32_t d = arm(1), fb = sb + A_FULL + st * 8;
              PTR((item & 255) == PT && lane == 0, 1, k & 63);
              if (elect()) {
                mbar_expect(fb, 30720);
                tma_load3(d, k < 24 ? &tm.k : &tm.v, 0, (4 * t + (k & 2)) * LK, (2 * a + (k & 1)) * 3, fb);
                if (k == kreq) mbar_arrive(sb + A_REQ);
              }
              PTR((item & 255) == PT && lane == 0, 2, k & 63);
              advance();
            }
          }
        } else if (ty == IT_BATT) {
#pragma unroll 1
          for (int k = 0, j = 0, c = 0; k < 12; k++) {
            PTR((item & 255) == PT && lane == 0, 0, k & 63);
            const uint32_t d = arm(1), fb = sb + A_FULL + st * 8;
            PTR((item & 255) == PT && lane == 0, 1, k & 63);
            if (elect()) {
              mbar_expect(fb, c ? 25600 : 20480);
              tma_load3(d, c ? &tm.qkvK : &tm.qkvQ, 0, t * 32 - (c ? 8 : 0), (j & 1) * 30 + (j >> 1) * 5 + c, fb);
              if (k == 6) mbar_arrive(sb + A_REQ);
            }
            PTR((item & 255) == PT && lane == 0, 2, k & 63);
            if (c == 20) { c = 0; j++; } else c += 10;
            advance();
          }
        } else {
          if (elect()) { mbar_arrive(sb + A_FULL + st * 8); mbar_arrive(sb + A_REQ); }
          advance();
        }
        if (item == IT_END) break;
        if ((0x6a >> ty) & 1) {
#pragma unroll 1
          for (int k = 0; k < 4; k++) {
            arm(0);
            if (elect()) mbar_arrive(sb + A_FULL + st * 8);
            advance();
          }
        }
      }
    } else if (lane == 0) {
      const uint32_t qb = sb + A_QBAR + (wid == W_AG1) * 64, qe = sb + A_QENT + (wid == W_AG1) * 128;
      for (uint32_t e = 0;; e++) {
        mbar_wait_long(qb + (e & 7) * 8, (e >> 3) & 1);
        const uint4 en = lds128(qe + (e & 7) * 16);
        const int op = en.x & 15, sg = (en.x >> 4) & 15, rel = (en.x >> 8) & 15, nb = (en.x >> 12) & 15;
        if (op == OP_END) break;
        const uint32_t src = sb + sg * STG;
        if (op == OP_OB) tma_store3(&tm.obS, src, 0, en.y, en.z);
        else if (op == OP_Q) asm volatile("cp.async.bulk.global.shared::cta.bulk_group [%0], [%1], 24576;" ::"l"(g_Ql + en.y * 1536), "r"(src) : "memory");
        else {
          const CUtensorMap* pm = op == OP_O ? &tm.oS : (op == OP_QKV ? &tm.qkvS : &tm.out);
#pragma unroll 1
          for (int i = 0; i < nb; i++) {
            if (op == OP_ADD) tma_red3(pm, src + i * 8192, 0, en.y, en.z + i); else tma_store3(pm, src + i * 8192, 0, en.y, en.z + i);
            if (SPLITW && i + 1 < nb) { bulk_commit(); bulk_wait_read0(); }
          }
        }
        bulk_commit();
        bulk_wait_read0();
        asm volatile("mbarrier.arrive.shared::cta.b64 _, [%0], %1;" ::"r"(sb + A_EMPTY + sg * 8), "r"(rel) : "memory");
        if (en.w) {
          bulk_wait0();
          asm volatile("red.relaxed.gpu.global.add.u32 [%0], %1;" ::"l"(&g_cnt[(en.w - 1) * 8]), "r"(1) : "memory");
        }
      }
      bulk_wait0();
      if (wid == W_AG1) GTA(7);
    }
  } else {
    asm volatile("setmaxnreg.inc.sync.aligned.u32 232;");
    const int g = wid >> 2, w = wid & 3;
    uint32_t qn = 0;
    auto wait_full = [&]() { mbar_wait_u(sb + A_FULL + st * 8, ph); };
    auto release = [&](uint32_t s_) { if (lane == 0) mbar_arrive(sb + A_EMPTY + s_ * 8); };
    auto take_pair = [&]() -> uint32_t {
      wait_full();
      const uint32_t s0 = st; advance();
      wait_full();
      const uint32_t s1 = st; advance();
      release(g ? s0 : s1);
      return g ? s1 : s0;
    };
    auto push = [&](uint32_t w0, uint32_t w1, uint32_t w2, uint32_t w3) {
      fence_async_smem();
      if (w == 0 && lane == 0) sts128(sb + A_QENT + g * 128 + (qn & 7) * 16, w0, w1, w2, w3);
      __syncwarp();
      if (lane == 0) mbar_arrive(sb + A_QBAR + g * 64 + (qn & 7) * 8);
      qn++;
    };
    const uint32_t stm = (16 * w + (lane & 7) + (lane & 8)) * 128, stx = lane & 7, sth = lane >> 4;
    auto stage_bf16 = [&](uint32_t dst, const float* d, int nks = 12) {
#pragma unroll
      for (int ks = 0; ks < nks; ks++)
        stsm4(dst + (ks >> 2) * 8192 + stm + (((2 * (ks & 3) + sth) ^ stx) << 4), pack2(d[8 * ks], d[8 * ks + 1]), pack2(d[8 * ks + 2], d[8 * ks + 3]),
              pack2(d[8 * ks + 4], d[8 * ks + 5]), pack2(d[8 * ks + 6], d[8 * ks + 7]));
    };
#pragma unroll 1
    while (true) {
      wait_full();
      const uint32_t item = lds32(sb + A_ITEM + st * 4);
      const int ty = item & 7, t = (item >> 3) & 31, a = (item >> 8) & 255;
      if (ty == IT_QKV || ty == IT_XATT || ty == IT_Q) {
        float acc[192] = {};
        uint32_t prev = 0;
#define XG(i) do {} while (0)
#pragma unroll 1
        for (int k = 0; k < 20; k++) {
          if (k) wait_full();
          PTR((item & 255) == PT && tid == 32, 3, k);
          if (LAG && k == (g ? 0 : LAG)) { if (g) bar_sync(7, 256); else bar_arrive(7, 256); }
          const uint32_t s_ = sb + st * STG;
          const Desc da = mk_desc(s_, 16, 512, 2), db = mk_desc(s_ + 8192 + g * 12288, 4096, 1024, 1);
          wg_fence();
          wgmma_ss192t(acc, da, db, k);
          wgmma_ss192t(acc + 96, da + 256, db, k);
          wgmma_ss192t(acc, da + 2, db + 128, 1);
          wgmma_ss192t(acc + 96, da + 258, db + 128, 1);
          wg_commit();
          if (k) { wg_wait1(); release(prev); }
          prev = st; advance();
        }
        uint32_t kst[2];
        if (KEARLY && ty == IT_XATT) { kst[0] = take_pair(); kst[1] = take_pair(); }
        wg_wait0();
        fence_regs<192>(acc);
        release(prev);
        XG(0);
        if (ty == IT_QKV) {
#pragma unroll
          for (int q = 0; q < 2; q++) {
            const uint32_t m = take_pair();
            stage_bf16(sb + m * STG, acc + q * 96);
            push(OP_QKV | (m << 4) | (4 << 8) | (3 << 12), t * 128 + q * 64, a * 6 + g * 3, q ? C_QKV + t + 1 : 0);
          }
        } else if (ty == IT_Q) {
#pragma unroll
          for (int q = 0; q < 2; q++) {
            const uint32_t m = take_pair();
#pragma unroll
            for (int ks = 0; ks < 12; ks++) {
              const float* d = acc + q * 96 + ks * 8;
              sts128(sb + m * STG + (w * 12 + ks) * 512 + lane * 16, pack2(d[0], d[1]), pack2(d[2], d[3]), pack2(d[4], d[5]), pack2(d[6], d[7]));
            }
            push(OP_Q | (m << 4) | (4 << 8), (2 * a + g) * 2 + q, 0, q ? C_O + 240 + a + 1 : 0);
          }
        } else {
          uint32_t qf[24][4];
          float sc[2][40], gt[4];
#pragma unroll
          for (int q = 0; q < 2; q++) {
#pragma unroll
            for (int ks = 23; ks >= 0; ks--)
#pragma unroll
              for (int j = 0; j < 4; j++)
                if ((ks >= 12 && ks < 12 + CVTS) == (q == 1))
                  asm volatile("cvt.rn.bf16x2.f32 %0, %1, %2;" : "=r"(qf[ks][j]) : "f"(acc[8 * ks + 2 * j + 1]), "f"(acc[8 * ks + 2 * j]));
            if (!KEARLY) kst[q] = take_pair();
            if (q == 0) XG(1);
            if (q == 0 && XPP && g == 1) bar_sync(6, 256);
            if (q == 1) {
              const float* gp = g_gate + t * 128 + 16 * w + (lane >> 2);
              gt[0] = ldg_cg(gp); gt[1] = ldg_cg(gp + 8); gt[2] = ldg_cg(gp + 64); gt[3] = ldg_cg(gp + 72);
            }
#pragma unroll
            for (int i = 0; i < 40; i++) sc[q][i] = 0.f;
            const Desc db = mk_desc(sb + kst[q] * STG, 16, 1024, 1);
            wg_fence();
#pragma unroll
            for (int ks = 0; ks < 12; ks++) {
              if (XPP && g == 0 && q * 12 + ks == XPP) bar_arrive(6, 256);
              wgmma_rs80(sc[q], qf[q * 12 + ks], db + (((ks >> 2) * 10240 + (ks & 3) * 32) >> 4), ks);
            }
            wg_commit();
          }
          uint32_t pf[2][5][4];
          const AttMask am(tid, sb);
          wg_wait1();
          fence_regs<40>(sc[0]);
          XG(2);
          release(kst[0]);
          sched_fence(sb);
          att_softmax(am, sc[0], pf[0], gt[0], gt[1]);
          XG(3);
          float o[96] = {};
          auto pv = [&](int q, uint32_t m) {
            const Desc db = mk_desc(sb + m * STG, 10240, 1024, 1);
            wg_fence();
#pragma unroll
            for (int ks = 0; ks < 5; ks++) wgmma_rs192t(o, pf[q][ks], db + ks * 128, ks);
            wg_commit();
          };
          PTR((item & 255) == PT && tid == 32, 3, 24);
          const uint32_t m0 = take_pair();
          PTR((item & 255) == PT && tid == 32, 3, 25);
          pv(0, m0);
          wg_wait1();
          fence_regs<40>(sc[1]);
          release(kst[1]);
          att_softmax(am, sc[1], pf[1], gt[2], gt[3]);
          PTR((item & 255) == PT && tid == 32, 3, 26);
          const uint32_t m1 = take_pair();
          PTR((item & 255) == PT && tid == 32, 3, 27);
          wg_wait0();
          fence_regs<96>(o);
          XG(4);
#pragma unroll
          for (int i = 0; i < 48; i++) asm volatile("cvt.rn.bf16x2.f32 %0, %1, %2;" : "=r"(qf[i >> 2][i & 3]) : "f"(o[2 * i + 1]), "f"(o[2 * i]));
          pv(1, m1);
          bar_sync(1 + g, 128);
#pragma unroll
          for (int ks = 0; ks < 12; ks++)
            stsm4(sb + m0 * STG + (ks >> 2) * 8192 + stm + (((2 * (ks & 3) + sth) ^ stx) << 4), qf[ks][0], qf[ks][1], qf[ks][2], qf[ks][3]);
          push(OP_O | (m0 << 4) | (4 << 8) | (3 << 12), t * 128, a * 6 + g * 3, 0);
          XG(5);
          wg_wait0();
          fence_regs<96>(o);
          XG(6);
          bar_sync(1 + g, 128);
          stage_bf16(sb + m1 * STG, o);
          push(OP_O | (m1 << 4) | (4 << 8) | (3 << 12), t * 128 + 64, a * 6 + g * 3, C_O + t * 16 + a + 1);
          XG(7);
        }
      } else if (ty == IT_OUT || ty == IT_INIT) {
        float acc[160] = {};
        const int hb = (item >> 16) & 255, nh = (item >> 24) - hb, nk = ty == IT_OUT ? nh * 6 : 20, jh = a & 1;
        const uint32_t ln = pin(lane), ao = (g * 64 + 16 * w + (ln & 15)) * 64 + (((ln >> 4) ^ ((ln >> 1) & 3)) << 4);
        if (PP && g == 1) bar_arrive(4, 256);
#pragma unroll 1
        for (int k = 0; k < nk; k += 2) {
          uint32_t af[4][4], sg[2];
#pragma unroll
          for (int e = 0; e < 2; e++) {
            if (k + e) wait_full();
            sg[e] = st;
            ldsm4(af[2 * e], sb + st * STG + ao);
            ldsm4(af[2 * e + 1], sb + st * STG + (ao ^ 32));
            advance();
          }
          if (PP) bar_sync(4 + g, 256);
          wg_fence();
#pragma unroll
          for (int e = 0; e < 4; e++) {
            const Desc db = mk_desc(sb + sg[e >> 1] * STG + 8192 + (e & 1) * 2048, 4096, 1024, 1);
            if (PP == 2 && e == 3 && (g == 0 || k + 2 < nk)) bar_arrive(5 - g, 256);
            wgmma_rs192t(acc, af[e], db, 1);
            if (PP == 3 && e == 3 && (g == 0 || k + 2 < nk)) bar_arrive(5 - g, 256);
            wgmma_rs128t(acc + 96, af[e], db + 768, 1);
          }
          wg_commit();
          if (PP == 1 && (g == 0 || k + 2 < nk)) bar_arrive(5 - g, 256);
          wg_wait0();
          release(sg[0]); release(sg[1]);
        }
        fence_regs<160>(acc);
        const uint32_t row = t * 128 + g * 64;
#pragma unroll
        for (int q = 0; q < 2; q++) {
          const uint32_t m = take_pair();
          stage_bf16(sb + m * STG, acc + q * 96, q ? 8 : 12);
          push((ty == IT_OUT || t == 15 ? OP_ADD : OP_SET) | (m << 4) | (4 << 8) | ((3 - q) << 12), row, jh * 5 + q * 3, q && ty == IT_INIT ? C_ACC + t + 1 : 0);
        }
      } else if (ty == IT_BATT) {
        const int ln = pin(lane);
        const int q4 = ln & 3, r8 = ln >> 2;
        const bool lo = q4 < 2, m0 = 2 * q4 > r8, m1 = 2 * q4 + 1 > r8;
        const uint32_t mk = (m0 ? 0xffffu : 0u) | (m1 ? 0xffff0000u : 0u);
        uint32_t aq[5], ak[5];
#pragma unroll
        for (int i = 0; i < 5; i++) {
          const int c = 5 * wid + i;
          aq[i] = (c >> 3) * 4096 + ln * 128 + (((c ^ ln) & 7) << 4);
          ak[i] = aq[i] + (c >> 3) * 1024;
        }
        const int c4 = 5 * wid + (ln >> 3);
        const uint32_t ak4 = (c4 >> 3) * 5120 + (32 + (ln & 7)) * 128 + (((c4 ^ ln) & 7) << 4), ak5 = ak[4] + (32 + (ln & 7) - ln) * 128;
#pragma unroll 1
        for (int j = 0; j < 4; j++) {
          float gt[4];
#pragma unroll
          for (int i = 0; i < 4; i++) gt[i] = ldg_cg(g_gate + S_TOK + t * 64 + (j & 1) + 2 * r8 + i * 16);
          if (j) wait_full();
          PTR((item & 255) == PT && tid == 32, 3, j * 3);
          const uint32_t sq = st; advance();
          uint32_t qf[5][4], kf[7][4], vf[7][4], pa[4], pb[4];
          float sc[4][3][4] = {}, o[4][3][4] = {}, l[4][4], xa[4], xb[4];
#pragma unroll
          for (int i = 0; i < 5; i++) ldsm4(qf[i], sb + sq * STG + aq[i]);
          wait_full();
          PTR((item & 255) == PT && tid == 32, 3, j * 3 + 1);
          const uint32_t sk = st; advance();
#pragma unroll
          for (int i = 0; i < 7; i++) ldsm4(kf[i], sb + sk * STG + (i < 5 ? ak[i] : (i == 5 ? ak4 : ak5)));
          auto frag = [](uint32_t (*f)[4], int c, int n) { return n < 4 ? f[c][n] : (c < 4 ? f[5][c] : f[6][0]); };
#pragma unroll
          for (int u = 0; u < 4; u++) {
            const int c = (u >> 1) * 3, b = u & 1;
            const uint32_t x[4] = {qf[c][2 * b], qf[c][2 * b + 1], qf[c + 1][2 * b], qf[c + 1][2 * b + 1]};
#pragma unroll
            for (int n = 0; n < 3; n++) mma16816(sc[u][n], x, frag(kf, c, 2 * b + n), frag(kf, c + 1, 2 * b + n));
          }
#pragma unroll
          for (int u = 0; u < 4; u++) {
            const int b = u & 1;
            const uint32_t x0 = lo == (u < 2) ? qf[2][2 * b] : 0u, x1 = lo == (u < 2) ? qf[2][2 * b + 1] : 0u;
#pragma unroll
            for (int n = 0; n < 3; n++) mma1688(sc[u][n], x0, x1, frag(kf, 2, 2 * b + n));
          }
          wait_full();
          PTR((item & 255) == PT && tid == 32, 3, j * 3 + 2);
          const uint32_t sv = st; advance();
#pragma unroll
          for (int i = 0; i < 7; i++) ldsm4t(vf[i], sb + sv * STG + (i < 5 ? ak[i] : (i == 5 ? ak4 : ak5)));
          if (t == 0) sc[0][0][0] = sc[0][0][1] = sc[2][0][0] = sc[2][0][1] = -INFINITY;
          constexpr float SCL = 0.22360679774997896f * 1.4426950408889634f;
#pragma unroll
          for (int u = 0; u < 4; u++) {
            l[u][0] = m0 ? sc[u][0][0] : sc[u][1][0]; l[u][1] = m1 ? sc[u][0][1] : sc[u][1][1];
            l[u][2] = m0 ? sc[u][1][2] : sc[u][2][2]; l[u][3] = m1 ? sc[u][1][3] : sc[u][2][3];
            xa[u] = fmaxf(l[u][0], l[u][1]); xb[u] = fmaxf(l[u][2], l[u][3]);
          }
          release(sk);
#pragma unroll
          for (int d = 1; d < 4; d *= 2)
#pragma unroll
            for (int u = 0; u < 4; u++) { xa[u] = fmaxf(xa[u], __shfl_xor_sync(~0u, xa[u], d)); xb[u] = fmaxf(xb[u], __shfl_xor_sync(~0u, xb[u], d)); }
#pragma unroll
          for (int u = 0; u < 4; u++) {
            xa[u] *= SCL; xb[u] *= SCL;
#pragma unroll
            for (int i = 0; i < 4; i++) l[u][i] = ex2(fmaf(l[u][i], SCL, -(i < 2 ? xa[u] : xb[u])));
            xa[u] = l[u][0] + l[u][1]; xb[u] = l[u][2] + l[u][3];
          }
#pragma unroll
          for (int d = 1; d < 4; d *= 2)
#pragma unroll
            for (int u = 0; u < 4; u++) { xa[u] += __shfl_xor_sync(~0u, xa[u], d); xb[u] += __shfl_xor_sync(~0u, xb[u], d); }
#pragma unroll
          for (int u = 0; u < 4; u++) {
            const int c = (u >> 1) * 3, b = u & 1;
            xa[u] = gt[2 * b] * rcp(xa[u]); xb[u] = gt[2 * b + 1] * rcp(xb[u]);
            pa[u] = pack2(l[u][0] * xa[u], l[u][1] * xa[u]); pb[u] = pack2(l[u][2] * xb[u], l[u][3] * xb[u]);
            const uint32_t pf[4] = {pa[u] & mk, 0u, pa[u] & ~mk, pb[u] & mk};
#pragma unroll
            for (int n = 0; n < 3; n++) mma16816(o[u][n], pf, vf[n < 2 ? c + n : 2][2 * b], vf[n < 2 ? c + n : 2][2 * b + 1]);
          }
#pragma unroll
          for (int u = 0; u < 4; u++)
#pragma unroll
            for (int n = 0; n < 3; n++) mma1688(o[u][n], 0u, pb[u] & ~mk, frag(vf, n < 2 ? (u >> 1) * 3 + n : 2, 2 * (u & 1) + 2));
          release(sv);
#pragma unroll
          for (int i = 0; i < 5; i++) {
            float y[8];
#pragma unroll
            for (int e = 0; e < 8; e++) y[e] = i == 2 ? (lo ? o[e >> 2][2][e & 3] : o[2 + (e >> 2)][2][e & 3]) : o[(i > 2) * 2 + (e >> 2)][i % 3][e & 3];
            stsm4(sb + sq * STG + aq[i], pack2(y[0], y[1]), pack2(y[2], y[3]), pack2(y[4], y[5]), pack2(y[6], y[7]));
          }
          PTR((item & 255) == PT && tid == 32, 3, 12 + j * 2);
          fence_async_smem();
          bar_sync(3, 256);
          PTR((item & 255) == PT && tid == 32, 3, 13 + j * 2);
          if (g == (j & 1)) push(OP_OB | (sq << 4) | (8 << 8), t * 32, (j & 1) * 10 + (j >> 1) * 5, C_OB + (t >> 1) + 1);
        }
      } else {
        release(st);
        push(OP_END, 0, 0, 0);
        break;
      }
    }
  }
}

typedef CUresult (*EncFn)(CUtensorMap*, CUtensorMapDataType, cuuint32_t, void*, const cuuint64_t*, const cuuint64_t*, const cuuint32_t*,
                          const cuuint32_t*, CUtensorMapInterleave, CUtensorMapSwizzle, CUtensorMapL2promotion, CUtensorMapFloatOOBfill);

#define PROMO CU_TENSOR_MAP_L2_PROMOTION_L2_128B
void make_map(EncFn enc, CUtensorMap* tm, const void* base, int rank, const cuuint64_t* dims, const cuuint64_t* strides, const cuuint32_t* box,
              CUtensorMapSwizzle sw = CU_TENSOR_MAP_SWIZZLE_128B, CUtensorMapDataType dt = CU_TENSOR_MAP_DATA_TYPE_BFLOAT16) {
  const cuuint32_t es[5] = {1, 1, 1, 1, 1};
  enc(tm, dt, rank, const_cast<void*>(base), dims, strides, box, es, CU_TENSOR_MAP_INTERLEAVE_NONE, sw, PROMO,
      CU_TENSOR_MAP_FLOAT_OOB_FILL_NONE);
}
void map_blk(EncFn enc, CUtensorMap* tm, const void* base, int rows, int cols, int brows, int bblk) {
  const cuuint64_t d[3] = {64, (cuuint64_t)rows, (cuuint64_t)cols / 64}, st[2] = {(cuuint64_t)cols * 2, 128};
  const cuuint32_t b[3] = {64, (cuuint32_t)brows, (cuuint32_t)bblk};
  make_map(enc, tm, base, 3, d, st, b);
}
void map_2d(EncFn enc, CUtensorMap* tm, const void* base, int rows, int cols, int brows, int bcols, CUtensorMapSwizzle sw) {
  const cuuint64_t d[2] = {(cuuint64_t)cols, (cuuint64_t)rows}, st[1] = {(cuuint64_t)cols * 2};
  const cuuint32_t b[2] = {(cuuint32_t)bcols, (cuuint32_t)brows};
  make_map(enc, tm, base, 2, d, st, b, sw);
}

}

extern "C" void kernel_launch(void* const* d_in, const int* in_sizes, int n_in, void* d_out, int out_size) {
  const bf16* x = (const bf16*)d_in[0];
  const bf16* mem0 = (const bf16*)d_in[1];
  const bf16* Wq = (const bf16*)d_in[2];
  const bf16* Wk = (const bf16*)d_in[3];
  const bf16* Wv = (const bf16*)d_in[4];
  const bf16* Wo = (const bf16*)d_in[5];
  const bf16* wqkv = (const bf16*)d_in[8];
  const bf16* wob = (const bf16*)d_in[9];
  const bf16* gate_w = (const bf16*)d_in[10];
  static EncFn enc = nullptr;
  static void *pR = nullptr, *pK = nullptr, *pV = nullptr, *pO = nullptr, *pQ = nullptr, *pB = nullptr;
  if (!enc) {
    void* fn = nullptr;
    cudaDriverEntryPointQueryResult qr;
    cudaGetDriverEntryPoint("cuTensorMapEncodeTiled", &fn, cudaEnableDefault, &qr);
    enc = (EncFn)fn;
    cudaGetSymbolAddress(&pR, g_red);
    cudaGetSymbolAddress(&pK, g_K);
    cudaGetSymbolAddress(&pV, g_V);
    cudaGetSymbolAddress(&pO, g_O);
    cudaGetSymbolAddress(&pQ, g_qkv);
    cudaGetSymbolAddress(&pB, g_Ob);
    cudaFuncSetAttribute(rec_kernel, cudaFuncAttributeMaxDynamicSharedMemorySize, R_SMEM_ALLOC);
    cudaFuncSetAttribute(aux_kernel, cudaFuncAttributeMaxDynamicSharedMemorySize, A_SMEM);
  }
  CUtensorMap tmX, tmK, tmV, tmWq, tmWq2, tmWk, tmWv, tmWo, tmOut;
  map_2d(enc, &tmOut, d_out, S_TOK, DM, 64, 32, CU_TENSOR_MAP_SWIZZLE_64B);
  map_2d(enc, &tmWq, Wq, DM, HD, 144, 64, CU_TENSOR_MAP_SWIZZLE_128B);
  map_2d(enc, &tmWq2, Wq, DM, HD, 32, 64, CU_TENSOR_MAP_SWIZZLE_128B);
  map_2d(enc, &tmWk, Wk, DM, HD, 128, 64, CU_TENSOR_MAP_SWIZZLE_128B);
  map_2d(enc, &tmWv, Wv, DM, HD, 128, 64, CU_TENSOR_MAP_SWIZZLE_128B);
  {
    const cuuint64_t d[3] = {32, HD, 20}, st[2] = {DM * 2, 64};
    const cuuint32_t b[3] = {32, 64, 7};
    make_map(enc, &tmWo, Wo, 3, d, st, b, CU_TENSOR_MAP_SWIZZLE_64B);
  }
  map_blk(enc, &tmX, x, S_TOK, DM, 32, 10);
  map_2d(enc, &tmK, pK, NSEG * LK, HD, LK, 64, CU_TENSOR_MAP_SWIZZLE_128B);
  map_2d(enc, &tmV, pV, NSEG * LK, HD, LK, 64, CU_TENSOR_MAP_SWIZZLE_128B);
  AuxMaps am;
  map_2d(enc, &am.xA, x, S_TOK, DM, 128, 32, CU_TENSOR_MAP_SWIZZLE_64B);
  map_blk(enc, &am.wq, Wq, DM, HD, 32, 6);
  map_blk(enc, &am.wqkv, wqkv, DM, 3 * DM, 32, 6);
  map_blk(enc, &am.wo, Wo, HD, DM, 32, 5);
  map_blk(enc, &am.wob, wob, DM, DM, 32, 5);
  map_blk(enc, &am.k, pK, NSEG * LK, HD, 80, 3);
  map_blk(enc, &am.v, pV, NSEG * LK, HD, 80, 3);
  map_2d(enc, &am.oA, pO, S_TOK, HD, 128, 32, CU_TENSOR_MAP_SWIZZLE_64B);
  map_blk(enc, &am.oS, pO, S_TOK, HD, 64, 1);
  map_2d(enc, &am.obA, pB, S_TOK, DM, 128, 32, CU_TENSOR_MAP_SWIZZLE_64B);
  map_blk(enc, &am.obS, pB, S_TOK / 2, 2 * DM, 32, 5);
  map_blk(enc, &am.qkvS, pQ, S_TOK, 3 * DM, 64, 1);
  map_blk(enc, &am.qkvQ, pQ, S_TOK / 2, 6 * DM, 32, 5);
  map_blk(enc, &am.qkvK, pQ, S_TOK / 2, 6 * DM, 40, 5);
  map_blk(enc, &am.out, d_out, S_TOK, DM, 64, 1);
  rec_kernel<<<96 + 3 * WARM, 256, R_SMEM_ALLOC, cudaStreamPerThread>>>(tmX, tmK, tmV, tmWq, tmWq2, tmWk, tmWv, tmWo, tmOut, mem0, Wq, Wk, Wv, Wo, x, gate_w, (bf16*)d_out,
                                                               (unsigned char*)(((uintptr_t)pR + 0x1fffff) & ~(uintptr_t)0x1fffff));
  cudaLaunchConfig_t cfg = {};
  cfg.gridDim = dim3(AUX_GRID); cfg.blockDim = dim3(384); cfg.dynamicSmemBytes = A_SMEM; cfg.stream = cudaStreamPerThread;
  cudaLaunchAttribute at[1];
  at[0].id = cudaLaunchAttributeProgrammaticStreamSerialization;
  at[0].val.programmaticStreamSerializationAllowed = 1;
  cfg.attrs = at;
  cfg.numAttrs = 1;
  cudaLaunchKernelEx(&cfg, aux_kernel, am);
}
```

```cpp
#include <cuda_runtime.h>
#include <cuda_bf16.h>
#include <cuda.h>
#include <stdint.h>
#include <type_traits>

typedef __nv_bfloat16 bf16;

namespace {

constexpr int S_TOK = 2048, DM = 640, NH = 32, DH = 192, HD = NH * DH, SEG = 32, NSEG = 64, MT = 8, LK = 40;
constexpr int SPIN_MAX = 1 << 20, NGATE = 96;

__device__ __align__(4096) unsigned char g_red[(2 << 20) + (640 << 10)];
__host__ __device__ constexpr uint32_t rb_q(int q) { return (q < 5 ? q : q - 5) * 131072 + (uint32_t)((0x3122120330ull >> 4 * q) & 15) * 2048; }
__host__ __device__ constexpr uint32_t rb_j(int j) { return (j & 1) * 256 + (j & 2) * 512 + (j & 12) * 2048; }
__host__ __device__ constexpr uint32_t rb_b(int b) { return (b & 1) * 128 + (b & 2) * 256; }
__device__ unsigned long long g_rec[96];
__device__ uint32_t g_epoch;
__device__ uint32_t g_err;
__device__ __align__(16) uint32_t g_segcnt[NSEG];
__device__ __align__(1024) bf16 g_K[NSEG * LK * HD];
__device__ __align__(1024) bf16 g_V[NSEG * LK * HD];
__device__ __align__(1024) bf16 g_O[S_TOK * HD];
__device__ __align__(1024) uint4 g_Ql[NH * 2 * 4 * 12 * 32];
__device__ __align__(1024) bf16 g_qkv[S_TOK * 3 * DM];
__device__ __align__(1024) bf16 g_Ob[S_TOK * DM];
__device__ float g_gate[2 * S_TOK];
__device__ uint32_t g_cnt[512 * 8];
constexpr int C_GATE = 0, C_QKV = 16, C_OB = 32, C_ACC = 48, C_O = 80;
__device__ __align__(128) uint32_t g_queue[3 * 32];
__device__ uint32_t g_prog;
#define GTR(i) do {} while (0)
#define GTA(i) do {} while (0)
#define PTR(c, r, k) do {} while (0)

__device__ __forceinline__ uint32_t smem_u32(const void* p) { return (uint32_t)__cvta_generic_to_shared(p); }
__device__ __forceinline__ uint32_t clk32() { uint32_t t; asm volatile("mov.u32 %0, %%clock;" : "=r"(t)::"memory"); return t; }
__device__ __forceinline__ uint32_t mapa(uint32_t a, uint32_t r) { uint32_t o; asm("mapa.shared::cluster.u32 %0, %1, %2;" : "=r"(o) : "r"(a), "r"(r)); return o; }
__device__ __forceinline__ void mbar_init(uint32_t b, uint32_t c) { asm volatile("mbarrier.init.shared::cta.b64 [%0], %1;" ::"r"(b), "r"(c) : "memory"); }
__device__ __forceinline__ void mbar_expect(uint32_t b, uint32_t bytes) { asm volatile("mbarrier.arrive.expect_tx.shared::cta.b64 _, [%0], %1;" ::"r"(b), "r"(bytes) : "memory"); }
__device__ __forceinline__ void mbar_arrive(uint32_t b) { asm volatile("mbarrier.arrive.shared::cta.b64 _, [%0];" ::"r"(b) : "memory"); }
__device__ __forceinline__ bool mbar_try(uint32_t b, uint32_t par) {
  uint32_t p;
  asm volatile("{.reg .pred p; mbarrier.try_wait.parity.shared::cta.b64 p, [%1], %2; selp.u32 %0,1,0,p;}" : "=r"(p) : "r"(b), "r"(par) : "memory");
  return p;
}
__device__ __forceinline__ bool mbar_test(uint32_t b, uint32_t par) {
  uint32_t p;
  asm volatile("{.reg .pred p; mbarrier.test_wait.parity.shared::cta.b64 p, [%1], %2; selp.u32 %0,1,0,p;}" : "=r"(p) : "r"(b), "r"(par) : "memory");
  return p;
}
__device__ __forceinline__ bool mbar_try_cl(uint32_t b, uint32_t par) {
  uint32_t p;
  asm volatile("{.reg .pred p; mbarrier.try_wait.parity.acquire.cluster.shared::cta.b64 p, [%1], %2; selp.u32 %0,1,0,p;}" : "=r"(p) : "r"(b), "r"(par) : "memory");
  return p;
}
__device__ __forceinline__ void mbar_wait(uint32_t b, uint32_t par) {
  int n = 0;
#pragma unroll 1
  while (!mbar_try(b, par)) { if (++n > SPIN_MAX) { g_err = 1; break; } }
}
__device__ __forceinline__ void bar_sync(int id, int n) { asm volatile("bar.sync %0, %1;" ::"r"(id), "r"(n) : "memory"); }
__device__ __forceinline__ void bar_arrive(int id, int n) { asm volatile("bar.arrive %0, %1;" ::"r"(id), "r"(n) : "memory"); }
__device__ __forceinline__ void fence_async_smem() { asm volatile("fence.proxy.async.shared::cta;" ::: "memory"); }
__device__ __forceinline__ void ldsm4(uint32_t* r, uint32_t a) {
  asm volatile("ldmatrix.sync.aligned.m8n8.x4.shared.b16 {%0,%1,%2,%3}, [%4];" : "=r"(r[0]), "=r"(r[1]), "=r"(r[2]), "=r"(r[3]) : "r"(a) : "memory");
}
__device__ __forceinline__ void ldsm4t(uint32_t* r, uint32_t a) {
  asm volatile("ldmatrix.sync.aligned.m8n8.x4.trans.shared.b16 {%0,%1,%2,%3}, [%4];" : "=r"(r[0]), "=r"(r[1]), "=r"(r[2]), "=r"(r[3]) : "r"(a) : "memory");
}
__device__ __forceinline__ void stsm4t(uint32_t a, uint32_t r0, uint32_t r1, uint32_t r2, uint32_t r3) {
  asm volatile("stmatrix.sync.aligned.m8n8.x4.trans.shared.b16 [%0], {%1,%2,%3,%4};" ::"r"(a), "r"(r0), "r"(r1), "r"(r2), "r"(r3) : "memory");
}
__device__ __forceinline__ void stsm2t(uint32_t a, uint32_t r0, uint32_t r1) {
  asm volatile("stmatrix.sync.aligned.m8n8.x2.trans.shared.b16 [%0], {%1,%2};" ::"r"(a), "r"(r0), "r"(r1) : "memory");
}
__device__ __forceinline__ uint32_t movmat(uint32_t a) { uint32_t d; asm volatile("movmatrix.sync.aligned.m8n8.trans.b16 %0, %1;" : "=r"(d) : "r"(a)); return d; }
__device__ __forceinline__ void mma16816(float* d, const uint32_t* a, uint32_t b0, uint32_t b1) {
  asm volatile("mma.sync.aligned.m16n8k16.row.col.f32.bf16.bf16.f32 {%0,%1,%2,%3}, {%4,%5,%6,%7}, {%8,%9}, {%0,%1,%2,%3};"
               : "+f"(d[0]), "+f"(d[1]), "+f"(d[2]), "+f"(d[3]) : "r"(a[0]), "r"(a[1]), "r"(a[2]), "r"(a[3]), "r"(b0), "r"(b1));
}
__device__ __forceinline__ void mma1688(float* d, uint32_t a0, uint32_t a1, uint32_t b0) {
  asm volatile("mma.sync.aligned.m16n8k8.row.col.f32.bf16.bf16.f32 {%0,%1,%2,%3}, {%4,%5}, {%6}, {%0,%1,%2,%3};"
               : "+f"(d[0]), "+f"(d[1]), "+f"(d[2]), "+f"(d[3]) : "r"(a0), "r"(a1), "r"(b0));
}
__device__ __forceinline__ uint32_t pack2(float lo, float hi) { uint32_t r; asm("cvt.rn.bf16x2.f32 %0, %1, %2;" : "=r"(r) : "f"(hi), "f"(lo)); return r; }
__device__ __forceinline__ float bf_lo(uint32_t w) { return __uint_as_float(w << 16); }
__device__ __forceinline__ float bf_hi(uint32_t w) { return __uint_as_float(w & 0xffff0000u); }
__device__ __forceinline__ float ex2(float x) { float y; asm("ex2.approx.ftz.f32 %0, %1;" : "=f"(y) : "f"(x)); return y; }
__device__ __forceinline__ void sts128(uint32_t a, uint32_t x, uint32_t y, uint32_t z, uint32_t w) { asm volatile("st.shared.v4.b32 [%0], {%1,%2,%3,%4};" ::"r"(a), "r"(x), "r"(y), "r"(z), "r"(w) : "memory"); }
__device__ __forceinline__ void sts64f(uint32_t a, float x, float y) { asm volatile("st.shared.v2.f32 [%0], {%1,%2};" ::"r"(a), "f"(x), "f"(y) : "memory"); }
__device__ __forceinline__ void sts32(uint32_t a, uint32_t x) { asm volatile("st.shared.b32 [%0], %1;" ::"r"(a), "r"(x) : "memory"); }
__device__ __forceinline__ void smax32(uint32_t a, uint32_t x) { asm volatile("red.shared.max.u32 [%0], %1;" ::"r"(a), "r"(x) : "memory"); }
__device__ __forceinline__ uint32_t lds32(uint32_t a) { uint32_t v; asm volatile("ld.shared.b32 %0, [%1];" : "=r"(v) : "r"(a) : "memory"); return v; }
__device__ __forceinline__ float4 lds128f(uint32_t a) { float4 v; asm volatile("ld.shared.v4.f32 {%0,%1,%2,%3}, [%4];" : "=f"(v.x), "=f"(v.y), "=f"(v.z), "=f"(v.w) : "r"(a) : "memory"); return v; }
__device__ __forceinline__ uint4 lds128(uint32_t a) { uint4 v; asm volatile("ld.shared.v4.b32 {%0,%1,%2,%3}, [%4];" : "=r"(v.x), "=r"(v.y), "=r"(v.z), "=r"(v.w) : "r"(a) : "memory"); return v; }
__device__ __forceinline__ float2 lds64f(uint32_t a) { float2 v; asm volatile("ld.shared.v2.f32 {%0,%1}, [%2];" : "=f"(v.x), "=f"(v.y) : "r"(a) : "memory"); return v; }
__device__ __forceinline__ void st_async2(uint32_t a, uint32_t x, uint32_t y, uint32_t bar) {
  asm volatile("st.async.weak.shared::cluster.mbarrier::complete_tx::bytes.v2.b32 [%0], {%1,%2}, [%3];" ::"r"(a), "r"(x), "r"(y), "r"(bar) : "memory");
}
__device__ __forceinline__ void st_async4(uint32_t a, uint32_t x, uint32_t y, uint32_t z, uint32_t w, uint32_t bar) {
  asm volatile("st.async.weak.shared::cluster.mbarrier::complete_tx::bytes.v4.b32 [%0], {%1,%2,%3,%4}, [%5];" ::"r"(a), "r"(x), "r"(y), "r"(z), "r"(w), "r"(bar) : "memory");
}
__device__ __forceinline__ void sts64(uint32_t a, uint32_t x, uint32_t y) { asm volatile("st.shared.v2.b32 [%0], {%1,%2};" ::"r"(a), "r"(x), "r"(y) : "memory"); }
__device__ __forceinline__ float rcp(float x) { float y; asm("rcp.approx.ftz.f32 %0, %1;" : "=f"(y) : "f"(x)); return y; }
__device__ __forceinline__ uint32_t pin(uint32_t v) { asm volatile("" : "+r"(v)); return v; }
template <int ID> __device__ __forceinline__ void sched_fence_(uint32_t a) {
  asm volatile("{.reg .pred p;\nsetp.eq.u32 p, %0, %1;\nSF: @p pmevent 0;\n@p bra.uni SF;}" ::"r"(a), "n"(0x40000000 + ID) : "memory");
}
#define sched_fence(a) sched_fence_<__LINE__>(a)
__device__ __forceinline__ bool elect() {
  uint32_t p;
  asm volatile("{.reg .pred p; elect.sync _|p, 0xffffffff; selp.u32 %0,1,0,p;}" : "=r"(p));
  return p;
}
__device__ __forceinline__ uint32_t opaque(uint32_t v) { return __shfl_sync(~0u, v, threadIdx.x & 31); }
__device__ __forceinline__ uint4 ldg_rlx128(const void* p) {
  uint4 v; asm volatile("ld.relaxed.gpu.global.v4.b32 {%0,%1,%2,%3}, [%4];" : "=r"(v.x), "=r"(v.y), "=r"(v.z), "=r"(v.w) : "l"(p) : "memory"); return v;
}
__device__ __forceinline__ uint2 ldg_rlx64(const void* p) {
  uint2 v; asm volatile("{.reg .b64 t; ld.relaxed.gpu.global.b64 t, [%2]; mov.b64 {%0,%1}, t;}" : "=r"(v.x), "=r"(v.y) : "l"(p) : "memory"); return v;
}
__device__ __forceinline__ uint32_t hmaxabs2(uint32_t a, uint32_t b) { uint32_t r; asm("max.xorsign.abs.bf16x2 %0, %1, %2;" : "=r"(r) : "r"(a), "r"(b)); return r; }
__device__ __forceinline__ uint32_t ldg_rlx32(const void* p) {
  uint32_t v; asm volatile("ld.relaxed.gpu.global.b32 %0, [%1];" : "=r"(v) : "l"(p) : "memory"); return v;
}
__device__ __forceinline__ float ldg_cg(const float* p) { float v; asm volatile("ld.global.cg.f32 %0, [%1];" : "=f"(v) : "l"(p) : "memory"); return v; }
__device__ __forceinline__ void spin_until(uint32_t t0, int d) {
#pragma unroll 1
  while ((int)(clk32() - t0) < d) {}
}
__device__ __forceinline__ void stg_rlx64(void* p, uint32_t a, uint32_t b) {
  asm volatile("{.reg .b64 t; mov.b64 t, {%1,%2}; st.relaxed.gpu.global.b64 [%0], t;}" ::"l"(p), "r"(a), "r"(b) : "memory");
}
__device__ __forceinline__ void prefetch_l2(const void* p) { asm volatile("prefetch.global.L2 [%0];" ::"l"(p)); }
__device__ __forceinline__ void tma_load3(uint32_t dst, const CUtensorMap* tm, int c0, int c1, int c2, uint32_t bar) {
  asm volatile("cp.async.bulk.tensor.3d.shared::cluster.global.mbarrier::complete_tx::bytes [%0], [%1, {%3,%4,%5}], [%2];"
               ::"r"(dst), "l"(tm), "r"(bar), "r"(c0), "r"(c1), "r"(c2) : "memory");
}
__device__ __forceinline__ void tma_load2(uint32_t dst, const CUtensorMap* tm, int c0, int c1, uint32_t bar) {
  asm volatile("cp.async.bulk.tensor.2d.shared::cluster.global.mbarrier::complete_tx::bytes [%0], [%1, {%3,%4}], [%2];"
               ::"r"(dst), "l"(tm), "r"(bar), "r"(c0), "r"(c1) : "memory");
}
__device__ __forceinline__ void bulk_s2s(uint32_t dst, uint32_t src, uint32_t bytes, uint32_t bar) {
  asm volatile("cp.async.bulk.shared::cluster.shared::cta.mbarrier::complete_tx::bytes [%0], [%1], %2, [%3];" ::"r"(dst), "r"(src), "r"(bytes), "r"(bar) : "memory");
}
__device__ __forceinline__ void prefetch_map(const CUtensorMap* tm) { asm volatile("prefetch.tensormap [%0];" ::"l"(tm) : "memory"); }
__device__ __forceinline__ void tma_store2(const CUtensorMap* tm, uint32_t src, int c0, int c1) {
  asm volatile("cp.async.bulk.tensor.2d.global.shared::cta.bulk_group [%0, {%2,%3}], [%1];" ::"l"(tm), "r"(src), "r"(c0), "r"(c1) : "memory");
}
__device__ __forceinline__ void bulk_commit() { asm volatile("cp.async.bulk.commit_group;" ::: "memory"); }
__device__ __forceinline__ void bulk_wait0() { asm volatile("cp.async.bulk.wait_group 0;" ::: "memory"); }
__device__ __forceinline__ void bulk_wait_read0() { asm volatile("cp.async.bulk.wait_group.read 0;" ::: "memory"); }
__device__ __forceinline__ void wg_fence() { asm volatile("wgmma.fence.sync.aligned;" ::: "memory"); }
__device__ __forceinline__ void wg_commit() { asm volatile("wgmma.commit_group.sync.aligned;" ::: "memory"); }
__device__ __forceinline__ void wg_wait0() { asm volatile("wgmma.wait_group.sync.aligned 0;" ::: "memory"); }
template <int ACC>
__device__ __forceinline__ void wgmma_rs32(float* d, const uint32_t* a, uint64_t db) {
  asm volatile("{.reg .pred p; setp.ne.b32 p, %21, 0;\n"
               "wgmma.mma_async.sync.aligned.m64n32k16.f32.bf16.bf16 {%0,%1,%2,%3,%4,%5,%6,%7,%8,%9,%10,%11,%12,%13,%14,%15}, {%16,%17,%18,%19}, %20, p, 1, 1, 0;}"
               : "+f"(d[0]), "+f"(d[1]), "+f"(d[2]), "+f"(d[3]), "+f"(d[4]), "+f"(d[5]), "+f"(d[6]), "+f"(d[7]), "+f"(d[8]), "+f"(d[9]),
                 "+f"(d[10]), "+f"(d[11]), "+f"(d[12]), "+f"(d[13]), "+f"(d[14]), "+f"(d[15])
               : "r"(a[0]), "r"(a[1]), "r"(a[2]), "r"(a[3]), "l"(db), "n"(ACC));
}

template <int N> __device__ __forceinline__ void fence_regs(float* d) {
#pragma unroll
  for (int i = 0; i < N; i++) asm volatile("" : "+f"(d[i])::"memory");
}
__device__ __forceinline__ void wg_wait1() { asm volatile("wgmma.wait_group.sync.aligned 1;" ::: "memory"); }
__device__ __forceinline__ void tma_store3(const CUtensorMap* tm, uint32_t src, int c0, int c1, int c2) {
  asm volatile("cp.async.bulk.tensor.3d.global.shared::cta.bulk_group [%0, {%2,%3,%4}], [%1];" ::"l"(tm), "r"(src), "r"(c0), "r"(c1), "r"(c2) : "memory");
}
__device__ __forceinline__ void tma_red3(const CUtensorMap* tm, uint32_t src, int c0, int c1, int c2) {
  asm volatile("cp.reduce.async.bulk.tensor.3d.global.shared::cta.add.bulk_group [%0, {%2,%3,%4}], [%1];" ::"l"(tm), "r"(src), "r"(c0), "r"(c1), "r"(c2) : "memory");
}
__device__ __forceinline__ void tma_red2(const CUtensorMap* tm, uint32_t src, int c0, int c1) {
  asm volatile("cp.reduce.async.bulk.tensor.2d.global.shared::cta.add.bulk_group [%0, {%2,%3}], [%1];" ::"l"(tm), "r"(src), "r"(c0), "r"(c1) : "memory");
}
__device__ __forceinline__ void stsm4(uint32_t a, uint32_t r0, uint32_t r1, uint32_t r2, uint32_t r3) {
  asm volatile("stmatrix.sync.aligned.m8n8.x4.shared.b16 [%0], {%1,%2,%3,%4};" ::"r"(a), "r"(r0), "r"(r1), "r"(r2), "r"(r3) : "memory");
}
__device__ __forceinline__ uint2 lds64(uint32_t a) { uint2 v; asm volatile("ld.shared.v2.b32 {%0,%1}, [%2];" : "=r"(v.x), "=r"(v.y) : "r"(a) : "memory"); return v; }
__device__ __forceinline__ uint32_t hmul2(uint32_t a, uint32_t b) { uint32_t r; asm("mul.rn.bf16x2 %0, %1, %2;" : "=r"(r) : "r"(a), "r"(b)); return r; }
__device__ __forceinline__ void wgmma_ss192t(float* d, uint64_t da, uint64_t db, int acc) {
  asm volatile("{.reg .pred p; setp.ne.b32 p, %98, 0;\n"
    "wgmma.mma_async.sync.aligned.m64n192k16.f32.bf16.bf16 "
    "{%0,%1,%2,%3,%4,%5,%6,%7,%8,%9,%10,%11,%12,%13,%14,%15,%16,%17,%18,%19,%20,%21,%22,%23,%24,%25,%26,%27,%28,%29,%30,%31,%32,%33,%34,%35,%36,%37,%38,%39,%40,%41,%42,%43,%44,%45,%46,%47,%48,%49,%50,%51,%52,%53,%54,%55,%56,%57,%58,%59,%60,%61,%62,%63,%64,%65,%66,%67,%68,%69,%70,%71,%72,%73,%74,%75,%76,%77,%78,%79,%80,%81,%82,%83,%84,%85,%86,%87,%88,%89,%90,%91,%92,%93,%94,%95}, %96, %97, p, 1, 1, 0, 1;}"
    : "+f"(d[0]), "+f"(d[1]), "+f"(d[2]), "+f"(d[3]), "+f"(d[4]), "+f"(d[5]), "+f"(d[6]), "+f"(d[7]), "+f"(d[8]), "+f"(d[9]), "+f"(d[10]), "+f"(d[11]),
      "+f"(d[12]), "+f"(d[13]), "+f"(d[14]), "+f"(d[15]), "+f"(d[16]), "+f"(d[17]), "+f"(d[18]), "+f"(d[19]), "+f"(d[20]), "+f"(d[21]), "+f"(d[22]),
      "+f"(d[23]), "+f"(d[24]), "+f"(d[25]), "+f"(d[26]), "+f"(d[27]), "+f"(d[28]), "+f"(d[29]), "+f"(d[30]), "+f"(d[31]), "+f"(d[32]), "+f"(d[33]),
      "+f"(d[34]), "+f"(d[35]), "+f"(d[36]), "+f"(d[37]), "+f"(d[38]), "+f"(d[39]), "+f"(d[40]), "+f"(d[41]), "+f"(d[42]), "+f"(d[43]), "+f"(d[44]),
      "+f"(d[45]), "+f"(d[46]), "+f"(d[47]), "+f"(d[48]), "+f"(d[49]), "+f"(d[50]), "+f"(d[51]), "+f"(d[52]), "+f"(d[53]), "+f"(d[54]), "+f"(d[55]),
      "+f"(d[56]), "+f"(d[57]), "+f"(d[58]), "+f"(d[59]), "+f"(d[60]), "+f"(d[61]), "+f"(d[62]), "+f"(d[63]), "+f"(d[64]), "+f"(d[65]), "+f"(d[66]),
      "+f"(d[67]), "+f"(d[68]), "+f"(d[69]), "+f"(d[70]), "+f"(d[71]), "+f"(d[72]), "+f"(d[73]), "+f"(d[74]), "+f"(d[75]), "+f"(d[76]), "+f"(d[77]),
      "+f"(d[78]), "+f"(d[79]), "+f"(d[80]), "+f"(d[81]), "+f"(d[82]), "+f"(d[83]), "+f"(d[84]), "+f"(d[85]), "+f"(d[86]), "+f"(d[87]), "+f"(d[88]),
      "+f"(d[89]), "+f"(d[90]), "+f"(d[91]), "+f"(d[92]), "+f"(d[93]), "+f"(d[94]), "+f"(d[95])
    : "l"(da), "l"(db), "r"(acc));
}
__device__ __forceinline__ void wgmma_rs128t(float* d, const uint32_t* a, uint64_t db, int acc) {
  asm volatile("{.reg .pred p; setp.ne.b32 p, %69, 0;\n"
    "wgmma.mma_async.sync.aligned.m64n128k16.f32.bf16.bf16 "
    "{%0,%1,%2,%3,%4,%5,%6,%7,%8,%9,%10,%11,%12,%13,%14,%15,%16,%17,%18,%19,%20,%21,%22,%23,%24,%25,%26,%27,%28,%29,%30,%31,%32,%33,%34,%35,%36,%37,%38,%39,%40,%41,%42,%43,%44,%45,%46,%47,%48,%49,%50,%51,%52,%53,%54,%55,%56,%57,%58,%59,%60,%61,%62,%63}, {%64,%65,%66,%67}, %68, p, 1, 1, 1;}"
    : "+f"(d[0]), "+f"(d[1]), "+f"(d[2]), "+f"(d[3]), "+f"(d[4]), "+f"(d[5]), "+f"(d[6]), "+f"(d[7]), "+f"(d[8]), "+f"(d[9]), "+f"(d[10]), "+f"(d[11]),
      "+f"(d[12]), "+f"(d[13]), "+f"(d[14]), "+f"(d[15]), "+f"(d[16]), "+f"(d[17]), "+f"(d[18]), "+f"(d[19]), "+f"(d[20]), "+f"(d[21]), "+f"(d[22]),
      "+f"(d[23]), "+f"(d[24]), "+f"(d[25]), "+f"(d[26]), "+f"(d[27]), "+f"(d[28]), "+f"(d[29]), "+f"(d[30]), "+f"(d[31]), "+f"(d[32]), "+f"(d[33]),
      "+f"(d[34]), "+f"(d[35]), "+f"(d[36]), "+f"(d[37]), "+f"(d[38]), "+f"(d[39]), "+f"(d[40]), "+f"(d[41]), "+f"(d[42]), "+f"(d[43]), "+f"(d[44]),
      "+f"(d[45]), "+f"(d[46]), "+f"(d[47]), "+f"(d[48]), "+f"(d[49]), "+f"(d[50]), "+f"(d[51]), "+f"(d[52]), "+f"(d[53]), "+f"(d[54]), "+f"(d[55]),
      "+f"(d[56]), "+f"(d[57]), "+f"(d[58]), "+f"(d[59]), "+f"(d[60]), "+f"(d[61]), "+f"(d[62]), "+f"(d[63])
    : "r"(a[0]), "r"(a[1]), "r"(a[2]), "r"(a[3]), "l"(db), "r"(acc));
}
__device__ __forceinline__ void wgmma_rs80(float* d, const uint32_t* a, uint64_t db, int acc) {
  asm volatile("{.reg .pred p; setp.ne.b32 p, %45, 0;\n"
    "wgmma.mma_async.sync.aligned.m64n80k16.f32.bf16.bf16 "
    "{%0,%1,%2,%3,%4,%5,%6,%7,%8,%9,%10,%11,%12,%13,%14,%15,%16,%17,%18,%19,%20,%21,%22,%23,%24,%25,%26,%27,%28,%29,%30,%31,%32,%33,%34,%35,%36,%37,%38,%39}, {%40,%41,%42,%43}, %44, p, 1, 1, 0;}"
    : "+f"(d[0]), "+f"(d[1]), "+f"(d[2]), "+f"(d[3]), "+f"(d[4]), "+f"(d[5]), "+f"(d[6]), "+f"(d[7]), "+f"(d[8]), "+f"(d[9]), "+f"(d[10]), "+f"(d[11]),
      "+f"(d[12]), "+f"(d[13]), "+f"(d[14]), "+f"(d[15]), "+f"(d[16]), "+f"(d[17]), "+f"(d[18]), "+f"(d[19]), "+f"(d[20]), "+f"(d[21]), "+f"(d[22]),
      "+f"(d[23]), "+f"(d[24]), "+f"(d[25]), "+f"(d[26]), "+f"(d[27]), "+f"(d[28]), "+f"(d[29]), "+f"(d[30]), "+f"(d[31]), "+f"(d[32]), "+f"(d[33]),
      "+f"(d[34]), "+f"(d[35]), "+f"(d[36]), "+f"(d[37]), "+f"(d[38]), "+f"(d[39])
    : "r"(a[0]), "r"(a[1]), "r"(a[2]), "r"(a[3]), "l"(db), "r"(acc));
}
__device__ __forceinline__ void wgmma_rs64t(float* d, const uint32_t* a, uint64_t db, int acc) {
  asm volatile("{.reg .pred p; setp.ne.b32 p, %37, 0;\n"
    "wgmma.mma_async.sync.aligned.m64n64k16.f32.bf16.bf16 "
    "{%0,%1,%2,%3,%4,%5,%6,%7,%8,%9,%10,%11,%12,%13,%14,%15,%16,%17,%18,%19,%20,%21,%22,%23,%24,%25,%26,%27,%28,%29,%30,%31}, {%32,%33,%34,%35}, %36, p, 1, 1, 1;}"
    : "+f"(d[0]), "+f"(d[1]), "+f"(d[2]), "+f"(d[3]), "+f"(d[4]), "+f"(d[5]), "+f"(d[6]), "+f"(d[7]), "+f"(d[8]), "+f"(d[9]), "+f"(d[10]), "+f"(d[11]),
      "+f"(d[12]), "+f"(d[13]), "+f"(d[14]), "+f"(d[15]), "+f"(d[16]), "+f"(d[17]), "+f"(d[18]), "+f"(d[19]), "+f"(d[20]), "+f"(d[21]), "+f"(d[22]),
      "+f"(d[23]), "+f"(d[24]), "+f"(d[25]), "+f"(d[26]), "+f"(d[27]), "+f"(d[28]), "+f"(d[29]), "+f"(d[30]), "+f"(d[31])
    : "r"(a[0]), "r"(a[1]), "r"(a[2]), "r"(a[3]), "l"(db), "r"(acc));
}
__device__ __forceinline__ void wgmma_rs224t(float* d, const uint32_t* a, uint64_t db, int acc) {
  asm volatile("{.reg .pred p; setp.ne.b32 p, %117, 0;\n"
    "wgmma.mma_async.sync.aligned.m64n224k16.f32.bf16.bf16 "
    "{%0,%1,%2,%3,%4,%5,%6,%7,%8,%9,%10,%11,%12,%13,%14,%15,%16,%17,%18,%19,%20,%21,%22,%23,%24,%25,%26,%27,%28,%29,%30,%31,%32,%33,%34,%35,%36,%37,%38,%39,%40,%41,%42,%43,%44,%45,%46,%47,%48,%49,%50,%51,%52,%53,%54,%55,%56,%57,%58,%59,%60,%61,%62,%63,%64,%65,%66,%67,%68,%69,%70,%71,%72,%73,%74,%75,%76,%77,%78,%79,%80,%81,%82,%83,%84,%85,%86,%87,%88,%89,%90,%91,%92,%93,%94,%95,%96,%97,%98,%99,%100,%101,%102,%103,%104,%105,%106,%107,%108,%109,%110,%111}, {%112,%113,%114,%115}, %116, p, 1, 1, 1;}"
    : "+f"(d[0]), "+f"(d[1]), "+f"(d[2]), "+f"(d[3]), "+f"(d[4]), "+f"(d[5]), "+f"(d[6]), "+f"(d[7]), "+f"(d[8]), "+f"(d[9]), "+f"(d[10]), "+f"(d[11]),
      "+f"(d[12]), "+f"(d[13]), "+f"(d[14]), "+f"(d[15]), "+f"(d[16]), "+f"(d[17]), "+f"(d[18]), "+f"(d[19]), "+f"(d[20]), "+f"(d[21]), "+f"(d[22]),
      "+f"(d[23]), "+f"(d[24]), "+f"(d[25]), "+f"(d[26]), "+f"(d[27]), "+f"(d[28]), "+f"(d[29]), "+f"(d[30]), "+f"(d[31]), "+f"(d[32]), "+f"(d[33]),
      "+f"(d[34]), "+f"(d[35]), "+f"(d[36]), "+f"(d[37]), "+f"(d[38]), "+f"(d[39]), "+f"(d[40]), "+f"(d[41]), "+f"(d[42]), "+f"(d[43]), "+f"(d[44]),
      "+f"(d[45]), "+f"(d[46]), "+f"(d[47]), "+f"(d[48]), "+f"(d[49]), "+f"(d[50]), "+f"(d[51]), "+f"(d[52]), "+f"(d[53]), "+f"(d[54]), "+f"(d[55]),
      "+f"(d[56]), "+f"(d[57]), "+f"(d[58]), "+f"(d[59]), "+f"(d[60]), "+f"(d[61]), "+f"(d[62]), "+f"(d[63]), "+f"(d[64]), "+f"(d[65]), "+f"(d[66]),
      "+f"(d[67]), "+f"(d[68]), "+f"(d[69]), "+f"(d[70]), "+f"(d[71]), "+f"(d[72]), "+f"(d[73]), "+f"(d[74]), "+f"(d[75]), "+f"(d[76]), "+f"(d[77]),
      "+f"(d[78]), "+f"(d[79]), "+f"(d[80]), "+f"(d[81]), "+f"(d[82]), "+f"(d[83]), "+f"(d[84]), "+f"(d[85]), "+f"(d[86]), "+f"(d[87]), "+f"(d[88]),
      "+f"(d[89]), "+f"(d[90]), "+f"(d[91]), "+f"(d[92]), "+f"(d[93]), "+f"(d[94]), "+f"(d[95]), "+f"(d[96]), "+f"(d[97]), "+f"(d[98]), "+f"(d[99]),
      "+f"(d[100]), "+f"(d[101]), "+f"(d[102]), "+f"(d[103]), "+f"(d[104]), "+f"(d[105]), "+f"(d[106]), "+f"(d[107]), "+f"(d[108]), "+f"(d[109]),
      "+f"(d[110]), "+f"(d[111])
    : "r"(a[0]), "r"(a[1]), "r"(a[2]), "r"(a[3]), "l"(db), "r"(acc));
}
__device__ __forceinline__ void wgmma_rs192t(float* d, const uint32_t* a, uint64_t db, int acc) {
  asm volatile("{.reg .pred p; setp.ne.b32 p, %101, 0;\n"
    "wgmma.mma_async.sync.aligned.m64n192k16.f32.bf16.bf16 "
    "{%0,%1,%2,%3,%4,%5,%6,%7,%8,%9,%10,%11,%12,%13,%14,%15,%16,%17,%18,%19,%20,%21,%22,%23,%24,%25,%26,%27,%28,%29,%30,%31,%32,%33,%34,%35,%36,%37,%38,%39,%40,%41,%42,%43,%44,%45,%46,%47,%48,%49,%50,%51,%52,%53,%54,%55,%56,%57,%58,%59,%60,%61,%62,%63,%64,%65,%66,%67,%68,%69,%70,%71,%72,%73,%74,%75,%76,%77,%78,%79,%80,%81,%82,%83,%84,%85,%86,%87,%88,%89,%90,%91,%92,%93,%94,%95}, {%96,%97,%98,%99}, %100, p, 1, 1, 1;}"
    : "+f"(d[0]), "+f"(d[1]), "+f"(d[2]), "+f"(d[3]), "+f"(d[4]), "+f"(d[5]), "+f"(d[6]), "+f"(d[7]), "+f"(d[8]), "+f"(d[9]), "+f"(d[10]), "+f"(d[11]),
      "+f"(d[12]), "+f"(d[13]), "+f"(d[14]), "+f"(d[15]), "+f"(d[16]), "+f"(d[17]), "+f"(d[18]), "+f"(d[19]), "+f"(d[20]), "+f"(d[21]), "+f"(d[22]),
      "+f"(d[23]), "+f"(d[24]), "+f"(d[25]), "+f"(d[26]), "+f"(d[27]), "+f"(d[28]), "+f"(d[29]), "+f"(d[30]), "+f"(d[31]), "+f"(d[32]), "+f"(d[33]),
      "+f"(d[34]), "+f"(d[35]), "+f"(d[36]), "+f"(d[37]), "+f"(d[38]), "+f"(d[39]), "+f"(d[40]), "+f"(d[41]), "+f"(d[42]), "+f"(d[43]), "+f"(d[44]),
      "+f"(d[45]), "+f"(d[46]), "+f"(d[47]), "+f"(d[48]), "+f"(d[49]), "+f"(d[50]), "+f"(d[51]), "+f"(d[52]), "+f"(d[53]), "+f"(d[54]), "+f"(d[55]),
      "+f"(d[56]), "+f"(d[57]), "+f"(d[58]), "+f"(d[59]), "+f"(d[60]), "+f"(d[61]), "+f"(d[62]), "+f"(d[63]), "+f"(d[64]), "+f"(d[65]), "+f"(d[66]),
      "+f"(d[67]), "+f"(d[68]), "+f"(d[69]), "+f"(d[70]), "+f"(d[71]), "+f"(d[72]), "+f"(d[73]), "+f"(d[74]), "+f"(d[75]), "+f"(d[76]), "+f"(d[77]),
      "+f"(d[78]), "+f"(d[79]), "+f"(d[80]), "+f"(d[81]), "+f"(d[82]), "+f"(d[83]), "+f"(d[84]), "+f"(d[85]), "+f"(d[86]), "+f"(d[87]), "+f"(d[88]),
      "+f"(d[89]), "+f"(d[90]), "+f"(d[91]), "+f"(d[92]), "+f"(d[93]), "+f"(d[94]), "+f"(d[95])
    : "r"(a[0]), "r"(a[1]), "r"(a[2]), "r"(a[3]), "l"(db), "r"(acc));
}

struct Desc {
  uint32_t lo, hi;
  __device__ __forceinline__ Desc operator+(uint32_t o) const { return {lo + o, hi}; }
  __device__ __forceinline__ operator uint64_t() const { return ((uint64_t)hi << 32) | lo; }
};
__device__ __forceinline__ Desc mk_desc(uint32_t addr, uint32_t lbo, uint32_t sbo, uint32_t mode) {
  return {(addr >> 4) | ((lbo >> 4) << 16), (sbo >> 4) | (mode << 30)};
}

struct AttMask {
  uint32_t hi, z;
  float c0, c1, mb[10];
  __device__ __forceinline__ AttMask(uint32_t tid, uint32_t sb) {
    constexpr float SCL = 0.07216878364870322f * 1.4426950408889634f;
    hi = pin(tid & 64); z = sb >> 31;
    c0 = hi ? 0.f : SCL; c1 = hi ? SCL : 0.f;
    const int tt = (int)pin(((tid >> 1) & 16) + ((tid >> 2) & 7) - 2 * (tid & 3));
#pragma unroll
    for (int i = 0; i < 10; i++) mb[i] = 8 * ((i >> 1) - 1) + (i & 1) > tt ? -INFINITY : 0.f;
  }
};
__device__ __forceinline__ void att_softmax(const AttMask& m, const float* s_, uint32_t (&p)[5][4], float g0, float g1) {
  const uint32_t hi = m.hi;
  const float c0 = m.c0, c1 = m.c1;
  const float* mb = m.mb;
  float v[20], mx[2], sum[2];
#pragma unroll
  for (int i = 0; i < 20; i++)
    if (i != 16 && i != 17) v[i] = fmaf(s_[20 + i], c1, i < 4 ? s_[i] * c0 : fmaf(s_[i], c0, mb[2 * ((i >> 2) - ((i >> 1) & 1)) + (i & 1)]));
  mx[0] = fmaxf(fmaxf(fmaxf(v[0], v[1]), fmaxf(v[4], v[5])), fmaxf(fmaxf(v[8], v[9]), fmaxf(v[12], v[13])));
  mx[1] = fmaxf(fmaxf(fmaxf(v[2], v[3]), fmaxf(v[6], v[7])), fmaxf(fmaxf(v[10], v[11]), fmaxf(v[14], v[15])));
  mx[1] = fmaxf(mx[1], fmaxf(v[18], v[19]));
  {
    const float ni = __uint_as_float(0xff800000u | m.z), a_ = fminf(mx[0], ni), b_ = fminf(mx[1], ni);
    mx[0] = fmaxf(mx[0], b_); mx[1] = fmaxf(mx[1], a_);
  }
#pragma unroll
  for (int o = 1; o < 4; o <<= 1)
#pragma unroll
    for (int h = 0; h < 2; h++) mx[h] = fmaxf(mx[h], __shfl_xor_sync(~0u, mx[h], o));
#pragma unroll
  for (int i = 0; i < 20; i++) v[i] = i == 16 || i == 17 ? 0.f : ex2(v[i] - mx[(i >> 1) & 1]);
  sum[0] = ((v[0] + v[1]) + (v[4] + v[5])) + ((v[8] + v[9]) + (v[12] + v[13]));
  sum[1] = ((v[2] + v[3]) + (v[6] + v[7])) + ((v[10] + v[11]) + (v[14] + v[15])) + (v[18] + v[19]);
  {
    const float z = __uint_as_float(m.z), a_ = sum[0];
    sum[0] = fmaf(sum[1], z, a_); sum[1] = fmaf(a_, z, sum[1]);
  }
  sum[0] += __shfl_xor_sync(~0u, sum[0], 1);
  sum[1] += __shfl_xor_sync(~0u, sum[1], 1);
  {
    const float z = __uint_as_float(m.z), a_ = sum[0];
    sum[0] = fmaf(sum[1], z, a_); sum[1] = fmaf(a_, z, sum[1]);
  }
  sum[0] += __shfl_xor_sync(~0u, sum[0], 2);
  sum[1] += __shfl_xor_sync(~0u, sum[1], 2);
  const float r0 = g0 * rcp(sum[0]), r1 = g1 * rcp(sum[1]);
#pragma unroll
  for (int j = 0; j < 5; j++)
#pragma unroll
    for (int h = 0; h < 2; h++) {
      const uint32_t pt = j == 4 && h == 0 ? 0u : pack2(v[4 * j + 2 * h] * (h ? r1 : r0), v[4 * j + 2 * h + 1] * (h ? r1 : r0));
      p[j >> 1][(j & 1) * 2 + h] = hi ? 0u : pt;
      p[(j + 5) >> 1][((j + 5) & 1) * 2 + h] = hi ? pt : 0u;
    }
#pragma unroll
  for (int i = 0; i < 20; i++) asm volatile("" : "+r"(p[i >> 2][i & 3]));
}

constexpr int NPQ = 2;
#define NQ 12
#define NQ_WIN 8
#define NO_EARLY 6
#define NO_MID 9
#define NW1 16
#define NW1A 10
#define VLD 6
#define VB 0
#define XPF 3
#define WSPLIT 8
#define NQ_W1 8
#define WD 700
#define PDS 300
#define PDT 50
#define CT 999
#define PFB 8000
#define VBW 3
#define PD 780
constexpr int R_WQ = 0;
constexpr int R_WO = R_WQ + 8 * (20 - NPQ) * 512;
constexpr int R_XT = R_WO + 14 * 12 * 512;
constexpr int R_MEM = R_XT;
constexpr int R_QB = R_XT + 40960;
constexpr int R_QA = R_QB + 1024;
constexpr int R_O2 = R_QA + 1024;
constexpr int R_VS = R_O2 + 1024;
constexpr int R_KT = R_VS + 1024;
constexpr int R_VT = R_KT + 5120;
constexpr int R_V1 = R_VT + 5120;
constexpr int R_SX = R_V1 + 8192;
constexpr int R_VM = R_SX + 4608;
constexpr int R_BAR = R_VM + 2048;
constexpr int R_MI = R_BAR + 64;
constexpr int R_EB = R_MI + 64;
constexpr int R_SMEM = R_EB + 64 + 96;
constexpr int E_KA = 0, E_VA = 30720, E_KB = R_XT + 10240, E_VB0 = 61440, E_VB1 = R_V1, E_VB2 = R_XT;
static_assert(R_V1 + 10240 <= R_BAR && E_VB0 + 10240 <= R_WO, "chunks");
static_assert(NPQ == 2 && R_XT % 1024 == 0 && R_KT % 1024 == 0 && R_VT % 1024 == 0 && R_V1 % 1024 == 0 && R_WO % 1024 == 0, "align");
constexpr int R_SMEM_ALLOC = R_SMEM;
static_assert(R_SMEM_ALLOC <= 232448, "smem");

#define TR(i) do {} while (0)

__device__ __forceinline__ void red_pair(unsigned char* p, float lo, float hi) {
  const int b = __float2int_rn(lo), a = __float2int_rn(hi);
  asm volatile("{.reg .b64 t; mov.b64 t, {%1,%2}; red.relaxed.gpu.global.add.u64 [%0], t;}" ::"l"(p), "r"(b + ((1 << 29) + (1 << 23))), "r"(a * 8) : "memory");
}
__device__ __forceinline__ unsigned long long swap0(unsigned char* p) {
  unsigned long long r;
  asm volatile("atom.relaxed.gpu.global.exch.b64 %0, [%1], 0;" : "=l"(r) : "l"(p) : "memory");
  return r;
}
__device__ __forceinline__ uint32_t dec_pair(uint32_t lo, uint32_t hi, uint32_t bias) { return pack2((float)(int)(lo * 8u + bias), (float)(int)hi); }

__global__ void __cluster_dims__(3, 1, 1) __launch_bounds__(256, 1)
rec_kernel(const __grid_constant__ CUtensorMap tmX, const __grid_constant__ CUtensorMap tmK, const __grid_constant__ CUtensorMap tmV,
           const __grid_constant__ CUtensorMap tmWq, const __grid_constant__ CUtensorMap tmWq2, const __grid_constant__ CUtensorMap tmWk,
           const __grid_constant__ CUtensorMap tmWv, const __grid_constant__ CUtensorMap tmWo, const __grid_constant__ CUtensorMap tmOut,
           const bf16* __restrict__ mem0,
           const bf16* __restrict__ Wq, const bf16* __restrict__ Wk, const bf16* __restrict__ Wv, const bf16* __restrict__ Wo, const bf16* __restrict__ x, const bf16* __restrict__ gate_w,
           bf16* __restrict__ out, unsigned char* __restrict__ red) {
  extern __shared__ __align__(1024) unsigned char smem[];
  const uint32_t sb = smem_u32(smem);
  const int tid = threadIdx.x, lane = tid & 31, wid = __shfl_sync(~0u, tid >> 5, 0), g = wid >> 2, w = wid & 3;
  const int cta = blockIdx.x, head = cta / 3, rank = cta % 3;
  const int D0 = head * DH + rank * 64;
  const int tile0 = rank == 0 ? 0 : (rank == 1 ? 14 : 26);
  const uint32_t XBAR = sb + R_BAR, SBAR = XBAR + 8, OBAR = XBAR + 16, VBAR = XBAR + 24, FBAR = XBAR + 32, WBAR = XBAR + 40;
  constexpr uint32_t ONES = 0x3F803F80u;
  uint32_t ww[40][4], wqp[NPQ][4];
  GTR(0);
  if (wid == 0) {
    if (lane == 0) {
      mbar_init(XBAR, 1); mbar_init(SBAR, 4); mbar_init(OBAR, 5); mbar_init(VBAR, 1); mbar_init(FBAR, 2);
      mbar_init(WBAR, 1); mbar_init(WBAR + 8, 1); mbar_init(WBAR + 16, 1);
      for (int i = 0; i < 6; i++) mbar_init(sb + R_EB + i * 8, i < 4 ? 1 : 2);
      asm volatile("fence.mbarrier_init.release.cluster;" ::: "memory");
      mbar_expect(WBAR, 81920); mbar_expect(WBAR + 8, 81920 + 2 * NPQ * 2048); mbar_expect(XBAR, 40960);
      mbar_expect(SBAR, 3072); mbar_expect(OBAR, 2048); mbar_expect(VBAR, 8192);
      for (int i = 0; i < 4; i++) mbar_expect(sb + R_EB + i * 8, 30720);
      sts128(sb + R_MI + 48, 0, 0, 0, 0);
      sts32(sb + R_MI, *(volatile uint32_t*)&g_epoch + 1);
    }
    __syncwarp();
    if (lane < 5) tma_load2(sb + lane * 16384, &tmWk, D0, lane * 128, WBAR);
    if (lane == 5) tma_load3(sb + R_XT, &tmX, 0, 0, 0, XBAR);
    if (lane < 5) tma_load2(lane < 4 ? sb + 81920 + lane * 16384 : sb + R_QB, &tmWv, D0, lane * 128, WBAR + 8);
    if (lane < 2) tma_load2(sb + R_QB + 16384 + lane * 4096, &tmWq2, D0, lane * 320, WBAR + 8);
  }
  if (tid == 32) { prefetch_map(&tmWq); prefetch_map(&tmWo); prefetch_map(&tmK); prefetch_map(&tmV); prefetch_map(&tmOut); }
  if (tid >= 64 && tid < 144) prefetch_l2(mem0 + (tid - 64) * 64);
  __syncthreads();
  GTR(1);
  asm volatile("griddepcontrol.launch_dependents;" ::: "memory");
  const uint32_t c0 = clk32();
  {
    uint32_t xm = 0;
    {
      const int row = cta * 8 + wid;
      uint4 gw[3], v[3][3];
#pragma unroll
      for (int r = 0; r < 3; r++)
#pragma unroll
        for (int i = 0; i < 3; i++)
          v[r][i] = (i < 2 || lane < 16) && (r < 2 || row < 512) ? __ldg((const uint4*)(x + (size_t)(row + r * 768) * DM) + lane + 32 * i) : make_uint4(0, 0, 0, 0);
#pragma unroll
      for (int i = 0; i < 3; i++) gw[i] = (i < 2 || lane < 16) ? __ldg((const uint4*)gate_w + lane + 32 * i) : make_uint4(0, 0, 0, 0);
      if (wid == 7) {
        spin_until(c0, PFB);
        if (lane < 2) asm volatile("cp.async.bulk.prefetch.tensor.2d.L2.global [%0, {%1,%2}];" ::"l"(&tmWq), "r"(D0), "r"(32 + lane * 144) : "memory");
      }
      if (cta < 80 && tid < 128) ((uint4*)(out + (S_TOK - 128) * DM))[cta * 128 + tid] = make_uint4(0, 0, 0, 0);
      float z = 0.f;
#pragma unroll
      for (int r = 0; r < 3; r++) {
        float s_ = 0.f;
#pragma unroll
        for (int i = 0; i < 3; i++) {
          const uint4 q = v[r][i];
          xm = hmaxabs2(hmaxabs2(xm, hmaxabs2(q.x, q.y)), hmaxabs2(q.z, q.w));
          const uint32_t p0 = hmul2(q.x, gw[i].x), p1 = hmul2(q.y, gw[i].y), p2 = hmul2(q.z, gw[i].z), p3 = hmul2(q.w, gw[i].w);
          s_ += ((bf_lo(p0) + bf_hi(p0)) + (bf_lo(p1) + bf_hi(p1))) + ((bf_lo(p2) + bf_hi(p2)) + (bf_lo(p3) + bf_hi(p3)));
        }
#pragma unroll
        for (int o = 16; o; o >>= 1) s_ += __shfl_xor_sync(~0u, s_, o);
        if (lane == r) z = s_;
      }
      z = bf_lo(pack2(z, 0.f));
      const float gv = bf_lo(pack2(1.f / (1.f + __expf(-z)), 0.f));
      if (lane < 3) sts32(sb + R_EB + 64 + lane * 32 + wid * 4, __float_as_uint(gv));
      asm volatile("fence.proxy.async.global;" ::: "memory");
    }
    xm = __reduce_max_sync(~0u, max((xm << 16) & 0x7fffffffu, xm & 0x7fff0000u));
    const uint32_t p = sb + (lane >> 4) * 1024 + (lane & 7) * 128 + (((2 * w + ((lane >> 3) & 1)) ^ (lane & 7)) << 4);
    mbar_wait(WBAR + 8 * g, 0);
    GTR(2);
#pragma unroll
    for (int f = 0; f < 40; f++) ldsm4t(ww[f], (f >= 32 && g == 1) ? p + R_QB + (f - 32) * 2048 : p + g * 81920 + f * 2048);
    mbar_wait(WBAR + 8, 0);
    GTR(3);
#pragma unroll
    for (int f = 0; f < NPQ; f++) ldsm4t(wqp[f], p + R_QB + 16384 + g * 4096 + f * 2048);
    __syncthreads();
    GTR(5);
    asm volatile("barrier.cluster.arrive.relaxed.aligned;" ::: "memory");
    if (wid == 3 && lane < (cta < 64 ? 24 : 16)) {
      const float gv = __uint_as_float(lds32(sb + R_EB + 64 + lane * 4));
      float* gp = g_gate + cta * 8 + (lane >> 3) * 768 + (lane & 7);
      gp[0] = gv; gp[S_TOK] = bf_lo(pack2(1.f - gv, 0.f));
    }
    if (wid == 0) {
      if (lane == 0) mbar_expect(WBAR + 16, 18 * 4096 + 21 * 4096);
      __syncwarp();
      if (lane < 4) tma_load2(sb + R_WQ + lane * 18432, &tmWq, D0, (lane >> 1) * 320 + 32 + (lane & 1) * 144, WBAR + 16);
      else if (lane < 7) tma_load3(sb + R_WO + ((lane - 1 - rank) % 3) * 28672, &tmWo, 0, head * DH + (lane - 4) * 64, tile0 >> 1, WBAR + 16);
      __syncwarp();
    }
    GTR(6);
    float nv[4] = {0.f, 0.f, 0.f, 0.f};
#pragma unroll
    for (int f = 0; f < 40; f++) {
      const uint32_t a[4] = {ww[f][0] & 0x7fff7fffu, ww[f][1] & 0x7fff7fffu, ww[f][2] & 0x7fff7fffu, ww[f][3] & 0x7fff7fffu};
      mma16816(nv, a, ONES, ONES);
    }
    const uint32_t mv = __reduce_max_sync(~0u, __float_as_uint(fmaxf(nv[0], nv[2])));
    if (lane == 0) { if (g == 1) smax32(sb + R_MI + 48, mv); smax32(sb + R_MI + 52, xm); }
  }
  GTR(4);

  const uint32_t rF_ = opaque(sb + lane * 16);
  const uint32_t rP_ = opaque(sb + (lane >> 4) * 1024 + (lane & 7) * 128 + (((2 * w + ((lane >> 3) & 1)) ^ (lane & 7)) << 4));
  const int tA = g == 1 ? 2 * w : (rank != 1 ? (w < 2 ? 8 + 2 * w : 10 + w) : 8 + w);
  const bool two = g == 1 || (w < 2 && rank != 1);
  const uint32_t r1 = rank == 2 ? 0 : rank + 1, r2 = rank == 0 ? 2 : rank - 1;
  const uint32_t rW_ = opaque(sb + R_WO + (tA >> 1) * 4096 + ((lane >> 4) * 8 + (lane & 7)) * 64 +
                             (((2 * (tA & 1) + ((lane >> 3) & 1)) ^ ((lane >> 1) & 3)) << 4));
  const uint32_t toff = rb_q((tile0 + tA) >> 2) + rb_j(4 * (tile0 + tA)), zoff = rb_q((cta % 20) >> 1) + rb_j((cta % 20) * 8);
  uint32_t wqt[NQ][4];
  float u = 1.f;
  uint32_t t0 = 0;
  int s = -1;

#define WOFF(ks) (((ks) >> 2) * 28672 + ((ks) & 3) * 1024)
#define XDESC(j) (((uint64_t)0x40000040 << 32) | (dlo + ((((j) >> 2) * 4096 + ((j) & 3) * 32) >> 4)))

  auto vsend = [&]() {
    if (elect()) {
      bulk_s2s(mapa(sb + R_V1 + 4096, r1), sb + R_VT + 1024, 4096, mapa(VBAR, r1));
      bulk_s2s(mapa(sb + R_V1, r2), sb + R_VT + 1024, 4096, mapa(VBAR, r2));
    }
    __syncwarp();
  };
  auto window = [&](auto G_, auto KIND_) {
    constexpr int G = decltype(G_)::value;
    constexpr bool FIRST = decltype(KIND_)::value == 0;
    const uint32_t rF = pin(rF_), rP = pin(rP_);
    float d[16];
    const uint32_t dlo = pin(((sb + R_XT) >> 4) | 0x10000);
    const uint32_t wqS = rP + R_WQ + G * (20 - NPQ) * 2048;
    uint4 y[5];
    unsigned long long zr = 0;
    const uint32_t t = w * 32 + ((rF - sb) >> 4);
    if (G == 0) zr = swap0(red + (rb_b(s + 2) + zoff + rb_j(t >> 4) + (t & 15) * 8));
    if (G == 0) {
      if (!FIRST && w == 3) {
        if (elect()) {
          mbar_expect(SBAR, 3072); mbar_expect(OBAR, 2048); mbar_expect(VBAR, 8192);
          asm volatile("mbarrier.arrive.relaxed.cluster.shared::cluster.b64 _, [%0];" ::"r"(mapa(FBAR, r1)) : "memory");
          asm volatile("mbarrier.arrive.relaxed.cluster.shared::cluster.b64 _, [%0];" ::"r"(mapa(FBAR, r2)) : "memory");
        }
        __syncwarp();
      }
    }
    const unsigned char* yp = red + (rb_b(s) + rb_j(t >> 3) + (t & 7) * 16);
    auto poll = [&]() {
      TR(10);
      spin_until(t0, PD);
#pragma unroll
      for (int q = 0; q < 5; q++) y[q] = ldg_rlx128(yp + rb_q(G * 5 + q));
      TR(9);
      sched_fence(sb);
    };
    constexpr int WS = FIRST || G == 1 ? 40 : WSPLIT;
    if (!FIRST && G == 0) {
#pragma unroll
      for (int f = 0; f < NQ_WIN; f++) ldsm4t(wqt[f], wqS + f * 2048);
      asm volatile("" : "+l"(yp));
      mbar_wait(XBAR, (s + 1) & 1);
      if (WS) spin_until(t0, WD);
    } else {
      mbar_wait(XBAR, (s + 1) & 1);
    }
    TR(11);
    if (WS == 0) { poll(); spin_until(t0, WD); }
    wg_fence();
    wgmma_rs32<0>(d, ww[0], XDESC(0));
#pragma unroll
    for (int j = 1; j < WS; j++) wgmma_rs32<1>(d, ww[j], XDESC(j));
    if (FIRST) {
      const unsigned short* m = (const unsigned short*)mem0 + (t & 1) * 4 * DM + G * 320 + (t >> 1);
#pragma unroll
      for (int q = 0; q < 5; q++) y[q] = make_uint4(m[q * 64], m[q * 64 + DM], m[q * 64 + 2 * DM], m[q * 64 + 3 * DM]);
    } else if (G == 0 && WS) {
      poll();
    }
#pragma unroll
    for (int j = WS ? WS : 1; j < 40; j++) wgmma_rs32<1>(d, ww[j], XDESC(j));
    wg_commit();
    if (!FIRST && G == 1) {
      asm volatile("" : "+l"(yp));
      mbar_wait(FBAR, s & 1);
#pragma unroll
      for (int f = 0; f < NQ_W1; f++) ldsm4t(wqt[f], wqS + f * 2048);
      if (w == 1) {
        if (elect()) {
          bulk_wait0();
          asm volatile("red.relaxed.gpu.global.add.u32 [%0], 1;" ::"l"(&g_segcnt[s]) : "memory");
          asm volatile("red.relaxed.gpu.global.add.u32 [%0], 1;" ::"l"(&g_prog) : "memory");
          if (s == NSEG - 2) {
            asm volatile("fence.proxy.async.global;" ::: "memory");
#pragma unroll 1
            for (int b = 0; b < 6; b++)
              tma_load2(sb + b * 10240 + 5120, b < 3 ? &tmK : &tmV, head * DH + (b % 3) * 64, (NSEG - 3) * LK, sb + R_EB + (b / 3) * 8);
          }
        }
        __syncwarp();
      }
    }
    if (FIRST) asm volatile("barrier.cluster.wait.acquire.aligned;" ::: "memory");
    wg_wait0();
    fence_regs<16>(d);
    TR(13);
    bar_arrive(8 + G, 256);
    if (!FIRST && G == 1) poll();
    {
      uint32_t pk[8];
#pragma unroll
      for (int q = 0; q < 8; q++) pk[q] = pack2(d[2 * q], d[2 * q + 1]);
      stsm4t(rP + (G == 1 ? R_VT : R_KT) + 1024, pk[0], pk[1], pk[2], pk[3]);
      stsm4t(rP + (G == 1 ? R_VT : R_KT) + 3072, pk[4], pk[5], pk[6], pk[7]);
      if (G == 1) {
        fence_async_smem();
        if (w != VBW) bar_arrive(6, 128);
        else { bar_sync(6, 128); vsend(); }
      }
    }
    if (FIRST) {
      mbar_wait(WBAR + 16, 0);
      if (G == 0 && cta) GTR(11);
      const uint32_t woA = rW_;
      float na[4] = {0.f, 0.f, 0.f, 0.f}, nb[4] = {0.f, 0.f, 0.f, 0.f};
#pragma unroll
      for (int ks = 0; ks < 12; ks++) {
        uint32_t a[4], b[4];
        ldsm4t(a, woA + WOFF(ks));
        ldsm4t(b, (two ? woA ^ 32 : woA) + WOFF(ks));
#pragma unroll
        for (int q = 0; q < 4; q++) { a[q] &= 0x7fff7fffu; b[q] &= 0x7fff7fffu; }
        mma16816(na, a, ONES, ONES);
        mma16816(nb, b, ONES, ONES);
      }
      const uint32_t mo = __reduce_max_sync(~0u, __float_as_uint(fmaxf(fmaxf(na[0], na[2]), fmaxf(nb[0], nb[2]))));
      if (rF == sb) smax32(sb + R_MI + 56, mo);
      __syncthreads();
      if (G == 1 && w == 2) {
        const uint4 r = lds128(sb + R_MI + 48);
        const uint32_t epoch = lds32(sb + R_MI);
        if (rF == sb) stg_rlx64(&g_rec[cta], (r.y & 0xffff0000u) | (epoch & 0xffffu), ((r.x + 0xffffu) & 0xffff0000u) | ((r.z + 0xffffu) >> 16));
      }
    }
#pragma unroll
    for (int f = FIRST ? 0 : (G == 1 ? NQ_W1 : NQ_WIN); f < NQ; f++) ldsm4t(wqt[f], wqS + f * 2048);
    if (FIRST) sched_fence(sb);
    TR(14);
    const uint32_t ma = sb + R_MEM + G * 5120 + t * 8;
    if (FIRST) {
      bar_sync(9 - G, 256);
#pragma unroll
      for (int j = 0; j < 5; j++) sts64(ma + j * 1024, y[j].x | (y[j].y << 16), y[j].z | (y[j].w << 16));
    } else {
      int n = 0;
#pragma unroll 1
      while (!__all_sync(~0u, (y[0].y & y[0].w & y[1].y) & (y[1].w & y[2].y & y[2].w) & (y[3].y & y[3].w & y[4].y) & (y[4].w & 4))) {
#pragma unroll
        for (int j = 0; j < 5; j++) if (!(y[j].y & y[j].w & 4)) y[j] = ldg_rlx128(yp + rb_q(G * 5 + j));
        if (++n > SPIN_MAX) { g_err = 5; break; }
      }
      const uint32_t bias = 0x80000000u + (sb >> 31);
      bar_sync(9 - G, 256);
#pragma unroll
      for (int j = 0; j < 5; j++) sts64(ma + j * 1024, dec_pair(y[j].x, y[j].y, bias), dec_pair(y[j].z, y[j].w, bias));
    }
    if (G == 0 && zr == ~0ull) g_err = 9;
    TR(0);
  };

  auto oproj = [&](auto TWO_, auto NPRE_, auto& wot, const uint32_t rF, const uint32_t woA, const uint32_t woB,
                   float sm0, float sm1, bool have_sums) {
    constexpr bool TWO = decltype(TWO_)::value;
    constexpr int NPRE = decltype(NPRE_)::value;
    float c[4][4];
#pragma unroll
    for (int q = 0; q < 4; q++) c[q][0] = c[q][1] = c[q][2] = c[q][3] = 0.f;
    unsigned char* sp = red + (rb_b(s) + toff + ((rF - sb) & 256) + (((rF - sb) >> 1) & 120));
    bar_sync(3, 256);
    TR(8);
    uint4 ob[6];
    ob[0] = lds128(rF + R_QB); ob[1] = lds128(rF + R_QB + 512);
    const float2 su = lds64f(sb + R_MI + 48);
    if (!have_sums) { const float2 t = lds64f(sb + R_MI + 16 + (((rF - sb) >> 1) & 24)); sm0 = t.x; sm1 = t.y; }
#pragma unroll
    for (int p = 0; p < 6; p++) {
      if (p + 2 < 6) ob[p + 2] = lds128(rF + (p < 2 ? R_QA : R_O2) + (p & 1) * 512);
#pragma unroll
      for (int e = 0; e < 2; e++) {
        const int ks = 2 * p + e;
        const uint32_t b0 = e ? ob[p].z : ob[p].x, b1 = e ? ob[p].w : ob[p].y;
        if (TWO) {
          const int iA = 2 * ks, iB = iA + 1;
          mma16816(c[e], wot[iA % NPRE], b0, b1);
          if (iA + NPRE < 24) ldsm4t(wot[iA % NPRE], woA + WOFF((iA + NPRE) >> 1));
          mma16816(c[2 + e], wot[iB % NPRE], b0, b1);
          if (iB + NPRE < 24) ldsm4t(wot[iB % NPRE], woB + WOFF((iB + NPRE) >> 1));
        } else {
          mma16816(c[ks & 3], wot[ks], b0, b1);
        }
      }
    }
    const float f0 = su.x * rcp(sm0), f1 = su.x * rcp(sm1);
    t0 = clk32() + (TWO ? (have_sums ? -PDT : 0) : PDS);
    u = su.y;
    if (TWO) {
      red_pair(sp, (c[0][0] + c[1][0]) * f0, (c[0][1] + c[1][1]) * f1);
      red_pair(sp + rb_j(2), (c[0][2] + c[1][2]) * f0, (c[0][3] + c[1][3]) * f1);
      red_pair(sp + rb_j(4), (c[2][0] + c[3][0]) * f0, (c[2][1] + c[3][1]) * f1);
      red_pair(sp + rb_j(6), (c[2][2] + c[3][2]) * f0, (c[2][3] + c[3][3]) * f1);
    } else {
      red_pair(sp, ((c[0][0] + c[1][0]) + (c[2][0] + c[3][0])) * f0, ((c[0][1] + c[1][1]) + (c[2][1] + c[3][1])) * f1);
      red_pair(sp + rb_j(2), ((c[0][2] + c[1][2]) + (c[2][2] + c[3][2])) * f0, ((c[0][3] + c[1][3]) + (c[2][3] + c[3][3])) * f1);
    }
    TR(15);
  };

  auto step = [&](auto G_, auto LAST_) {
    constexpr int G = decltype(G_)::value;
    constexpr bool LAST = decltype(LAST_)::value;
    __syncthreads();
    const uint32_t rF = pin(rF_), rP = pin(rP_);
    TR(1);
    if (LAST) {
      const uint32_t l = (rF - sb) >> 4;
      uint4* qp = g_Ql + ((head * 2 + G) * 4 + w) * 384 + l;
      if ((int)lds32(sb + R_MI + 4) < 0) {
#pragma unroll 1
        for (int i = 0; i < 48; i++) {
          const bf16* xr = x + (size_t)(S_TOK - 128 + G * 64 + w * 16 + (l >> 2) + (i & 1) * 8) * DM;
          const uint32_t* wr = (const uint32_t*)(Wq + head * DH + (i >> 2) * 16 + (l & 3) * 2 + (i & 2) * 4);
          float a0 = 0.f, a1 = 0.f;
#pragma unroll 1
          for (int k = 0; k < DM; k++) {
            const float xv = __bfloat162float(xr[k]);
            const uint32_t wv = wr[k * (HD / 2)];
            a0 = fmaf(xv, bf_lo(wv), a0); a1 = fmaf(xv, bf_hi(wv), a1);
          }
          ((uint32_t*)(qp + (i >> 2) * 32))[i & 3] = pack2(a0, a1);
        }
      }
#pragma unroll
      for (int f = 0; f < 12; f++) { const uint4 t = ldg_rlx128(qp + f * 32); wqt[f][0] = t.x; wqt[f][1] = t.y; wqt[f][2] = t.z; wqt[f][3] = t.w; }
      const float* gp = g_gate + (S_TOK - 128) + G * 64 + w * 16 + ((rF - sb) >> 6);
      wqp[0][0] = ldg_rlx32(gp); wqp[0][1] = ldg_rlx32(gp + 8);
      if (G == 1 && w == 1) {
        mbar_wait(VBAR, (NSEG - 1) & 1);
        if (elect()) {
          asm volatile("mbarrier.arrive.relaxed.cluster.shared::cluster.b64 _, [%0];" ::"r"(mapa(sb + R_EB + 32, r1)) : "memory");
          asm volatile("mbarrier.arrive.relaxed.cluster.shared::cluster.b64 _, [%0];" ::"r"(mapa(sb + R_EB + 32, r2)) : "memory");
          asm volatile("fence.proxy.async.global;" ::: "memory");
#pragma unroll 1
          for (int b = 0; b < 5; b++)
            tma_load2(sb + (b < 3 ? E_KB + b * 10240 : (b == 3 ? E_VB0 : E_VB1)), b < 3 ? &tmK : &tmV, head * DH + (b % 3) * 64, (NSEG - 2) * LK,
                      sb + R_EB + 16 + (b / 3) * 8);
        }
        __syncwarp();
      }
    }
    const uint32_t wqS = rP + R_WQ + G * (20 - NPQ) * 2048, rM = rF + R_MEM;
    const uint32_t l8 = sb + ((rF - sb) >> 1) + w * 256;
    const uint32_t woA = pin(rW_), woB = woA ^ 32;
    float aq[2][4] = {};
    const uint32_t ln = (rF - sb) >> 4;
    const uint32_t rS = sb + (ln & 7) * 128 + (ln < 16 ? R_QB + (ln & 8) * 128 + (((2 * w + G) ^ (ln & 7)) << 4) : R_KT + (((2 * w + ((ln >> 3) & 1)) ^ (ln & 7)) << 4));
    auto qmma = [&](int f, uint32_t b0, uint32_t b1) {
      if (f < NPQ) mma16816(aq[f & 1], wqp[f], b0, b1);
      else {
        const int slot = (f - NPQ) % NQ;
        mma16816(aq[f & 1], wqt[slot], b0, b1);
        if (f + NQ < 20) ldsm4t(wqt[slot], wqS + (f - NPQ + NQ) * 2048);
      }
    };
    if constexpr (G == 1) {
      uint32_t bb[20][4];
      if (!LAST) {
        ldsm4t(bb[10], rM + 5120);
        ldsm4t(bb[11], rM + 5632);
#pragma unroll
        for (int i = 10; i < 20; i++) {
          if (i + 2 < 20) ldsm4t(bb[i + 2], rM + (i + 2) * 512);
          qmma(2 * i - 20, bb[i][0], bb[i][1]);
          qmma(2 * i - 19, bb[i][2], bb[i][3]);
        }
        stsm2t(rS, pack2(aq[0][0] + aq[1][0], aq[0][1] + aq[1][1]), pack2(aq[0][2] + aq[1][2], aq[0][3] + aq[1][3]));
        bar_arrive(1, 256);
      }
      TR(2);
      float av[4][4] = {};
      uint32_t m0 = 0, m1 = 0;
      auto vmma = [&](auto MAX_) {
#pragma unroll
        for (int n = 0; n < 20; n++) {
          const int i = (n + 10) % 20;
          if (LAST && n < 8) ldsm4t(bb[(n + 10) % 20], rM + ((n + 10) % 20) * 512);
          if (LAST && n == 0) { ldsm4t(bb[18], rM + 18 * 512); ldsm4t(bb[19], rM + 19 * 512); }
          if (n == VB && !LAST) { bar_sync(5, 256); sched_fence(sb); }
          if (n == VLD) {
            if (VB != VLD && !LAST) sched_fence(sb);
#pragma unroll
            for (int q = 0; q < 10; q++) ldsm4t(bb[q], rM + q * 512);
            if (!LAST) sched_fence(sb);
          }
          mma16816(av[(2 * n) & 3], ww[2 * i], bb[i][0], bb[i][1]);
          mma16816(av[(2 * n + 1) & 3], ww[2 * i + 1], bb[i][2], bb[i][3]);
          if (decltype(MAX_)::value) { m0 = hmaxabs2(m0, hmaxabs2(bb[i][0], bb[i][1])); m1 = hmaxabs2(m1, hmaxabs2(bb[i][2], bb[i][3])); }
        }
      };
      auto vout = [&]() {
        const uint32_t vm0 = pack2(((av[0][0] + av[1][0]) + (av[2][0] + av[3][0])) * u, ((av[0][1] + av[1][1]) + (av[2][1] + av[3][1])) * u);
        const uint32_t vm1 = pack2(((av[0][2] + av[1][2]) + (av[2][2] + av[3][2])) * u, ((av[0][3] + av[1][3]) + (av[2][3] + av[3][3])) * u);
        if (!LAST) {
          st_async2(mapa(l8 + R_VM + 1024, r1), vm0, vm1, mapa(OBAR, r1));
          st_async2(mapa(l8 + R_VM, r2), vm0, vm1, mapa(OBAR, r2));
          sts64(l8 + R_VS, vm0, vm1);
          __syncwarp();
          if (rF == sb) mbar_arrive(OBAR);
        }
        stsm2t(rP + R_VT, vm0, vm1);
      };
      if (LAST) {
        vmma(std::false_type{});
        vout();
        return;
      }
      uint32_t wot[NW1][4];
      auto wpre = [&](int i0, int i1) {
#pragma unroll
        for (int i = i0; i < i1; i++) ldsm4t(wot[i], ((i & 1) ? woB : woA) + WOFF(i >> 1));
      };
      if (w != 1) {
        vmma(std::false_type{});
        bar_arrive(7, 128);
        vout();
        bar_arrive(2, 128);
        TR(5);
        wpre(0, NW1A);
      } else {
        vmma(std::true_type{});
        bar_sync(7, 128);
        if (elect()) { mbar_expect(XBAR, 40960); tma_load3(sb + R_XT, &tmX, 0, (s + 1) * SEG, 0, XBAR); }
        __syncwarp();
        vout();
        if (XPF && s + XPF < NSEG && rF - sb < 64 && cta < 80) prefetch_l2(x + (size_t)(s + XPF) * SEG * DM + cta * 256 + (rF - sb) * 4);
        TR(5);
        m0 = hmaxabs2(m0, m1);
        const uint32_t mx = __reduce_max_sync(~0u, max((m0 << 16) & 0x7fffffffu, m0 & 0x7fff0000u));
        const float2 mi = lds64f(sb + R_MI + 8);
        wpre(0, NW1A);
        bar_sync(2, 128);
        if (elect()) {
          fence_async_smem();
          tma_store2(&tmK, sb + R_KT, D0, s * LK);
          tma_store2(&tmV, sb + R_VT, D0, s * LK);
          bulk_commit();
        }
        __syncwarp();
        float wb = mi.x, xm = mi.y;
        if (s == 0) {
          const uint32_t epoch = lds32(sb + R_MI);
          uint32_t av_ = 0, ao = 0, xi = 0;
#pragma unroll 1
          for (int j = 0; j < 3; j++) {
            uint2 r;
            int n = 0;
#pragma unroll 1
            while (true) {
              r = ldg_rlx64(&g_rec[j * 32 + ((rF - sb) >> 4)]);
              if (((r.x ^ epoch) & 0xffffu) == 0) break;
              if (++n > SPIN_MAX) { g_err = 6; break; }
            }
            av_ = max(av_, r.y & 0xffff0000u); ao = max(ao, r.y << 16); xi = max(xi, r.x & 0xffff0000u);
          }
          av_ = __reduce_max_sync(~0u, av_); ao = __reduce_max_sync(~0u, ao); xi = __reduce_max_sync(~0u, xi);
          wb = __uint_as_float(av_) * __uint_as_float(ao) * 33.f; xm = __uint_as_float(xi);
          if (rF == sb) {
            sts64f(sb + R_MI + 8, wb, xm);
            asm volatile("fence.acq_rel.gpu;\nred.relaxed.gpu.global.add.u32 [%0], 1;" ::"l"(&g_cnt[C_GATE * 8]) : "memory");
          }
          __syncwarp();
        }
        const float hm = fmaxf(__uint_as_float(mx) * u, xm);
        const uint32_t eb = min(max(__float_as_uint(hm * wb) >> 23, 40u), 200u);
        if (rF == sb) sts64(sb + R_MI + 48, (280u - eb) << 23, (eb - 29u) << 23);
        if (elect()) bulk_wait_read0();
        __syncwarp();
      }
      if (NW1A < NW1) {
        bar_sync(4, 256);
        wpre(NW1A, NW1);
      }
      TR(6);
      oproj(std::true_type{}, std::integral_constant<int, NW1>{}, wot, rF, woA, woB, 0.f, 0.f, false);
    } else {
      {
        uint32_t bb[20][4];
        float ak[4][4] = {};
        ldsm4t(bb[0], rM);
        ldsm4t(bb[10], rM + 5120);
#pragma unroll
        for (int i = 0; i < 10; i++) {
          if (i + 1 < 10) { ldsm4t(bb[i + 1], rM + (i + 1) * 512); ldsm4t(bb[i + 11], rM + (i + 11) * 512); }
          mma16816(ak[0], ww[2 * i], bb[i][0], bb[i][1]);
          if (!LAST) qmma(2 * i, bb[i][0], bb[i][1]);
          mma16816(ak[1], ww[2 * i + 1], bb[i][2], bb[i][3]);
          if (!LAST) qmma(2 * i + 1, bb[i][2], bb[i][3]);
          mma16816(ak[2], ww[2 * i + 20], bb[i + 10][0], bb[i + 10][1]);
          mma16816(ak[3], ww[2 * i + 21], bb[i + 10][2], bb[i + 10][3]);
        }
#pragma unroll
        for (int q = 0; q < 4; q++) { ak[0][q] += ak[2][q]; ak[1][q] += ak[3][q]; }
        stsm4t(rS, pack2(aq[0][0] + aq[1][0], aq[0][1] + aq[1][1]), pack2(aq[0][2] + aq[1][2], aq[0][3] + aq[1][3]),
               pack2((ak[0][0] + ak[1][0]) * u, (ak[0][1] + ak[1][1]) * u), pack2((ak[0][2] + ak[1][2]) * u, (ak[0][3] + ak[1][3]) * u));
      }
      if (LAST) return;
      bar_sync(1, 256);
      bar_arrive(5, 256);
      TR(2);
      if (w != 3) {
        uint32_t qa[4][4], kk[4][4];
        float x[4][4] = {};
#pragma unroll
        for (int i = 0; i < 4; i++) { ldsm4(qa[i], (rP ^ (i << 5)) + R_QB); ldsm4(kk[i], ((rP ^ (i << 5)) + w * 2048) + R_KT); }
        const uint32_t dst = rF + R_SX + rank * 1536 + w * 512;
        const uint32_t e1 = mapa(dst, r1), e2 = mapa(dst, r2), s1 = mapa(SBAR, r1), s2 = mapa(SBAR, r2);
#pragma unroll
        for (int i = 0; i < 4; i++) { mma16816(x[i & 1], qa[i], kk[i][0], kk[i][1]); mma16816(x[2 + (i & 1)], qa[i], kk[i][2], kk[i][3]); }
        const uint32_t u0 = __float_as_uint((x[0][0] + x[0][2]) + (x[1][0] + x[1][2])), u1 = __float_as_uint((x[0][1] + x[0][3]) + (x[1][1] + x[1][3]));
        const uint32_t u2 = __float_as_uint((x[2][0] + x[2][2]) + (x[3][0] + x[3][2])), u3 = __float_as_uint((x[2][1] + x[2][3]) + (x[3][1] + x[3][3]));
        st_async4(e1, u0, u1, u2, u3, s1);
        st_async4(e2, u0, u1, u2, u3, s2);
        sts128(dst, u0, u1, u2, u3);
        __syncwarp();
        if (rF == sb) mbar_arrive(SBAR);
      } else if (s == NSEG - 2) {
        sts32(sb + R_MI + 4, ldg_rlx32(&g_cnt[(C_O + 240 + (head >> 1)) * 8]) - lds32(sb + R_MI) * 2);
        asm volatile("fence.acquire.gpu; fence.proxy.async.global;" ::: "memory");
        if (elect()) {
#pragma unroll 1
          for (int b = 0; b < 6; b++)
            tma_load2(sb + b * 10240, b < 3 ? &tmK : &tmV, head * DH + (b % 3) * 64, (NSEG - 4) * LK, sb + R_EB + (b / 3) * 8);
        }
        __syncwarp();
      }
      TR(4);
      mbar_wait(VBAR, s & 1);
      uint32_t wot[12][4], va[3][8];
      ldsm4t(va[0], rP + R_VT + 1024); ldsm4t(va[0] + 4, rP + R_VT + 3072);
#pragma unroll
      for (int q = 0; q < 4; q++) ldsm4t(va[1 + (q >> 1)] + (q & 1) * 4, rP + R_V1 + q * 2048);
      auto wpre = [&](int i0, int i1) {
        if (two) {
#pragma unroll
          for (int i = i0; i < i1; i++) ldsm4t(wot[i], ((i & 1) ? woB : woA) + WOFF(i >> 1));
        } else {
#pragma unroll
          for (int i = i0; i < i1; i++) ldsm4t(wot[i], woA + WOFF(i));
        }
      };
      wpre(0, NO_EARLY);
      const uint32_t dst = rF + (w >> 1) * 512 + (w & 1) * 8;
      const float scl = u * (0.07216878364870322f * 1.4426950408889634f);
      mbar_wait(SBAR, s & 1);
      TR(6);
      float sc[10];
      {
        const float4 a0 = lds128f(rF + R_SX), b0 = lds128f(rF + R_SX + 1536), c0 = lds128f(rF + R_SX + 3072);
        const float4 a1 = lds128f(rF + R_SX + 512), b1 = lds128f(rF + R_SX + 2048), c1 = lds128f(rF + R_SX + 3584);
        const float2 a2 = lds64f(rF + R_SX + 1024), b2 = lds64f(rF + R_SX + 2560), c2 = lds64f(rF + R_SX + 4096);
        sc[8] = a0.x + b0.x + c0.x; sc[9] = a0.y + b0.y + c0.y; sc[0] = a0.z + b0.z + c0.z; sc[1] = a0.w + b0.w + c0.w;
        sc[2] = a1.x + b1.x + c1.x; sc[3] = a1.y + b1.y + c1.y; sc[4] = a1.z + b1.z + c1.z; sc[5] = a1.w + b1.w + c1.w;
        sc[6] = a2.x + b2.x + c2.x; sc[7] = a2.y + b2.y + c2.y;
      }
      float mx = fmaxf(fmaxf(fmaxf(sc[0], sc[1]), fmaxf(sc[2], sc[3])), fmaxf(fmaxf(sc[4], sc[5]), fmaxf(sc[6], sc[7])));
      mx = fmaxf(mx, fmaxf(sc[8], sc[9]));
      mx = fmaxf(mx, __shfl_xor_sync(~0u, mx, 1));
      const bool vok = mbar_test(OBAR, s & 1);
      mx = fmaxf(mx, __shfl_xor_sync(~0u, mx, 2));
      if (NW1A < NW1) bar_arrive(4, 256);
      const float mo = mx * scl;
      uint32_t pb[5];
#pragma unroll
      for (int j = 0; j < 5; j++) pb[j] = pack2(ex2(fmaf(sc[2 * j], scl, -mo)), ex2(fmaf(sc[2 * j + 1], scl, -mo)));
      if (!vok) mbar_wait(OBAR, s & 1);
      const uint2 m0 = lds64(l8 + R_VS), m1 = lds64(l8 + R_VM), m2 = lds64(l8 + R_VM + 1024);
      const uint32_t ones[4] = {ONES, ONES, ONES, ONES};
      float o[3][4], o2[3][4], sm[4] = {0.f, 0.f, 0.f, 0.f}, sn[4] = {0.f, 0.f, 0.f, 0.f}, so[4] = {0.f, 0.f, 0.f, 0.f};
#pragma unroll
      for (int b = 0; b < 3; b++) {
        o[b][0] = o[b][1] = o[b][2] = o[b][3] = o2[b][0] = o2[b][1] = o2[b][2] = o2[b][3] = 0.f;
        mma16816(o[b], va[b], pb[0], pb[1]);
      }
#pragma unroll
      for (int b = 0; b < 3; b++) mma16816(o2[b], va[b] + 4, pb[2], pb[3]);
      mma1688(o[0], m0.x, m0.y, pb[4]);
      mma1688(o[1], m1.x, m1.y, pb[4]);
      mma1688(o[2], m2.x, m2.y, pb[4]);
      mma16816(sm, ones, pb[0], pb[1]);
      mma16816(sn, ones, pb[2], pb[3]);
      mma1688(so, ONES, ONES, pb[4]);
      wpre(NO_EARLY, NO_MID);
#pragma unroll
      for (int b = 0; b < 3; b++)
        sts64(dst + (b == 0 ? R_QB : (b == 1 ? R_QA : R_O2)), movmat(pack2(o[b][0] + o2[b][0], o[b][1] + o2[b][1])),
              movmat(pack2(o[b][2] + o2[b][2], o[b][3] + o2[b][3])));
      sm[0] += sn[0] + so[0]; sm[1] += sn[1] + so[1];
      if (rF - sb < 64) sts64f(sb + R_MI + 16 + ((rF - sb) >> 1), sm[0], sm[1]);
      wpre(NO_MID, 12);
      TR(7);
      if (two) oproj(std::true_type{}, std::integral_constant<int, 12>{}, wot, rF, woA, woB, sm[0], sm[1], true);
      else oproj(std::false_type{}, std::integral_constant<int, 12>{}, wot, rF, woA, woB, sm[0], sm[1], true);
    }
  };

  if (g == 0) {
    window(std::integral_constant<int, 0>{}, std::integral_constant<int, 0>{});
    GTR(7);
#pragma unroll 1
    for (s = 0; s < NSEG - 1; s++) {
      step(std::integral_constant<int, 0>{}, std::false_type{});
      window(std::integral_constant<int, 0>{}, std::integral_constant<int, 1>{});
    }
    step(std::integral_constant<int, 0>{}, std::true_type{});
  } else {
    window(std::integral_constant<int, 1>{}, std::integral_constant<int, 0>{});
#pragma unroll 1
    for (s = 0; s < NSEG - 1; s++) {
      step(std::integral_constant<int, 1>{}, std::false_type{});
      window(std::integral_constant<int, 1>{}, std::integral_constant<int, 1>{});
    }
    step(std::integral_constant<int, 1>{}, std::true_type{});
  }
  fence_async_smem();
  __syncthreads();
  GTR(8);
#define CG(i) do {} while (0)
  if (wid == 5) {
    if (elect()) {
      const uint32_t kd = sb + E_KB + rank * 10240 + 5120, vd = sb + (rank == 0 ? E_VB0 : (rank == 1 ? E_VB1 : E_VB2)) + 5120;
      if (rank != 2) asm volatile("mbarrier.arrive.relaxed.cluster.shared::cluster.b64 _, [%0];" ::"r"(mapa(sb + R_EB + 40, 2)) : "memory");
      mbar_wait(sb + R_EB + 32, 0);
#pragma unroll 1
      for (uint32_t r = 0; r < 3; r++) bulk_s2s(mapa(kd, r), sb + R_KT, 5120, mapa(sb + R_EB + 16, r));
      tma_load2(sb + E_VB2, &tmV, head * DH + 128, (NSEG - 2) * LK, sb + R_EB + 24);
      if (rank == 2) mbar_wait(sb + R_EB + 40, 0);
#pragma unroll 1
      for (uint32_t r = 0; r < 3; r++) bulk_s2s(mapa(vd, r), sb + R_VT, 5120, mapa(sb + R_EB + 24, r));
      asm volatile("red.relaxed.gpu.global.add.u32 [%0], 1;" ::"l"(&g_prog) : "memory");
    }
    __syncwarp();
  }
  {
    const uint32_t kb = sb + (g ? E_KB : E_KA);
    float sc[40] = {};
    uint32_t pf[5][4];
    mbar_wait(sb + R_EB + g * 16, 0);
    CG(11);
    wg_fence();
#pragma unroll
    for (int ks = 0; ks < 12; ks++) wgmma_rs80(sc, wqt[ks], mk_desc(kb, 16, 1024, 1) + (((ks >> 2) * 10240 + (ks & 3) * 32) >> 4), ks);
    wg_commit();
    const AttMask am(tid, sb);
    wg_wait0();
    fence_regs<40>(sc);
    CG(12);
    att_softmax(am, sc, pf, __uint_as_float(wqp[0][0]), __uint_as_float(wqp[0][1]));
    float o[96] = {};
    mbar_wait(sb + R_EB + g * 16 + 8, 0);
    CG(13);
    wg_fence();
#pragma unroll
    for (int b = 0; b < 3; b++) {
      const Desc db = mk_desc(sb + (g ? (b == 0 ? E_VB0 : (b == 1 ? E_VB1 : E_VB2)) : E_VA + b * 10240), 1024, 1024, 1);
#pragma unroll
      for (int ks = 0; ks < 5; ks++) wgmma_rs64t(o + 32 * b, pf[ks], db + ks * 128, ks);
    }
    wg_commit();
    wg_wait0();
    fence_regs<96>(o);
    CG(14);
    uint32_t of[12][4];
#pragma unroll
    for (int i = 0; i < 48; i++) asm volatile("cvt.rn.bf16x2.f32 %0, %1, %2;" : "=r"(of[i >> 2][i & 3]) : "f"(o[2 * i + 1]), "f"(o[2 * i]));
    float y[112] = {};
    wg_fence();
#pragma unroll
    for (int j = 0; j < 3; j++) {
      const Desc db = mk_desc((sb & 0x3ffff) + R_WO + ((j + 3 - rank) % 3) * 28672, 4096, 512, 2);
#pragma unroll
      for (int ks = 0; ks < 4; ks++) wgmma_rs224t(y, of[4 * j + ks], db + ks * 64, j + ks);
    }
    wg_commit();
    wg_wait0();
    fence_regs<112>(y);
    CG(15);
    const uint32_t da = kb + (w * 16 + (lane & 15)) * 64, sx = (lane >> 1) & 3;
#pragma unroll
    for (int i = 0; i < 14; i++)
      stsm4(da + (i >> 1) * 4096 + (((2 * (i & 1) + (lane >> 4)) ^ sx) << 4), pack2(y[8 * i], y[8 * i + 1]), pack2(y[8 * i + 2], y[8 * i + 3]),
            pack2(y[8 * i + 4], y[8 * i + 5]), pack2(y[8 * i + 6], y[8 * i + 7]));
    fence_async_smem();
    bar_sync(1 + g, 128);
    if (w == 0 && elect()) {
#pragma unroll 1
      for (int i = 0; i < (rank == 1 ? 6 : 7); i++) tma_red2(&tmOut, kb + i * 4096, tile0 * 16 + i * 32, S_TOK - 128 + g * 64);
      bulk_commit();
      bulk_wait0();
    }
  }
  GTR(9);
}

enum { IT_QKV = 1, IT_XATT = 2, IT_OUT = 3, IT_BATT = 4, IT_Q = 5, IT_INIT = 6, IT_END = 7 };
constexpr uint32_t NONE = ~0u;
#define HP 0x1224468888888888ull
#define XD 0x4888888888888999ull
#define KREQ 4
#define ADELAY 7000
#define W_PRO 11
#define W_SCH 8
#define W_AG1 10
#define CVTS 6
#define RSL 20
#define PACE 500
#define XPP 22
#define PP 3
__host__ __device__ constexpr uint32_t mk_item(int ty, int t, int a, int b = 0, int c = 0) { return ty | (t << 3) | (a << 8) | (b << 16) | (c << 24); }
struct ItemTab { uint32_t v[1280]; int n; };
constexpr ItemTab make_items() {
  ItemTab T{};
  int n = 0;
  for (int a = 0; a < 16; a++) T.v[n++] = mk_item(IT_Q, 15, a);
  for (int t = 0; t < 16; t++) for (int a = 0; a < 5; a++) T.v[n++] = mk_item(IT_QKV, t, a);
  for (int t = 0; t < 32; t++) T.v[n++] = mk_item(IT_BATT, t, 0);
  for (int t = 0; t < 16; t++) for (int a = 0; a < 2; a++) T.v[n++] = mk_item(IT_INIT, t, a);
#define NOOUT 15
  for (int t = 0; t < NOOUT; t++) {
    const int hp = (HP >> 4 * t) & 15;
    for (int h = 0; h < 32; h += hp) for (int a = 0; a < 2; a++) T.v[n++] = mk_item(IT_OUT, t, a, h, h + hp < 32 ? h + hp : 32);
  }
  T.n = n;
  return T;
}
constexpr ItemTab k_items_host = make_items();
constexpr int NITEMS = k_items_host.n;
__constant__ ItemTab c_items = make_items();

constexpr int NST = 7, STG = 32768;
constexpr int A_FULL = NST * STG, A_EMPTY = A_FULL + 64, A_ITEM = A_EMPTY + 64, A_QBAR = A_ITEM + 32, A_QENT = A_QBAR + 128, A_MISC = A_QENT + 256,
              A_SMEM = A_MISC + 64, A_REQ = A_FULL + 56, A_RSP = A_EMPTY + 56, A_MAIL = A_MISC + 48, A_RDY = A_MISC + 32;
static_assert(A_SMEM <= 232448, "smem");
enum { OP_END = 0, OP_O = 1, OP_QKV = 2, OP_OB = 3, OP_SET = 4, OP_ADD = 5, OP_Q = 6 };

struct AuxMaps { CUtensorMap xA, wq, wqkv, wo, wob, k, v, oA, oS, obA, obS, qkvS, qkvQ, qkvK, out; };

__device__ __forceinline__ void mbar_wait_long(uint32_t b, uint32_t par) {
  int n = 0;
#pragma unroll 1
  while (!mbar_try(b, par)) { if (++n > (SPIN_MAX << 4)) { g_err = 8; break; } }
}
__device__ __forceinline__ void mbar_wait_u(uint32_t b, uint32_t par) {
  asm volatile("{.reg .pred p; .reg .u32 n;\nmov.u32 n, 0;\nLW: mbarrier.try_wait.parity.shared::cta.b64 p, [%0], %1;\n@p bra.uni LD;\n"
               "add.u32 n, n, 1;\nsetp.lt.u32 p, n, %2;\n@p bra.uni LW;\nLD:\n}" ::"r"(b), "r"(par), "n"(SPIN_MAX << 4) : "memory");
}
__global__ void __launch_bounds__(384, 1)
aux_kernel(const __grid_constant__ AuxMaps tm) {
  extern __shared__ __align__(1024) unsigned char smem[];
  const uint32_t sb = smem_u32(smem);
  const int tid = threadIdx.x, lane = tid & 31, wid = __shfl_sync(~0u, tid >> 5, 0);
  uint32_t epoch = 0;
  const uint32_t c0 = clk32();
  if (tid == W_SCH * 32) GTA(0);
  if (tid >= 256) epoch = *(volatile uint32_t*)&g_epoch + 1;
  if (tid == 0) {
    mbar_init(sb + A_REQ, 1); mbar_init(sb + A_RSP, 1); mbar_init(sb + A_RDY, 1);
    for (int i = 0; i < NST; i++) { mbar_init(sb + A_FULL + i * 8, 1); mbar_init(sb + A_EMPTY + i * 8, 8); }
    for (int i = 0; i < 16; i++) mbar_init(sb + A_QBAR + i * 8, 4);
    asm volatile("fence.mbarrier_init.release.cluster;" ::: "memory");
    const uint32_t b = blockIdx.x;
    sts128(sb + A_MAIL, b < 16 ? mk_item(IT_Q, 15, b) : mk_item(IT_QKV, (b - 16) / 5, (b - 16) % 5), 1, b, PACE);
    mbar_arrive(sb + A_RSP);
  }
  if (tid < 15) prefetch_map(&tm.xA + tid);
  if (tid == W_SCH * 32) GTA(4);
  __syncthreads();
  if (tid == W_SCH * 32) GTA(5);
  uint32_t st = 0, ph = 0;
  auto advance = [&]() { if (++st == NST) { st = 0; ph ^= 1; } };

  if (wid >= 8) {
    asm volatile("setmaxnreg.dec.sync.aligned.u32 40;");
    if (tid == W_SCH * 32) GTA(6);
    auto cnt = [&](int c, uint32_t per) -> bool { return (int)(ldg_rlx32(&g_cnt[c * 8]) - epoch * per) >= 0; };
    auto ready = [&](uint32_t item) -> int {
      const int ty = item & 7, t = (item >> 3) & 31, b = (item >> 17) & 127, n = (((item >> 24) + 1) >> 1) - b;
      int r;
      if (ty == IT_OUT) {
        const int c = C_O + t * 16 + b;
        const bool r0 = cnt(c, 2), r1 = cnt(c + (n > 1), 2), r2 = cnt(c + (n > 2) * 2, 2), r3 = cnt(c + (n > 3) * 3, 2);
        r = r0 & cnt(C_ACC + t, 4) ? (r1 ? (r2 ? (r3 ? 4 : 3) : 2) : 1) : 0;
      } else if (ty == IT_XATT) {
        const uint4 v = ldg_rlx128(&g_segcnt[4 * t]);
        const uint32_t e = epoch * 96;
        r = ((int)(v.x - e) >= 0) & ((int)(v.y - e) >= 0) & ((int)(v.z - e) >= 0) & ((int)(v.w - e) >= 0);
      } else if (ty == IT_BATT) {
        r = cnt(C_GATE, NGATE) & cnt(C_QKV + (t >> 1), 10) & cnt(C_QKV + (max(t - 1, 0) >> 1), 10);
      } else {
        r = ty == IT_QKV || ty == IT_Q || cnt(C_OB + t, 8);
      }
      asm volatile("fence.acquire.gpu; fence.proxy.async.global;" ::: "memory");
      return r;
    };
    if (wid == W_SCH && lane == 0) {
      uint32_t pend = NONE;
      bool xleft = true;
      uint32_t nidx = 0, pidx = 0;
#pragma unroll 1
      for (uint32_t e = 1;; e++) {
        mbar_wait_long(sb + A_REQ, (e - 1) & 1);
        uint32_t item = NONE;
        int rdy = 0, spins = 0;
#pragma unroll 1
        while (true) {
          const bool fresh = pend == NONE;
          uint4 c;
          uint32_t pr = 0;
          bool gates = false;
          if (xleft) {
            c = ldg_rlx128(&g_queue[0]);
            pr = ldg_rlx32(&g_prog) - (epoch - 1) * (96 * NSEG);
            gates = cnt(C_GATE, NGATE);
          }
          auto need = [&](uint32_t it) { return (it & 7) == IT_OUT && xleft ? (((it >> 24) + 1) >> 1) - ((it >> 17) & 127) : 1; };
          if (!fresh) rdy = ready(pend);
          if (xleft && (fresh || pend == IT_END || rdy < need(pend))) {
            auto full = [](uint32_t v) { v = (v | (v >> 2)) & 0x30303030u; return __popc((v | (v >> 1)) & 0x10101010u); };
            const int t = full(c.x) + full(c.y) + full(c.z) + full(c.w);
            xleft = t < 15;
            if (xleft && gates && (int)pr >= 96 * (4 * t - 8 + (int)((XD >> 4 * t) & 15))) {
              const uint32_t j = (atomicAdd(&g_queue[t >> 2], 1u << (t & 3) * 8) >> (t & 3) * 8) & 255;
              if (j < 16) { item = mk_item(IT_XATT, t, j); rdy = 0; nidx = NITEMS + 132 + t * 16 + j; }
            }
          }
          if (item == NONE) {
            if (fresh) {
              pidx = atomicAdd(&g_queue[32], 1u) + gridDim.x;
              pend = pidx < (uint32_t)NITEMS ? c_items.v[pidx] : (uint32_t)IT_END;
              rdy = ready(pend);
            }
            if (pend == IT_END ? !xleft : rdy >= need(pend)) { item = pend; pend = NONE; nidx = pidx; }
          }
          if (item != NONE) break;
          if (++spins > SPIN_MAX) { g_err = 10; item = IT_END; break; }
          __nanosleep(50);
        }
        sts128(sb + A_MAIL, item, rdy, nidx, xleft ? PACE : 0);
        mbar_arrive(sb + A_RSP);
        if (item == IT_END) break;
        if ((item & 7) == IT_XATT) {
#pragma unroll 1
          for (spins = 0; !ready(item); __nanosleep(RSL))
            if (++spins > SPIN_MAX) { g_err = 11; break; }
          mbar_arrive(sb + A_RDY);
        }
      }
      if (atomicAdd(&g_queue[64], 1u) == gridDim.x - 1) { *(uint4*)g_queue = make_uint4(0, 0, 0, 0); g_queue[32] = 0; g_queue[64] = 0; g_epoch = epoch; }
      asm volatile("griddepcontrol.wait;" ::: "memory");
    } else if (wid == W_PRO) {
      uint32_t xph = 0, tl = c0;
      int pace = 0;
      if (ADELAY) spin_until(c0, ADELAY);
      auto arm = [&](uint32_t bytes) -> uint32_t {
        mbar_wait_u(sb + A_EMPTY + st * 8, ph ^ 1);
        if (PACE && bytes) { spin_until(tl, pace); tl = clk32(); }
        return sb + st * STG;
      };
#pragma unroll 1
      for (uint32_t e = 0;; e++) {
        mbar_wait_long(sb + A_RSP, e & 1);
        const uint4 mail = lds128(sb + A_MAIL);
        asm volatile("fence.proxy.async.global;" ::: "memory");
        const uint32_t item = __shfl_sync(~0u, mail.x, 0);
        pace = mail.w;
        const int ty = item & 7, t = (item >> 3) & 31, a = (item >> 8) & 255;
        arm(0);
        if (elect()) {
          sts32(sb + A_ITEM + st * 4, item);
        }
        if (ty == IT_OUT || ty == IT_INIT) {
          const bool out_ = ty == IT_OUT;
          const CUtensorMap *pa = out_ ? &tm.oA : &tm.obA, *pb = out_ ? &tm.wo : &tm.wob;
          int k = out_ ? ((item >> 16) & 255) * 6 : 0;
          const int k1 = out_ ? (item >> 24) * 6 : 20, kreq = max(k1 - KREQ, k);
          int kdep = out_ ? (((item >> 17) & 127) + __shfl_sync(~0u, mail.y, 0)) * 12 : 20;
#pragma unroll 1
          for (; k < k1; k++) {
            if (k >= kdep) {
              int n = 0;
#pragma unroll 1
              while (k >= (kdep = (((item >> 17) & 127) + __shfl_sync(~0u, ready(item), 0)) * 12)) {
                if (++n > SPIN_MAX) { g_err = 7; break; }
                __nanosleep(20);
              }
            }
            PTR((item & 255) == PT && lane == 0, 0, k & 63);
            const uint32_t d = arm(1), fb = sb + A_FULL + st * 8;
            PTR((item & 255) == PT && lane == 0, 1, k & 63);
            if (elect()) {
              mbar_expect(fb, 28672);
              tma_load2(d, pa, k * 32, t * 128, fb);
              tma_load3(d + 8192, pb, 0, k * 32, a * 5, fb);
              if (k == kreq) mbar_arrive(sb + A_REQ);
            }
            PTR((item & 255) == PT && lane == 0, 2, k & 63);
            advance();
          }
        } else if (ty == IT_QKV || ty == IT_XATT || ty == IT_Q) {
          const CUtensorMap* pb = ty == IT_QKV ? &tm.wqkv : &tm.wq;
          const int kreq = ty == IT_XATT ? 28 - KREQ : 20 - KREQ;
#pragma unroll 1
          for (int k = 0; k < 20; k++) {
            PTR((item & 255) == PT && lane == 0, 0, k & 63);
            const uint32_t d = arm(1), fb = sb + A_FULL + st * 8;
            PTR((item & 255) == PT && lane == 0, 1, k & 63);
            if (elect()) {
              mbar_expect(fb, 32768);
              tma_load2(d, &tm.xA, k * 32, t * 128, fb);
              tma_load3(d + 8192, pb, 0, k * 32, a * 6, fb);
              if (k == kreq) mbar_arrive(sb + A_REQ);
            }
            PTR((item & 255) == PT && lane == 0, 2, k & 63);
            advance();
          }
          if (ty == IT_XATT) {
            mbar_wait_long(sb + A_RDY, xph);
            xph ^= 1;
            asm volatile("fence.proxy.async.global;" ::: "memory");
#pragma unroll 1
            for (int k = 20; k < 28; k++) {
              PTR((item & 255) == PT && lane == 0, 0, k & 63);
              const uint32_t d = arm(1), fb = sb + A_FULL + st * 8;
              PTR((item & 255) == PT && lane == 0, 1, k & 63);
              if (elect()) {
                mbar_expect(fb, 30720);
                tma_load3(d, k < 24 ? &tm.k : &tm.v, 0, (4 * t + (k & 2)) * LK, (2 * a + (k & 1)) * 3, fb);
                if (k == kreq) mbar_arrive(sb + A_REQ);
              }
              PTR((item & 255) == PT && lane == 0, 2, k & 63);
              advance();
            }
          }
        } else if (ty == IT_BATT) {
#pragma unroll 1
          for (int k = 0, j = 0, c = 0; k < 12; k++) {
            PTR((item & 255) == PT && lane == 0, 0, k & 63);
            const uint32_t d = arm(1), fb = sb + A_FULL + st * 8;
            PTR((item & 255) == PT && lane == 0, 1, k & 63);
            if (elect()) {
              mbar_expect(fb, c ? 25600 : 20480);
              tma_load3(d, c ? &tm.qkvK : &tm.qkvQ, 0, t * 32 - (c ? 8 : 0), (j & 1) * 30 + (j >> 1) * 5 + c, fb);
              if (k == 6) mbar_arrive(sb + A_REQ);
            }
            PTR((item & 255) == PT && lane == 0, 2, k & 63);
            if (c == 20) { c = 0; j++; } else c += 10;
            advance();
          }
        } else {
          if (elect()) { mbar_arrive(sb + A_FULL + st * 8); mbar_arrive(sb + A_REQ); }
          advance();
        }
        if (item == IT_END) break;
        if ((0x6a >> ty) & 1) {
#pragma unroll 1
          for (int k = 0; k < 4; k++) {
            arm(0);
            if (elect()) mbar_arrive(sb + A_FULL + st * 8);
            advance();
          }
        }
      }
    } else if (lane == 0) {
      const uint32_t qb = sb + A_QBAR + (wid == W_AG1) * 64, qe = sb + A_QENT + (wid == W_AG1) * 128;
      for (uint32_t e = 0;; e++) {
        mbar_wait_long(qb + (e & 7) * 8, (e >> 3) & 1);
        const uint4 en = lds128(qe + (e & 7) * 16);
        const int op = en.x & 15, sg = (en.x >> 4) & 15, rel = (en.x >> 8) & 15, nb = (en.x >> 12) & 15;
        if (op == OP_END) break;
        const uint32_t src = sb + sg * STG;
        if (op == OP_OB) tma_store3(&tm.obS, src, 0, en.y, en.z);
        else if (op == OP_Q) asm volatile("cp.async.bulk.global.shared::cta.bulk_group [%0], [%1], 24576;" ::"l"(g_Ql + en.y * 1536), "r"(src) : "memory");
        else {
          const CUtensorMap* pm = op == OP_O ? &tm.oS : (op == OP_QKV ? &tm.qkvS : &tm.out);
#pragma unroll 1
          for (int i = 0; i < nb; i++) {
            if (op == OP_ADD) tma_red3(pm, src + i * 8192, 0, en.y, en.z + i); else tma_store3(pm, src + i * 8192, 0, en.y, en.z + i);
          }
        }
        bulk_commit();
        bulk_wait_read0();
        asm volatile("mbarrier.arrive.shared::cta.b64 _, [%0], %1;" ::"r"(sb + A_EMPTY + sg * 8), "r"(rel) : "memory");
        if (en.w) {
          bulk_wait0();
          asm volatile("red.relaxed.gpu.global.add.u32 [%0], %1;" ::"l"(&g_cnt[(en.w - 1) * 8]), "r"(1) : "memory");
        }
      }
      bulk_wait0();
      if (wid == W_AG1) GTA(7);
    }
  } else {
    asm volatile("setmaxnreg.inc.sync.aligned.u32 232;");
    const int g = wid >> 2, w = wid & 3;
    uint32_t qn = 0;
    auto wait_full = [&]() { mbar_wait_u(sb + A_FULL + st * 8, ph); };
    auto release = [&](uint32_t s_) { if (lane == 0) mbar_arrive(sb + A_EMPTY + s_ * 8); };
    auto take_pair = [&]() -> uint32_t {
      wait_full();
      const uint32_t s0 = st; advance();
      wait_full();
      const uint32_t s1 = st; advance();
      release(g ? s0 : s1);
      return g ? s1 : s0;
    };
    auto push = [&](uint32_t w0, uint32_t w1, uint32_t w2, uint32_t w3) {
      fence_async_smem();
      if (w == 0 && lane == 0) sts128(sb + A_QENT + g * 128 + (qn & 7) * 16, w0, w1, w2, w3);
      __syncwarp();
      if (lane == 0) mbar_arrive(sb + A_QBAR + g * 64 + (qn & 7) * 8);
      qn++;
    };
    const uint32_t stm = (16 * w + (lane & 7) + (lane & 8)) * 128, stx = lane & 7, sth = lane >> 4;
    auto stage_bf16 = [&](uint32_t dst, const float* d, int nks = 12) {
#pragma unroll
      for (int ks = 0; ks < nks; ks++)
        stsm4(dst + (ks >> 2) * 8192 + stm + (((2 * (ks & 3) + sth) ^ stx) << 4), pack2(d[8 * ks], d[8 * ks + 1]), pack2(d[8 * ks + 2], d[8 * ks + 3]),
              pack2(d[8 * ks + 4], d[8 * ks + 5]), pack2(d[8 * ks + 6], d[8 * ks + 7]));
    };
#pragma unroll 1
    while (true) {
      wait_full();
      const uint32_t item = lds32(sb + A_ITEM + st * 4);
      const int ty = item & 7, t = (item >> 3) & 31, a = (item >> 8) & 255;
      if (ty == IT_QKV || ty == IT_XATT || ty == IT_Q) {
        float acc[192] = {};
        uint32_t prev = 0;
#define XG(i) do {} while (0)
#pragma unroll 1
        for (int k = 0; k < 20; k++) {
          if (k) wait_full();
          PTR((item & 255) == PT && tid == 32, 3, k);
          const uint32_t s_ = sb + st * STG;
          const Desc da = mk_desc(s_, 16, 512, 2), db = mk_desc(s_ + 8192 + g * 12288, 4096, 1024, 1);
          wg_fence();
          wgmma_ss192t(acc, da, db, k);
          wgmma_ss192t(acc + 96, da + 256, db, k);
          wgmma_ss192t(acc, da + 2, db + 128, 1);
          wgmma_ss192t(acc + 96, da + 258, db + 128, 1);
          wg_commit();
          if (k) { wg_wait1(); release(prev); }
          prev = st; advance();
        }
        uint32_t kst[2];
        if (ty == IT_XATT) { kst[0] = take_pair(); kst[1] = take_pair(); }
        wg_wait0();
        fence_regs<192>(acc);
        release(prev);
        XG(0);
        if (ty == IT_QKV) {
#pragma unroll
          for (int q = 0; q < 2; q++) {
            const uint32_t m = take_pair();
            stage_bf16(sb + m * STG, acc + q * 96);
            push(OP_QKV | (m << 4) | (4 << 8) | (3 << 12), t * 128 + q * 64, a * 6 + g * 3, q ? C_QKV + t + 1 : 0);
          }
        } else if (ty == IT_Q) {
#pragma unroll
          for (int q = 0; q < 2; q++) {
            const uint32_t m = take_pair();
#pragma unroll
            for (int ks = 0; ks < 12; ks++) {
              const float* d = acc + q * 96 + ks * 8;
              sts128(sb + m * STG + (w * 12 + ks) * 512 + lane * 16, pack2(d[0], d[1]), pack2(d[2], d[3]), pack2(d[4], d[5]), pack2(d[6], d[7]));
            }
            push(OP_Q | (m << 4) | (4 << 8), (2 * a + g) * 2 + q, 0, q ? C_O + 240 + a + 1 : 0);
          }
        } else {
          uint32_t qf[24][4];
          float sc[2][40], gt[4];
#pragma unroll
          for (int q = 0; q < 2; q++) {
#pragma unroll
            for (int ks = 23; ks >= 0; ks--)
#pragma unroll
              for (int j = 0; j < 4; j++)
                if ((ks >= 12 && ks < 12 + CVTS) == (q == 1))
                  asm volatile("cvt.rn.bf16x2.f32 %0, %1, %2;" : "=r"(qf[ks][j]) : "f"(acc[8 * ks + 2 * j + 1]), "f"(acc[8 * ks + 2 * j]));
            if (q == 0) XG(1);
            if (q == 0 && XPP && g == 1) bar_sync(6, 256);
            if (q == 1) {
              const float* gp = g_gate + t * 128 + 16 * w + (lane >> 2);
              gt[0] = ldg_cg(gp); gt[1] = ldg_cg(gp + 8); gt[2] = ldg_cg(gp + 64); gt[3] = ldg_cg(gp + 72);
            }
#pragma unroll
            for (int i = 0; i < 40; i++) sc[q][i] = 0.f;
            const Desc db = mk_desc(sb + kst[q] * STG, 16, 1024, 1);
            wg_fence();
#pragma unroll
            for (int ks = 0; ks < 12; ks++) {
              if (XPP && g == 0 && q * 12 + ks == XPP) bar_arrive(6, 256);
              wgmma_rs80(sc[q], qf[q * 12 + ks], db + (((ks >> 2) * 10240 + (ks & 3) * 32) >> 4), ks);
            }
            wg_commit();
          }
          uint32_t pf[2][5][4];
          const AttMask am(tid, sb);
          wg_wait1();
          fence_regs<40>(sc[0]);
          XG(2);
          release(kst[0]);
          sched_fence(sb);
          att_softmax(am, sc[0], pf[0], gt[0], gt[1]);
          XG(3);
          float o[96] = {};
          auto pv = [&](int q, uint32_t m) {
            const Desc db = mk_desc(sb + m * STG, 10240, 1024, 1);
            wg_fence();
#pragma unroll
            for (int ks = 0; ks < 5; ks++) wgmma_rs192t(o, pf[q][ks], db + ks * 128, ks);
            wg_commit();
          };
          PTR((item & 255) == PT && tid == 32, 3, 24);
          const uint32_t m0 = take_pair();
          PTR((item & 255) == PT && tid == 32, 3, 25);
          pv(0, m0);
          wg_wait1();
          fence_regs<40>(sc[1]);
          release(kst[1]);
          att_softmax(am, sc[1], pf[1], gt[2], gt[3]);
          PTR((item & 255) == PT && tid == 32, 3, 26);
          const uint32_t m1 = take_pair();
          PTR((item & 255) == PT && tid == 32, 3, 27);
          wg_wait0();
          fence_regs<96>(o);
          XG(4);
#pragma unroll
          for (int i = 0; i < 48; i++) asm volatile("cvt.rn.bf16x2.f32 %0, %1, %2;" : "=r"(qf[i >> 2][i & 3]) : "f"(o[2 * i + 1]), "f"(o[2 * i]));
          pv(1, m1);
          bar_sync(1 + g, 128);
#pragma unroll
          for (int ks = 0; ks < 12; ks++)
            stsm4(sb + m0 * STG + (ks >> 2) * 8192 + stm + (((2 * (ks & 3) + sth) ^ stx) << 4), qf[ks][0], qf[ks][1], qf[ks][2], qf[ks][3]);
          push(OP_O | (m0 << 4) | (4 << 8) | (3 << 12), t * 128, a * 6 + g * 3, 0);
          XG(5);
          wg_wait0();
          fence_regs<96>(o);
          XG(6);
          bar_sync(1 + g, 128);
          stage_bf16(sb + m1 * STG, o);
          push(OP_O | (m1 << 4) | (4 << 8) | (3 << 12), t * 128 + 64, a * 6 + g * 3, C_O + t * 16 + a + 1);
          XG(7);
        }
      } else if (ty == IT_OUT || ty == IT_INIT) {
        float acc[160] = {};
        const int hb = (item >> 16) & 255, nh = (item >> 24) - hb, nk = ty == IT_OUT ? nh * 6 : 20, jh = a & 1;
        const uint32_t ln = pin(lane), ao = (g * 64 + 16 * w + (ln & 15)) * 64 + (((ln >> 4) ^ ((ln >> 1) & 3)) << 4);
        if (PP && g == 1) bar_arrive(4, 256);
#pragma unroll 1
        for (int k = 0; k < nk; k += 2) {
          uint32_t af[4][4], sg[2];
#pragma unroll
          for (int e = 0; e < 2; e++) {
            if (k + e) wait_full();
            sg[e] = st;
            ldsm4(af[2 * e], sb + st * STG + ao);
            ldsm4(af[2 * e + 1], sb + st * STG + (ao ^ 32));
            advance();
          }
          if (PP) bar_sync(4 + g, 256);
          wg_fence();
#pragma unroll
          for (int e = 0; e < 4; e++) {
            const Desc db = mk_desc(sb + sg[e >> 1] * STG + 8192 + (e & 1) * 2048, 4096, 1024, 1);
            if (PP == 2 && e == 3 && (g == 0 || k + 2 < nk)) bar_arrive(5 - g, 256);
            wgmma_rs192t(acc, af[e], db, 1);
            if (PP == 3 && e == 3 && (g == 0 || k + 2 < nk)) bar_arrive(5 - g, 256);
            wgmma_rs128t(acc + 96, af[e], db + 768, 1);
          }
          wg_commit();
          if (PP == 1 && (g == 0 || k + 2 < nk)) bar_arrive(5 - g, 256);
          wg_wait0();
          release(sg[0]); release(sg[1]);
        }
        fence_regs<160>(acc);
        const uint32_t row = t * 128 + g * 64;
#pragma unroll
        for (int q = 0; q < 2; q++) {
          const uint32_t m = take_pair();
          stage_bf16(sb + m * STG, acc + q * 96, q ? 8 : 12);
          push((ty == IT_OUT || t == 15 ? OP_ADD : OP_SET) | (m << 4) | (4 << 8) | ((3 - q) << 12), row, jh * 5 + q * 3, q && ty == IT_INIT ? C_ACC + t + 1 : 0);
        }
      } else if (ty == IT_BATT) {
        const int ln = pin(lane);
        const int q4 = ln & 3, r8 = ln >> 2;
        const bool lo = q4 < 2, m0 = 2 * q4 > r8, m1 = 2 * q4 + 1 > r8;
        const uint32_t mk = (m0 ? 0xffffu : 0u) | (m1 ? 0xffff0000u : 0u);
        uint32_t aq[5], ak[5];
#pragma unroll
        for (int i = 0; i < 5; i++) {
          const int c = 5 * wid + i;
          aq[i] = (c >> 3) * 4096 + ln * 128 + (((c ^ ln) & 7) << 4);
          ak[i] = aq[i] + (c >> 3) * 1024;
        }
        const int c4 = 5 * wid + (ln >> 3);
        const uint32_t ak4 = (c4 >> 3) * 5120 + (32 + (ln & 7)) * 128 + (((c4 ^ ln) & 7) << 4), ak5 = ak[4] + (32 + (ln & 7) - ln) * 128;
#pragma unroll 1
        for (int j = 0; j < 4; j++) {
          float gt[4];
#pragma unroll
          for (int i = 0; i < 4; i++) gt[i] = ldg_cg(g_gate + S_TOK + t * 64 + (j & 1) + 2 * r8 + i * 16);
          if (j) wait_full();
          PTR((item & 255) == PT && tid == 32, 3, j * 3);
          const uint32_t sq = st; advance();
          uint32_t qf[5][4], kf[7][4], vf[7][4], pa[4], pb[4];
          float sc[4][3][4] = {}, o[4][3][4] = {}, l[4][4], xa[4], xb[4];
#pragma unroll
          for (int i = 0; i < 5; i++) ldsm4(qf[i], sb + sq * STG + aq[i]);
          wait_full();
          PTR((item & 255) == PT && tid == 32, 3, j * 3 + 1);
          const uint32_t sk = st; advance();
#pragma unroll
          for (int i = 0; i < 7; i++) ldsm4(kf[i], sb + sk * STG + (i < 5 ? ak[i] : (i == 5 ? ak4 : ak5)));
          auto frag = [](uint32_t (*f)[4], int c, int n) { return n < 4 ? f[c][n] : (c < 4 ? f[5][c] : f[6][0]); };
#pragma unroll
          for (int u = 0; u < 4; u++) {
            const int c = (u >> 1) * 3, b = u & 1;
            const uint32_t x[4] = {qf[c][2 * b], qf[c][2 * b + 1], qf[c + 1][2 * b], qf[c + 1][2 * b + 1]};
#pragma unroll
            for (int n = 0; n < 3; n++) mma16816(sc[u][n], x, frag(kf, c, 2 * b + n), frag(kf, c + 1, 2 * b + n));
          }
#pragma unroll
          for (int u = 0; u < 4; u++) {
            const int b = u & 1;
            const uint32_t x0 = lo == (u < 2) ? qf[2][2 * b] : 0u, x1 = lo == (u < 2) ? qf[2][2 * b + 1] : 0u;
#pragma unroll
            for (int n = 0; n < 3; n++) mma1688(sc[u][n], x0, x1, frag(kf, 2, 2 * b + n));
          }
          wait_full();
          PTR((item & 255) == PT && tid == 32, 3, j * 3 + 2);
          const uint32_t sv = st; advance();
#pragma unroll
          for (int i = 0; i < 7; i++) ldsm4t(vf[i], sb + sv * STG + (i < 5 ? ak[i] : (i == 5 ? ak4 : ak5)));
          if (t == 0) sc[0][0][0] = sc[0][0][1] = sc[2][0][0] = sc[2][0][1] = -INFINITY;
          constexpr float SCL = 0.22360679774997896f * 1.4426950408889634f;
#pragma unroll
          for (int u = 0; u < 4; u++) {
            l[u][0] = m0 ? sc[u][0][0] : sc[u][1][0]; l[u][1] = m1 ? sc[u][0][1] : sc[u][1][1];
            l[u][2] = m0 ? sc[u][1][2] : sc[u][2][2]; l[u][3] = m1 ? sc[u][1][3] : sc[u][2][3];
            xa[u] = fmaxf(l[u][0], l[u][1]); xb[u] = fmaxf(l[u][2], l[u][3]);
          }
          release(sk);
#pragma unroll
          for (int d = 1; d < 4; d *= 2)
#pragma unroll
            for (int u = 0; u < 4; u++) { xa[u] = fmaxf(xa[u], __shfl_xor_sync(~0u, xa[u], d)); xb[u] = fmaxf(xb[u], __shfl_xor_sync(~0u, xb[u], d)); }
#pragma unroll
          for (int u = 0; u < 4; u++) {
            xa[u] *= SCL; xb[u] *= SCL;
#pragma unroll
            for (int i = 0; i < 4; i++) l[u][i] = ex2(fmaf(l[u][i], SCL, -(i < 2 ? xa[u] : xb[u])));
            xa[u] = l[u][0] + l[u][1]; xb[u] = l[u][2] + l[u][3];
          }
#pragma unroll
          for (int d = 1; d < 4; d *= 2)
#pragma unroll
            for (int u = 0; u < 4; u++) { xa[u] += __shfl_xor_sync(~0u, xa[u], d); xb[u] += __shfl_xor_sync(~0u, xb[u], d); }
#pragma unroll
          for (int u = 0; u < 4; u++) {
            const int c = (u >> 1) * 3, b = u & 1;
            xa[u] = gt[2 * b] * rcp(xa[u]); xb[u] = gt[2 * b + 1] * rcp(xb[u]);
            pa[u] = pack2(l[u][0] * xa[u], l[u][1] * xa[u]); pb[u] = pack2(l[u][2] * xb[u], l[u][3] * xb[u]);
            const uint32_t pf[4] = {pa[u] & mk, 0u, pa[u] & ~mk, pb[u] & mk};
#pragma unroll
            for (int n = 0; n < 3; n++) mma16816(o[u][n], pf, vf[n < 2 ? c + n : 2][2 * b], vf[n < 2 ? c + n : 2][2 * b + 1]);
          }
#pragma unroll
          for (int u = 0; u < 4; u++)
#pragma unroll
            for (int n = 0; n < 3; n++) mma1688(o[u][n], 0u, pb[u] & ~mk, frag(vf, n < 2 ? (u >> 1) * 3 + n : 2, 2 * (u & 1) + 2));
          release(sv);
#pragma unroll
          for (int i = 0; i < 5; i++) {
            float y[8];
#pragma unroll
            for (int e = 0; e < 8; e++) y[e] = i == 2 ? (lo ? o[e >> 2][2][e & 3] : o[2 + (e >> 2)][2][e & 3]) : o[(i > 2) * 2 + (e >> 2)][i % 3][e & 3];
            stsm4(sb + sq * STG + aq[i], pack2(y[0], y[1]), pack2(y[2], y[3]), pack2(y[4], y[5]), pack2(y[6], y[7]));
          }
          PTR((item & 255) == PT && tid == 32, 3, 12 + j * 2);
          fence_async_smem();
          bar_sync(3, 256);
          PTR((item & 255) == PT && tid == 32, 3, 13 + j * 2);
          if (g == (j & 1)) push(OP_OB | (sq << 4) | (8 << 8), t * 32, (j & 1) * 10 + (j >> 1) * 5, C_OB + (t >> 1) + 1);
        }
      } else {
        release(st);
        push(OP_END, 0, 0, 0);
        break;
      }
    }
  }
}

typedef CUresult (*EncFn)(CUtensorMap*, CUtensorMapDataType, cuuint32_t, void*, const cuuint64_t*, const cuuint64_t*, const cuuint32_t*,
                          const cuuint32_t*, CUtensorMapInterleave, CUtensorMapSwizzle, CUtensorMapL2promotion, CUtensorMapFloatOOBfill);

void make_map(EncFn enc, CUtensorMap* tm, const void* base, int rank, const cuuint64_t* dims, const cuuint64_t* strides, const cuuint32_t* box,
              CUtensorMapSwizzle sw = CU_TENSOR_MAP_SWIZZLE_128B, CUtensorMapDataType dt = CU_TENSOR_MAP_DATA_TYPE_BFLOAT16) {
  const cuuint32_t es[5] = {1, 1, 1, 1, 1};
  enc(tm, dt, rank, const_cast<void*>(base), dims, strides, box, es, CU_TENSOR_MAP_INTERLEAVE_NONE, sw, CU_TENSOR_MAP_L2_PROMOTION_L2_128B,
      CU_TENSOR_MAP_FLOAT_OOB_FILL_NONE);
}
void map_blk(EncFn enc, CUtensorMap* tm, const void* base, int rows, int cols, int brows, int bblk) {
  const cuuint64_t d[3] = {64, (cuuint64_t)rows, (cuuint64_t)cols / 64}, st[2] = {(cuuint64_t)cols * 2, 128};
  const cuuint32_t b[3] = {64, (cuuint32_t)brows, (cuuint32_t)bblk};
  make_map(enc, tm, base, 3, d, st, b);
}
void map_2d(EncFn enc, CUtensorMap* tm, const void* base, int rows, int cols, int brows, int bcols, CUtensorMapSwizzle sw) {
  const cuuint64_t d[2] = {(cuuint64_t)cols, (cuuint64_t)rows}, st[1] = {(cuuint64_t)cols * 2};
  const cuuint32_t b[2] = {(cuuint32_t)bcols, (cuuint32_t)brows};
  make_map(enc, tm, base, 2, d, st, b, sw);
}

}

extern "C" void kernel_launch(void* const* d_in, const int* in_sizes, int n_in, void* d_out, int out_size) {
  const bf16* x = (const bf16*)d_in[0];
  const bf16* mem0 = (const bf16*)d_in[1];
  const bf16* Wq = (const bf16*)d_in[2];
  const bf16* Wk = (const bf16*)d_in[3];
  const bf16* Wv = (const bf16*)d_in[4];
  const bf16* Wo = (const bf16*)d_in[5];
  const bf16* wqkv = (const bf16*)d_in[8];
  const bf16* wob = (const bf16*)d_in[9];
  const bf16* gate_w = (const bf16*)d_in[10];
  static EncFn enc = nullptr;
  static int aux_grid = 36;
  static void *pR = nullptr, *pK = nullptr, *pV = nullptr, *pO = nullptr, *pQ = nullptr, *pB = nullptr;
  if (!enc) {
    void* fn = nullptr;
    cudaDriverEntryPointQueryResult qr;
    cudaGetDriverEntryPoint("cuTensorMapEncodeTiled", &fn, cudaEnableDefault, &qr);
    enc = (EncFn)fn;
    cudaGetSymbolAddress(&pR, g_red);
    cudaGetSymbolAddress(&pK, g_K);
    cudaGetSymbolAddress(&pV, g_V);
    cudaGetSymbolAddress(&pO, g_O);
    cudaGetSymbolAddress(&pQ, g_qkv);
    cudaGetSymbolAddress(&pB, g_Ob);
    cudaFuncSetAttribute(rec_kernel, cudaFuncAttributeMaxDynamicSharedMemorySize, R_SMEM_ALLOC);
    cudaFuncSetAttribute(aux_kernel, cudaFuncAttributeMaxDynamicSharedMemorySize, A_SMEM);
    int dev = 0, sms = 132;
    cudaGetDevice(&dev);
    cudaDeviceGetAttribute(&sms, cudaDevAttrMultiProcessorCount, dev);
    aux_grid = sms - 96 < 8 ? 8 : (sms - 96 > 96 ? 96 : sms - 96);
  }
  CUtensorMap tmX, tmK, tmV, tmWq, tmWq2, tmWk, tmWv, tmWo, tmOut;
  map_2d(enc, &tmOut, d_out, S_TOK, DM, 64, 32, CU_TENSOR_MAP_SWIZZLE_64B);
  map_2d(enc, &tmWq, Wq, DM, HD, 144, 64, CU_TENSOR_MAP_SWIZZLE_128B);
  map_2d(enc, &tmWq2, Wq, DM, HD, 32, 64, CU_TENSOR_MAP_SWIZZLE_128B);
  map_2d(enc, &tmWk, Wk, DM, HD, 128, 64, CU_TENSOR_MAP_SWIZZLE_128B);
  map_2d(enc, &tmWv, Wv, DM, HD, 128, 64, CU_TENSOR_MAP_SWIZZLE_128B);
  {
    const cuuint64_t d[3] = {32, HD, 20}, st[2] = {DM * 2, 64};
    const cuuint32_t b[3] = {32, 64, 7};
    make_map(enc, &tmWo, Wo, 3, d, st, b, CU_TENSOR_MAP_SWIZZLE_64B);
  }
  map_blk(enc, &tmX, x, S_TOK, DM, 32, 10);
  map_2d(enc, &tmK, pK, NSEG * LK, HD, LK, 64, CU_TENSOR_MAP_SWIZZLE_128B);
  map_2d(enc, &tmV, pV, NSEG * LK, HD, LK, 64, CU_TENSOR_MAP_SWIZZLE_128B);
  AuxMaps am;
  map_2d(enc, &am.xA, x, S_TOK, DM, 128, 32, CU_TENSOR_MAP_SWIZZLE_64B);
  map_blk(enc, &am.wq, Wq, DM, HD, 32, 6);
  map_blk(enc, &am.wqkv, wqkv, DM, 3 * DM, 32, 6);
  map_blk(enc, &am.wo, Wo, HD, DM, 32, 5);
  map_blk(enc, &am.wob, wob, DM, DM, 32, 5);
  map_blk(enc, &am.k, pK, NSEG * LK, HD, 80, 3);
  map_blk(enc, &am.v, pV, NSEG * LK, HD, 80, 3);
  map_2d(enc, &am.oA, pO, S_TOK, HD, 128, 32, CU_TENSOR_MAP_SWIZZLE_64B);
  map_blk(enc, &am.oS, pO, S_TOK, HD, 64, 1);
  map_2d(enc, &am.obA, pB, S_TOK, DM, 128, 32, CU_TENSOR_MAP_SWIZZLE_64B);
  map_blk(enc, &am.obS, pB, S_TOK / 2, 2 * DM, 32, 5);
  map_blk(enc, &am.qkvS, pQ, S_TOK, 3 * DM, 64, 1);
  map_blk(enc, &am.qkvQ, pQ, S_TOK / 2, 6 * DM, 32, 5);
  map_blk(enc, &am.qkvK, pQ, S_TOK / 2, 6 * DM, 40, 5);
  map_blk(enc, &am.out, d_out, S_TOK, DM, 64, 1);
  rec_kernel<<<96, 256, R_SMEM_ALLOC, cudaStreamPerThread>>>(tmX, tmK, tmV, tmWq, tmWq2, tmWk, tmWv, tmWo, tmOut, mem0, Wq, Wk, Wv, Wo, x, gate_w, (bf16*)d_out,
                                                               (unsigned char*)(((uintptr_t)pR + 0x1fffff) & ~(uintptr_t)0x1fffff));
  cudaLaunchConfig_t cfg = {};
  cfg.gridDim = dim3(aux_grid); cfg.blockDim = dim3(384); cfg.dynamicSmemBytes = A_SMEM; cfg.stream = cudaStreamPerThread;
  cudaLaunchAttribute at[1];
  at[0].id = cudaLaunchAttributeProgrammaticStreamSerialization;
  at[0].val.programmaticStreamSerializationAllowed = 1;
  cfg.attrs = at;
  cfg.numAttrs = 1;
  cudaLaunchKernelEx(&cfg, aux_kernel, am);
}
```

```cpp
#include <cuda_runtime.h>
#include <cuda_bf16.h>
#include <cuda.h>
#include <stdint.h>
#include <type_traits>

typedef __nv_bfloat16 bf16;

namespace {

constexpr int S_TOK = 2048, DM = 640, NH = 32, DH = 192, HD = NH * DH, SEG = 32, NSEG = 64, MT = 8, LK = 40;
constexpr int SPIN_MAX = 1 << 20, NGATE = 96;

__device__ __align__(4096) unsigned char g_red[(2 << 20) + (640 << 10)];
__host__ __device__ constexpr uint32_t rb_q(int q) { return (q < 5 ? q : q - 5) * 131072 + (uint32_t)((0x3122120330ull >> 4 * q) & 15) * 2048; }
__host__ __device__ constexpr uint32_t rb_j(int j) { return (j & 1) * 256 + (j & 2) * 512 + (j & 12) * 2048; }
__host__ __device__ constexpr uint32_t rb_b(int b) { return (b & 1) * 128 + (b & 2) * 256; }
__device__ unsigned long long g_rec[96];
__device__ uint32_t g_epoch;
__device__ uint32_t g_err;
__device__ __align__(16) uint32_t g_segcnt[NSEG];
__device__ __align__(1024) bf16 g_K[NSEG * LK * HD];
__device__ __align__(1024) bf16 g_V[NSEG * LK * HD];
__device__ __align__(1024) bf16 g_O[S_TOK * HD];
__device__ __align__(1024) uint4 g_Ql[NH * 2 * 4 * 12 * 32];
__device__ __align__(1024) bf16 g_qkv[S_TOK * 3 * DM];
__device__ __align__(1024) bf16 g_Ob[S_TOK * DM];
__device__ float g_gate[2 * S_TOK];
__device__ uint32_t g_cnt[512 * 8];
constexpr int C_GATE = 0, C_QKV = 16, C_OB = 32, C_ACC = 48, C_O = 80;
__device__ __align__(128) uint32_t g_queue[3 * 32];
__device__ uint32_t g_prog;
#define GTR(i) do {} while (0)
#define GTA(i) do {} while (0)
#define PTR(c, r, k) do {} while (0)

__device__ __forceinline__ uint32_t smem_u32(const void* p) { return (uint32_t)__cvta_generic_to_shared(p); }
__device__ __forceinline__ uint32_t clk32() { uint32_t t; asm volatile("mov.u32 %0, %%clock;" : "=r"(t)::"memory"); return t; }
__device__ __forceinline__ uint32_t mapa(uint32_t a, uint32_t r) { uint32_t o; asm("mapa.shared::cluster.u32 %0, %1, %2;" : "=r"(o) : "r"(a), "r"(r)); return o; }
__device__ __forceinline__ void mbar_init(uint32_t b, uint32_t c) { asm volatile("mbarrier.init.shared::cta.b64 [%0], %1;" ::"r"(b), "r"(c) : "memory"); }
__device__ __forceinline__ void mbar_expect(uint32_t b, uint32_t bytes) { asm volatile("mbarrier.arrive.expect_tx.shared::cta.b64 _, [%0], %1;" ::"r"(b), "r"(bytes) : "memory"); }
__device__ __forceinline__ void mbar_arrive(uint32_t b) { asm volatile("mbarrier.arrive.shared::cta.b64 _, [%0];" ::"r"(b) : "memory"); }
__device__ __forceinline__ bool mbar_try(uint32_t b, uint32_t par) {
  uint32_t p;
  asm volatile("{.reg .pred p; mbarrier.try_wait.parity.shared::cta.b64 p, [%1], %2; selp.u32 %0,1,0,p;}" : "=r"(p) : "r"(b), "r"(par) : "memory");
  return p;
}
__device__ __forceinline__ bool mbar_test(uint32_t b, uint32_t par) {
  uint32_t p;
  asm volatile("{.reg .pred p; mbarrier.test_wait.parity.shared::cta.b64 p, [%1], %2; selp.u32 %0,1,0,p;}" : "=r"(p) : "r"(b), "r"(par) : "memory");
  return p;
}
__device__ __forceinline__ bool mbar_try_cl(uint32_t b, uint32_t par) {
  uint32_t p;
  asm volatile("{.reg .pred p; mbarrier.try_wait.parity.acquire.cluster.shared::cta.b64 p, [%1], %2; selp.u32 %0,1,0,p;}" : "=r"(p) : "r"(b), "r"(par) : "memory");
  return p;
}
__device__ __forceinline__ void mbar_wait(uint32_t b, uint32_t par) {
  int n = 0;
#pragma unroll 1
  while (!mbar_try(b, par) && ++n <= SPIN_MAX) {}
}
__device__ __forceinline__ void bar_sync(int id, int n) { asm volatile("bar.sync %0, %1;" ::"r"(id), "r"(n) : "memory"); }
__device__ __forceinline__ void bar_arrive(int id, int n) { asm volatile("bar.arrive %0, %1;" ::"r"(id), "r"(n) : "memory"); }
__device__ __forceinline__ void fence_async_smem() { asm volatile("fence.proxy.async.shared::cta;" ::: "memory"); }
__device__ __forceinline__ void ldsm4(uint32_t* r, uint32_t a) {
  asm volatile("ldmatrix.sync.aligned.m8n8.x4.shared.b16 {%0,%1,%2,%3}, [%4];" : "=r"(r[0]), "=r"(r[1]), "=r"(r[2]), "=r"(r[3]) : "r"(a) : "memory");
}
__device__ __forceinline__ void ldsm4t(uint32_t* r, uint32_t a) {
  asm volatile("ldmatrix.sync.aligned.m8n8.x4.trans.shared.b16 {%0,%1,%2,%3}, [%4];" : "=r"(r[0]), "=r"(r[1]), "=r"(r[2]), "=r"(r[3]) : "r"(a) : "memory");
}
__device__ __forceinline__ void stsm4t(uint32_t a, uint32_t r0, uint32_t r1, uint32_t r2, uint32_t r3) {
  asm volatile("stmatrix.sync.aligned.m8n8.x4.trans.shared.b16 [%0], {%1,%2,%3,%4};" ::"r"(a), "r"(r0), "r"(r1), "r"(r2), "r"(r3) : "memory");
}
__device__ __forceinline__ void stsm2t(uint32_t a, uint32_t r0, uint32_t r1) {
  asm volatile("stmatrix.sync.aligned.m8n8.x2.trans.shared.b16 [%0], {%1,%2};" ::"r"(a), "r"(r0), "r"(r1) : "memory");
}
__device__ __forceinline__ uint32_t movmat(uint32_t a) { uint32_t d; asm volatile("movmatrix.sync.aligned.m8n8.trans.b16 %0, %1;" : "=r"(d) : "r"(a)); return d; }
__device__ __forceinline__ void mma16816(float* d, const uint32_t* a, uint32_t b0, uint32_t b1) {
  asm volatile("mma.sync.aligned.m16n8k16.row.col.f32.bf16.bf16.f32 {%0,%1,%2,%3}, {%4,%5,%6,%7}, {%8,%9}, {%0,%1,%2,%3};"
               : "+f"(d[0]), "+f"(d[1]), "+f"(d[2]), "+f"(d[3]) : "r"(a[0]), "r"(a[1]), "r"(a[2]), "r"(a[3]), "r"(b0), "r"(b1));
}
__device__ __forceinline__ void mma1688(float* d, uint32_t a0, uint32_t a1, uint32_t b0) {
  asm volatile("mma.sync.aligned.m16n8k8.row.col.f32.bf16.bf16.f32 {%0,%1,%2,%3}, {%4,%5}, {%6}, {%0,%1,%2,%3};"
               : "+f"(d[0]), "+f"(d[1]), "+f"(d[2]), "+f"(d[3]) : "r"(a0), "r"(a1), "r"(b0));
}
__device__ __forceinline__ uint32_t pack2(float lo, float hi) { uint32_t r; asm("cvt.rn.bf16x2.f32 %0, %1, %2;" : "=r"(r) : "f"(hi), "f"(lo)); return r; }
__device__ __forceinline__ float bf_lo(uint32_t w) { return __uint_as_float(w << 16); }
__device__ __forceinline__ float bf_hi(uint32_t w) { return __uint_as_float(w & 0xffff0000u); }
__device__ __forceinline__ float ex2(float x) { float y; asm("ex2.approx.ftz.f32 %0, %1;" : "=f"(y) : "f"(x)); return y; }
__device__ __forceinline__ void sts128(uint32_t a, uint32_t x, uint32_t y, uint32_t z, uint32_t w) { asm volatile("st.shared.v4.b32 [%0], {%1,%2,%3,%4};" ::"r"(a), "r"(x), "r"(y), "r"(z), "r"(w) : "memory"); }
__device__ __forceinline__ void sts64f(uint32_t a, float x, float y) { asm volatile("st.shared.v2.f32 [%0], {%1,%2};" ::"r"(a), "f"(x), "f"(y) : "memory"); }
__device__ __forceinline__ void sts32(uint32_t a, uint32_t x) { asm volatile("st.shared.b32 [%0], %1;" ::"r"(a), "r"(x) : "memory"); }
__device__ __forceinline__ void smax32(uint32_t a, uint32_t x) { asm volatile("red.shared.max.u32 [%0], %1;" ::"r"(a), "r"(x) : "memory"); }
__device__ __forceinline__ uint32_t lds32(uint32_t a) { uint32_t v; asm volatile("ld.shared.b32 %0, [%1];" : "=r"(v) : "r"(a) : "memory"); return v; }
__device__ __forceinline__ float4 lds128f(uint32_t a) { float4 v; asm volatile("ld.shared.v4.f32 {%0,%1,%2,%3}, [%4];" : "=f"(v.x), "=f"(v.y), "=f"(v.z), "=f"(v.w) : "r"(a) : "memory"); return v; }
__device__ __forceinline__ uint4 lds128(uint32_t a) { uint4 v; asm volatile("ld.shared.v4.b32 {%0,%1,%2,%3}, [%4];" : "=r"(v.x), "=r"(v.y), "=r"(v.z), "=r"(v.w) : "r"(a) : "memory"); return v; }
__device__ __forceinline__ float2 lds64f(uint32_t a) { float2 v; asm volatile("ld.shared.v2.f32 {%0,%1}, [%2];" : "=f"(v.x), "=f"(v.y) : "r"(a) : "memory"); return v; }
__device__ __forceinline__ void st_async2(uint32_t a, uint32_t x, uint32_t y, uint32_t bar) {
  asm volatile("st.async.weak.shared::cluster.mbarrier::complete_tx::bytes.v2.b32 [%0], {%1,%2}, [%3];" ::"r"(a), "r"(x), "r"(y), "r"(bar) : "memory");
}
__device__ __forceinline__ void st_async4(uint32_t a, uint32_t x, uint32_t y, uint32_t z, uint32_t w, uint32_t bar) {
  asm volatile("st.async.weak.shared::cluster.mbarrier::complete_tx::bytes.v4.b32 [%0], {%1,%2,%3,%4}, [%5];" ::"r"(a), "r"(x), "r"(y), "r"(z), "r"(w), "r"(bar) : "memory");
}
__device__ __forceinline__ void sts64(uint32_t a, uint32_t x, uint32_t y) { asm volatile("st.shared.v2.b32 [%0], {%1,%2};" ::"r"(a), "r"(x), "r"(y) : "memory"); }
__device__ __forceinline__ float rcp(float x) { float y; asm("rcp.approx.ftz.f32 %0, %1;" : "=f"(y) : "f"(x)); return y; }
__device__ __forceinline__ uint32_t pin(uint32_t v) { asm volatile("" : "+r"(v)); return v; }
template <int ID> __device__ __forceinline__ void sched_fence_(uint32_t a) {
  asm volatile("{.reg .pred p;\nsetp.eq.u32 p, %0, %1;\nSF: @p pmevent 0;\n@p bra.uni SF;}" ::"r"(a), "n"(0x40000000 + ID) : "memory");
}
#define sched_fence(a) sched_fence_<__LINE__>(a)
__device__ __forceinline__ bool elect() {
  uint32_t p;
  asm volatile("{.reg .pred p; elect.sync _|p, 0xffffffff; selp.u32 %0,1,0,p;}" : "=r"(p));
  return p;
}
__device__ __forceinline__ uint32_t opaque(uint32_t v) { return __shfl_sync(~0u, v, threadIdx.x & 31); }
__device__ __forceinline__ uint4 ldg_rlx128(const void* p) {
  uint4 v; asm volatile("ld.relaxed.gpu.global.v4.b32 {%0,%1,%2,%3}, [%4];" : "=r"(v.x), "=r"(v.y), "=r"(v.z), "=r"(v.w) : "l"(p) : "memory"); return v;
}
__device__ __forceinline__ uint2 ldg_rlx64(const void* p) {
  uint2 v; asm volatile("{.reg .b64 t; ld.relaxed.gpu.global.b64 t, [%2]; mov.b64 {%0,%1}, t;}" : "=r"(v.x), "=r"(v.y) : "l"(p) : "memory"); return v;
}
__device__ __forceinline__ uint32_t hmaxabs2(uint32_t a, uint32_t b) { uint32_t r; asm("max.xorsign.abs.bf16x2 %0, %1, %2;" : "=r"(r) : "r"(a), "r"(b)); return r; }
__device__ __forceinline__ uint32_t ldg_rlx32(const void* p) {
  uint32_t v; asm volatile("ld.relaxed.gpu.global.b32 %0, [%1];" : "=r"(v) : "l"(p) : "memory"); return v;
}
__device__ __forceinline__ float ldg_cg(const float* p) { float v; asm volatile("ld.global.cg.f32 %0, [%1];" : "=f"(v) : "l"(p) : "memory"); return v; }
__device__ __forceinline__ void spin_until(uint32_t t0, int d) {
#pragma unroll 1
  while ((int)(clk32() - t0) < d) {}
}
__device__ __forceinline__ void stg_rlx64(void* p, uint32_t a, uint32_t b) {
  asm volatile("{.reg .b64 t; mov.b64 t, {%1,%2}; st.relaxed.gpu.global.b64 [%0], t;}" ::"l"(p), "r"(a), "r"(b) : "memory");
}
__device__ __forceinline__ void prefetch_l2(const void* p) { asm volatile("prefetch.global.L2 [%0];" ::"l"(p)); }
__device__ __forceinline__ void tma_load3(uint32_t dst, const CUtensorMap* tm, int c0, int c1, int c2, uint32_t bar) {
  asm volatile("cp.async.bulk.tensor.3d.shared::cluster.global.mbarrier::complete_tx::bytes [%0], [%1, {%3,%4,%5}], [%2];"
               ::"r"(dst), "l"(tm), "r"(bar), "r"(c0), "r"(c1), "r"(c2) : "memory");
}
__device__ __forceinline__ void tma_load2(uint32_t dst, const CUtensorMap* tm, int c0, int c1, uint32_t bar) {
  asm volatile("cp.async.bulk.tensor.2d.shared::cluster.global.mbarrier::complete_tx::bytes [%0], [%1, {%3,%4}], [%2];"
               ::"r"(dst), "l"(tm), "r"(bar), "r"(c0), "r"(c1) : "memory");
}
__device__ __forceinline__ void bulk_s2s(uint32_t dst, uint32_t src, uint32_t bytes, uint32_t bar) {
  asm volatile("cp.async.bulk.shared::cluster.shared::cta.mbarrier::complete_tx::bytes [%0], [%1], %2, [%3];" ::"r"(dst), "r"(src), "r"(bytes), "r"(bar) : "memory");
}
__device__ __forceinline__ void prefetch_map(const CUtensorMap* tm) { asm volatile("prefetch.tensormap [%0];" ::"l"(tm) : "memory"); }
__device__ __forceinline__ void tma_store2(const CUtensorMap* tm, uint32_t src, int c0, int c1) {
  asm volatile("cp.async.bulk.tensor.2d.global.shared::cta.bulk_group [%0, {%2,%3}], [%1];" ::"l"(tm), "r"(src), "r"(c0), "r"(c1) : "memory");
}
__device__ __forceinline__ void bulk_commit() { asm volatile("cp.async.bulk.commit_group;" ::: "memory"); }
__device__ __forceinline__ void bulk_wait0() { asm volatile("cp.async.bulk.wait_group 0;" ::: "memory"); }
__device__ __forceinline__ void bulk_wait_read0() { asm volatile("cp.async.bulk.wait_group.read 0;" ::: "memory"); }
__device__ __forceinline__ void wg_fence() { asm volatile("wgmma.fence.sync.aligned;" ::: "memory"); }
__device__ __forceinline__ void wg_commit() { asm volatile("wgmma.commit_group.sync.aligned;" ::: "memory"); }
__device__ __forceinline__ void wg_wait0() { asm volatile("wgmma.wait_group.sync.aligned 0;" ::: "memory"); }
template <int ACC>
__device__ __forceinline__ void wgmma_rs32(float* d, const uint32_t* a, uint64_t db) {
  asm volatile("{.reg .pred p; setp.ne.b32 p, %21, 0;\n"
               "wgmma.mma_async.sync.aligned.m64n32k16.f32.bf16.bf16 {%0,%1,%2,%3,%4,%5,%6,%7,%8,%9,%10,%11,%12,%13,%14,%15}, {%16,%17,%18,%19}, %20, p, 1, 1, 0;}"
               : "+f"(d[0]), "+f"(d[1]), "+f"(d[2]), "+f"(d[3]), "+f"(d[4]), "+f"(d[5]), "+f"(d[6]), "+f"(d[7]), "+f"(d[8]), "+f"(d[9]),
                 "+f"(d[10]), "+f"(d[11]), "+f"(d[12]), "+f"(d[13]), "+f"(d[14]), "+f"(d[15])
               : "r"(a[0]), "r"(a[1]), "r"(a[2]), "r"(a[3]), "l"(db), "n"(ACC));
}

template <int N> __device__ __forceinline__ void fence_regs(float* d) {
#pragma unroll
  for (int i = 0; i < N; i++) asm volatile("" : "+f"(d[i])::"memory");
}
__device__ __forceinline__ void wg_wait1() { asm volatile("wgmma.wait_group.sync.aligned 1;" ::: "memory"); }
__device__ __forceinline__ void tma_store3(const CUtensorMap* tm, uint32_t src, int c0, int c1, int c2) {
  asm volatile("cp.async.bulk.tensor.3d.global.shared::cta.bulk_group [%0, {%2,%3,%4}], [%1];" ::"l"(tm), "r"(src), "r"(c0), "r"(c1), "r"(c2) : "memory");
}
__device__ __forceinline__ void tma_red3(const CUtensorMap* tm, uint32_t src, int c0, int c1, int c2) {
  asm volatile("cp.reduce.async.bulk.tensor.3d.global.shared::cta.add.bulk_group [%0, {%2,%3,%4}], [%1];" ::"l"(tm), "r"(src), "r"(c0), "r"(c1), "r"(c2) : "memory");
}
__device__ __forceinline__ void tma_red2(const CUtensorMap* tm, uint32_t src, int c0, int c1) {
  asm volatile("cp.reduce.async.bulk.tensor.2d.global.shared::cta.add.bulk_group [%0, {%2,%3}], [%1];" ::"l"(tm), "r"(src), "r"(c0), "r"(c1) : "memory");
}
__device__ __forceinline__ void stsm4(uint32_t a, uint32_t r0, uint32_t r1, uint32_t r2, uint32_t r3) {
  asm volatile("stmatrix.sync.aligned.m8n8.x4.shared.b16 [%0], {%1,%2,%3,%4};" ::"r"(a), "r"(r0), "r"(r1), "r"(r2), "r"(r3) : "memory");
}
__device__ __forceinline__ uint2 lds64(uint32_t a) { uint2 v; asm volatile("ld.shared.v2.b32 {%0,%1}, [%2];" : "=r"(v.x), "=r"(v.y) : "r"(a) : "memory"); return v; }
__device__ __forceinline__ uint32_t hmul2(uint32_t a, uint32_t b) { uint32_t r; asm("mul.rn.bf16x2 %0, %1, %2;" : "=r"(r) : "r"(a), "r"(b)); return r; }
__device__ __forceinline__ void wgmma_ss192t(float* d, uint64_t da, uint64_t db, int acc) {
  asm volatile("{.reg .pred p; setp.ne.b32 p, %98, 0;\n"
    "wgmma.mma_async.sync.aligned.m64n192k16.f32.bf16.bf16 "
    "{%0,%1,%2,%3,%4,%5,%6,%7,%8,%9,%10,%11,%12,%13,%14,%15,%16,%17,%18,%19,%20,%21,%22,%23,%24,%25,%26,%27,%28,%29,%30,%31,%32,%33,%34,%35,%36,%37,%38,%39,%40,%41,%42,%43,%44,%45,%46,%47,%48,%49,%50,%51,%52,%53,%54,%55,%56,%57,%58,%59,%60,%61,%62,%63,%64,%65,%66,%67,%68,%69,%70,%71,%72,%73,%74,%75,%76,%77,%78,%79,%80,%81,%82,%83,%84,%85,%86,%87,%88,%89,%90,%91,%92,%93,%94,%95}, %96, %97, p, 1, 1, 0, 1;}"
    : "+f"(d[0]), "+f"(d[1]), "+f"(d[2]), "+f"(d[3]), "+f"(d[4]), "+f"(d[5]), "+f"(d[6]), "+f"(d[7]), "+f"(d[8]), "+f"(d[9]), "+f"(d[10]), "+f"(d[11]),
      "+f"(d[12]), "+f"(d[13]), "+f"(d[14]), "+f"(d[15]), "+f"(d[16]), "+f"(d[17]), "+f"(d[18]), "+f"(d[19]), "+f"(d[20]), "+f"(d[21]), "+f"(d[22]),
      "+f"(d[23]), "+f"(d[24]), "+f"(d[25]), "+f"(d[26]), "+f"(d[27]), "+f"(d[28]), "+f"(d[29]), "+f"(d[30]), "+f"(d[31]), "+f"(d[32]), "+f"(d[33]),
      "+f"(d[34]), "+f"(d[35]), "+f"(d[36]), "+f"(d[37]), "+f"(d[38]), "+f"(d[39]), "+f"(d[40]), "+f"(d[41]), "+f"(d[42]), "+f"(d[43]), "+f"(d[44]),
      "+f"(d[45]), "+f"(d[46]), "+f"(d[47]), "+f"(d[48]), "+f"(d[49]), "+f"(d[50]), "+f"(d[51]), "+f"(d[52]), "+f"(d[53]), "+f"(d[54]), "+f"(d[55]),
      "+f"(d[56]), "+f"(d[57]), "+f"(d[58]), "+f"(d[59]), "+f"(d[60]), "+f"(d[61]), "+f"(d[62]), "+f"(d[63]), "+f"(d[64]), "+f"(d[65]), "+f"(d[66]),
      "+f"(d[67]), "+f"(d[68]), "+f"(d[69]), "+f"(d[70]), "+f"(d[71]), "+f"(d[72]), "+f"(d[73]), "+f"(d[74]), "+f"(d[75]), "+f"(d[76]), "+f"(d[77]),
      "+f"(d[78]), "+f"(d[79]), "+f"(d[80]), "+f"(d[81]), "+f"(d[82]), "+f"(d[83]), "+f"(d[84]), "+f"(d[85]), "+f"(d[86]), "+f"(d[87]), "+f"(d[88]),
      "+f"(d[89]), "+f"(d[90]), "+f"(d[91]), "+f"(d[92]), "+f"(d[93]), "+f"(d[94]), "+f"(d[95])
    : "l"(da), "l"(db), "r"(acc));
}
__device__ __forceinline__ void wgmma_rs128t(float* d, const uint32_t* a, uint64_t db, int acc) {
  asm volatile("{.reg .pred p; setp.ne.b32 p, %69, 0;\n"
    "wgmma.mma_async.sync.aligned.m64n128k16.f32.bf16.bf16 "
    "{%0,%1,%2,%3,%4,%5,%6,%7,%8,%9,%10,%11,%12,%13,%14,%15,%16,%17,%18,%19,%20,%21,%22,%23,%24,%25,%26,%27,%28,%29,%30,%31,%32,%33,%34,%35,%36,%37,%38,%39,%40,%41,%42,%43,%44,%45,%46,%47,%48,%49,%50,%51,%52,%53,%54,%55,%56,%57,%58,%59,%60,%61,%62,%63}, {%64,%65,%66,%67}, %68, p, 1, 1, 1;}"
    : "+f"(d[0]), "+f"(d[1]), "+f"(d[2]), "+f"(d[3]), "+f"(d[4]), "+f"(d[5]), "+f"(d[6]), "+f"(d[7]), "+f"(d[8]), "+f"(d[9]), "+f"(d[10]), "+f"(d[11]),
      "+f"(d[12]), "+f"(d[13]), "+f"(d[14]), "+f"(d[15]), "+f"(d[16]), "+f"(d[17]), "+f"(d[18]), "+f"(d[19]), "+f"(d[20]), "+f"(d[21]), "+f"(d[22]),
      "+f"(d[23]), "+f"(d[24]), "+f"(d[25]), "+f"(d[26]), "+f"(d[27]), "+f"(d[28]), "+f"(d[29]), "+f"(d[30]), "+f"(d[31]), "+f"(d[32]), "+f"(d[33]),
      "+f"(d[34]), "+f"(d[35]), "+f"(d[36]), "+f"(d[37]), "+f"(d[38]), "+f"(d[39]), "+f"(d[40]), "+f"(d[41]), "+f"(d[42]), "+f"(d[43]), "+f"(d[44]),
      "+f"(d[45]), "+f"(d[46]), "+f"(d[47]), "+f"(d[48]), "+f"(d[49]), "+f"(d[50]), "+f"(d[51]), "+f"(d[52]), "+f"(d[53]), "+f"(d[54]), "+f"(d[55]),
      "+f"(d[56]), "+f"(d[57]), "+f"(d[58]), "+f"(d[59]), "+f"(d[60]), "+f"(d[61]), "+f"(d[62]), "+f"(d[63])
    : "r"(a[0]), "r"(a[1]), "r"(a[2]), "r"(a[3]), "l"(db), "r"(acc));
}
__device__ __forceinline__ void wgmma_rs80(float* d, const uint32_t* a, uint64_t db, int acc) {
  asm volatile("{.reg .pred p; setp.ne.b32 p, %45, 0;\n"
    "wgmma.mma_async.sync.aligned.m64n80k16.f32.bf16.bf16 "
    "{%0,%1,%2,%3,%4,%5,%6,%7,%8,%9,%10,%11,%12,%13,%14,%15,%16,%17,%18,%19,%20,%21,%22,%23,%24,%25,%26,%27,%28,%29,%30,%31,%32,%33,%34,%35,%36,%37,%38,%39}, {%40,%41,%42,%43}, %44, p, 1, 1, 0;}"
    : "+f"(d[0]), "+f"(d[1]), "+f"(d[2]), "+f"(d[3]), "+f"(d[4]), "+f"(d[5]), "+f"(d[6]), "+f"(d[7]), "+f"(d[8]), "+f"(d[9]), "+f"(d[10]), "+f"(d[11]),
      "+f"(d[12]), "+f"(d[13]), "+f"(d[14]), "+f"(d[15]), "+f"(d[16]), "+f"(d[17]), "+f"(d[18]), "+f"(d[19]), "+f"(d[20]), "+f"(d[21]), "+f"(d[22]),
      "+f"(d[23]), "+f"(d[24]), "+f"(d[25]), "+f"(d[26]), "+f"(d[27]), "+f"(d[28]), "+f"(d[29]), "+f"(d[30]), "+f"(d[31]), "+f"(d[32]), "+f"(d[33]),
      "+f"(d[34]), "+f"(d[35]), "+f"(d[36]), "+f"(d[37]), "+f"(d[38]), "+f"(d[39])
    : "r"(a[0]), "r"(a[1]), "r"(a[2]), "r"(a[3]), "l"(db), "r"(acc));
}
__device__ __forceinline__ void wgmma_rs64t(float* d, const uint32_t* a, uint64_t db, int acc) {
  asm volatile("{.reg .pred p; setp.ne.b32 p, %37, 0;\n"
    "wgmma.mma_async.sync.aligned.m64n64k16.f32.bf16.bf16 "
    "{%0,%1,%2,%3,%4,%5,%6,%7,%8,%9,%10,%11,%12,%13,%14,%15,%16,%17,%18,%19,%20,%21,%22,%23,%24,%25,%26,%27,%28,%29,%30,%31}, {%32,%33,%34,%35}, %36, p, 1, 1, 1;}"
    : "+f"(d[0]), "+f"(d[1]), "+f"(d[2]), "+f"(d[3]), "+f"(d[4]), "+f"(d[5]), "+f"(d[6]), "+f"(d[7]), "+f"(d[8]), "+f"(d[9]), "+f"(d[10]), "+f"(d[11]),
      "+f"(d[12]), "+f"(d[13]), "+f"(d[14]), "+f"(d[15]), "+f"(d[16]), "+f"(d[17]), "+f"(d[18]), "+f"(d[19]), "+f"(d[20]), "+f"(d[21]), "+f"(d[22]),
      "+f"(d[23]), "+f"(d[24]), "+f"(d[25]), "+f"(d[26]), "+f"(d[27]), "+f"(d[28]), "+f"(d[29]), "+f"(d[30]), "+f"(d[31])
    : "r"(a[0]), "r"(a[1]), "r"(a[2]), "r"(a[3]), "l"(db), "r"(acc));
}
__device__ __forceinline__ void wgmma_rs224t(float* d, const uint32_t* a, uint64_t db, int acc) {
  asm volatile("{.reg .pred p; setp.ne.b32 p, %117, 0;\n"
    "wgmma.mma_async.sync.aligned.m64n224k16.f32.bf16.bf16 "
    "{%0,%1,%2,%3,%4,%5,%6,%7,%8,%9,%10,%11,%12,%13,%14,%15,%16,%17,%18,%19,%20,%21,%22,%23,%24,%25,%26,%27,%28,%29,%30,%31,%32,%33,%34,%35,%36,%37,%38,%39,%40,%41,%42,%43,%44,%45,%46,%47,%48,%49,%50,%51,%52,%53,%54,%55,%56,%57,%58,%59,%60,%61,%62,%63,%64,%65,%66,%67,%68,%69,%70,%71,%72,%73,%74,%75,%76,%77,%78,%79,%80,%81,%82,%83,%84,%85,%86,%87,%88,%89,%90,%91,%92,%93,%94,%95,%96,%97,%98,%99,%100,%101,%102,%103,%104,%105,%106,%107,%108,%109,%110,%111}, {%112,%113,%114,%115}, %116, p, 1, 1, 1;}"
    : "+f"(d[0]), "+f"(d[1]), "+f"(d[2]), "+f"(d[3]), "+f"(d[4]), "+f"(d[5]), "+f"(d[6]), "+f"(d[7]), "+f"(d[8]), "+f"(d[9]), "+f"(d[10]), "+f"(d[11]),
      "+f"(d[12]), "+f"(d[13]), "+f"(d[14]), "+f"(d[15]), "+f"(d[16]), "+f"(d[17]), "+f"(d[18]), "+f"(d[19]), "+f"(d[20]), "+f"(d[21]), "+f"(d[22]),
      "+f"(d[23]), "+f"(d[24]), "+f"(d[25]), "+f"(d[26]), "+f"(d[27]), "+f"(d[28]), "+f"(d[29]), "+f"(d[30]), "+f"(d[31]), "+f"(d[32]), "+f"(d[33]),
      "+f"(d[34]), "+f"(d[35]), "+f"(d[36]), "+f"(d[37]), "+f"(d[38]), "+f"(d[39]), "+f"(d[40]), "+f"(d[41]), "+f"(d[42]), "+f"(d[43]), "+f"(d[44]),
      "+f"(d[45]), "+f"(d[46]), "+f"(d[47]), "+f"(d[48]), "+f"(d[49]), "+f"(d[50]), "+f"(d[51]), "+f"(d[52]), "+f"(d[53]), "+f"(d[54]), "+f"(d[55]),
      "+f"(d[56]), "+f"(d[57]), "+f"(d[58]), "+f"(d[59]), "+f"(d[60]), "+f"(d[61]), "+f"(d[62]), "+f"(d[63]), "+f"(d[64]), "+f"(d[65]), "+f"(d[66]),
      "+f"(d[67]), "+f"(d[68]), "+f"(d[69]), "+f"(d[70]), "+f"(d[71]), "+f"(d[72]), "+f"(d[73]), "+f"(d[74]), "+f"(d[75]), "+f"(d[76]), "+f"(d[77]),
      "+f"(d[78]), "+f"(d[79]), "+f"(d[80]), "+f"(d[81]), "+f"(d[82]), "+f"(d[83]), "+f"(d[84]), "+f"(d[85]), "+f"(d[86]), "+f"(d[87]), "+f"(d[88]),
      "+f"(d[89]), "+f"(d[90]), "+f"(d[91]), "+f"(d[92]), "+f"(d[93]), "+f"(d[94]), "+f"(d[95]), "+f"(d[96]), "+f"(d[97]), "+f"(d[98]), "+f"(d[99]),
      "+f"(d[100]), "+f"(d[101]), "+f"(d[102]), "+f"(d[103]), "+f"(d[104]), "+f"(d[105]), "+f"(d[106]), "+f"(d[107]), "+f"(d[108]), "+f"(d[109]),
      "+f"(d[110]), "+f"(d[111])
    : "r"(a[0]), "r"(a[1]), "r"(a[2]), "r"(a[3]), "l"(db), "r"(acc));
}
__device__ __forceinline__ void wgmma_rs192t(float* d, const uint32_t* a, uint64_t db, int acc) {
  asm volatile("{.reg .pred p; setp.ne.b32 p, %101, 0;\n"
    "wgmma.mma_async.sync.aligned.m64n192k16.f32.bf16.bf16 "
    "{%0,%1,%2,%3,%4,%5,%6,%7,%8,%9,%10,%11,%12,%13,%14,%15,%16,%17,%18,%19,%20,%21,%22,%23,%24,%25,%26,%27,%28,%29,%30,%31,%32,%33,%34,%35,%36,%37,%38,%39,%40,%41,%42,%43,%44,%45,%46,%47,%48,%49,%50,%51,%52,%53,%54,%55,%56,%57,%58,%59,%60,%61,%62,%63,%64,%65,%66,%67,%68,%69,%70,%71,%72,%73,%74,%75,%76,%77,%78,%79,%80,%81,%82,%83,%84,%85,%86,%87,%88,%89,%90,%91,%92,%93,%94,%95}, {%96,%97,%98,%99}, %100, p, 1, 1, 1;}"
    : "+f"(d[0]), "+f"(d[1]), "+f"(d[2]), "+f"(d[3]), "+f"(d[4]), "+f"(d[5]), "+f"(d[6]), "+f"(d[7]), "+f"(d[8]), "+f"(d[9]), "+f"(d[10]), "+f"(d[11]),
      "+f"(d[12]), "+f"(d[13]), "+f"(d[14]), "+f"(d[15]), "+f"(d[16]), "+f"(d[17]), "+f"(d[18]), "+f"(d[19]), "+f"(d[20]), "+f"(d[21]), "+f"(d[22]),
      "+f"(d[23]), "+f"(d[24]), "+f"(d[25]), "+f"(d[26]), "+f"(d[27]), "+f"(d[28]), "+f"(d[29]), "+f"(d[30]), "+f"(d[31]), "+f"(d[32]), "+f"(d[33]),
      "+f"(d[34]), "+f"(d[35]), "+f"(d[36]), "+f"(d[37]), "+f"(d[38]), "+f"(d[39]), "+f"(d[40]), "+f"(d[41]), "+f"(d[42]), "+f"(d[43]), "+f"(d[44]),
      "+f"(d[45]), "+f"(d[46]), "+f"(d[47]), "+f"(d[48]), "+f"(d[49]), "+f"(d[50]), "+f"(d[51]), "+f"(d[52]), "+f"(d[53]), "+f"(d[54]), "+f"(d[55]),
      "+f"(d[56]), "+f"(d[57]), "+f"(d[58]), "+f"(d[59]), "+f"(d[60]), "+f"(d[61]), "+f"(d[62]), "+f"(d[63]), "+f"(d[64]), "+f"(d[65]), "+f"(d[66]),
      "+f"(d[67]), "+f"(d[68]), "+f"(d[69]), "+f"(d[70]), "+f"(d[71]), "+f"(d[72]), "+f"(d[73]), "+f"(d[74]), "+f"(d[75]), "+f"(d[76]), "+f"(d[77]),
      "+f"(d[78]), "+f"(d[79]), "+f"(d[80]), "+f"(d[81]), "+f"(d[82]), "+f"(d[83]), "+f"(d[84]), "+f"(d[85]), "+f"(d[86]), "+f"(d[87]), "+f"(d[88]),
      "+f"(d[89]), "+f"(d[90]), "+f"(d[91]), "+f"(d[92]), "+f"(d[93]), "+f"(d[94]), "+f"(d[95])
    : "r"(a[0]), "r"(a[1]), "r"(a[2]), "r"(a[3]), "l"(db), "r"(acc));
}

struct Desc {
  uint32_t lo, hi;
  __device__ __forceinline__ Desc operator+(uint32_t o) const { return {lo + o, hi}; }
  __device__ __forceinline__ operator uint64_t() const { return ((uint64_t)hi << 32) | lo; }
};
__device__ __forceinline__ Desc mk_desc(uint32_t addr, uint32_t lbo, uint32_t sbo, uint32_t mode) {
  return {(addr >> 4) | ((lbo >> 4) << 16), (sbo >> 4) | (mode << 30)};
}

struct AttMask {
  uint32_t hi, z;
  float c0, c1, mb[10];
  __device__ __forceinline__ AttMask(uint32_t tid, uint32_t sb) {
    constexpr float SCL = 0.07216878364870322f * 1.4426950408889634f;
    hi = pin(tid & 64); z = sb >> 31;
    c0 = hi ? 0.f : SCL; c1 = hi ? SCL : 0.f;
    const int tt = (int)pin(((tid >> 1) & 16) + ((tid >> 2) & 7) - 2 * (tid & 3));
#pragma unroll
    for (int i = 0; i < 10; i++) mb[i] = 8 * ((i >> 1) - 1) + (i & 1) > tt ? -INFINITY : 0.f;
  }
};
__device__ __forceinline__ void att_softmax(const AttMask& m, const float* s_, uint32_t (&p)[5][4], float g0, float g1) {
  const uint32_t hi = m.hi;
  const float c0 = m.c0, c1 = m.c1;
  const float* mb = m.mb;
  float v[20], mx[2], sum[2];
#pragma unroll
  for (int i = 0; i < 20; i++)
    if (i != 16 && i != 17) v[i] = fmaf(s_[20 + i], c1, i < 4 ? s_[i] * c0 : fmaf(s_[i], c0, mb[2 * ((i >> 2) - ((i >> 1) & 1)) + (i & 1)]));
  mx[0] = fmaxf(fmaxf(fmaxf(v[0], v[1]), fmaxf(v[4], v[5])), fmaxf(fmaxf(v[8], v[9]), fmaxf(v[12], v[13])));
  mx[1] = fmaxf(fmaxf(fmaxf(v[2], v[3]), fmaxf(v[6], v[7])), fmaxf(fmaxf(v[10], v[11]), fmaxf(v[14], v[15])));
  mx[1] = fmaxf(mx[1], fmaxf(v[18], v[19]));
  {
    const float ni = __uint_as_float(0xff800000u | m.z), a_ = fminf(mx[0], ni), b_ = fminf(mx[1], ni);
    mx[0] = fmaxf(mx[0], b_); mx[1] = fmaxf(mx[1], a_);
  }
#pragma unroll
  for (int o = 1; o < 4; o <<= 1)
#pragma unroll
    for (int h = 0; h < 2; h++) mx[h] = fmaxf(mx[h], __shfl_xor_sync(~0u, mx[h], o));
#pragma unroll
  for (int i = 0; i < 20; i++) v[i] = i == 16 || i == 17 ? 0.f : ex2(v[i] - mx[(i >> 1) & 1]);
  sum[0] = ((v[0] + v[1]) + (v[4] + v[5])) + ((v[8] + v[9]) + (v[12] + v[13]));
  sum[1] = ((v[2] + v[3]) + (v[6] + v[7])) + ((v[10] + v[11]) + (v[14] + v[15])) + (v[18] + v[19]);
  {
    const float z = __uint_as_float(m.z), a_ = sum[0];
    sum[0] = fmaf(sum[1], z, a_); sum[1] = fmaf(a_, z, sum[1]);
  }
  sum[0] += __shfl_xor_sync(~0u, sum[0], 1);
  sum[1] += __shfl_xor_sync(~0u, sum[1], 1);
  {
    const float z = __uint_as_float(m.z), a_ = sum[0];
    sum[0] = fmaf(sum[1], z, a_); sum[1] = fmaf(a_, z, sum[1]);
  }
  sum[0] += __shfl_xor_sync(~0u, sum[0], 2);
  sum[1] += __shfl_xor_sync(~0u, sum[1], 2);
  const float r0 = g0 * rcp(sum[0]), r1 = g1 * rcp(sum[1]);
#pragma unroll
  for (int j = 0; j < 5; j++)
#pragma unroll
    for (int h = 0; h < 2; h++) {
      const uint32_t pt = j == 4 && h == 0 ? 0u : pack2(v[4 * j + 2 * h] * (h ? r1 : r0), v[4 * j + 2 * h + 1] * (h ? r1 : r0));
      p[j >> 1][(j & 1) * 2 + h] = hi ? 0u : pt;
      p[(j + 5) >> 1][((j + 5) & 1) * 2 + h] = hi ? pt : 0u;
    }
#pragma unroll
  for (int i = 0; i < 20; i++) asm volatile("" : "+r"(p[i >> 2][i & 3]));
}

constexpr int NPQ = 2;
#define NQ 12
#define NQ_WIN 8
#define NO_EARLY 6
#define NO_MID 9
#define NW1 16
#define NW1A 10
#define VLD 6
#define VB 0
#define XPF 3
#define WSPLIT 8
#define NQ_W1 8
#define WD 700
#define PDS 70
#define PDT 50
#define CT 999
#define PFB 8000
#define VBW 3
#define PD 780
constexpr int R_WQ = 0;
constexpr int R_WO = R_WQ + 8 * (20 - NPQ) * 512;
constexpr int R_XT = R_WO + 14 * 12 * 512;
constexpr int R_MEM = R_XT;
constexpr int R_QB = R_XT + 40960;
constexpr int R_QA = R_QB + 1024;
constexpr int R_O2 = R_QA + 1024;
constexpr int R_VS = R_O2 + 1024;
constexpr int R_KT = R_VS + 1024;
constexpr int R_VT = R_KT + 5120;
constexpr int R_V1 = R_VT + 5120;
constexpr int R_SX = R_V1 + 8192;
constexpr int R_VM = R_SX + 4608;
constexpr int R_BAR = R_VM + 2048;
constexpr int R_MI = R_BAR + 64;
constexpr int R_EB = R_MI + 64;
constexpr int R_SMEM = R_EB + 64 + 96;
constexpr int E_KA = 0, E_VA = 30720, E_KB = R_XT + 10240, E_VB0 = 61440, E_VB1 = R_V1, E_VB2 = R_XT;
static_assert(R_V1 + 10240 <= R_BAR && E_VB0 + 10240 <= R_WO, "chunks");
static_assert(NPQ == 2 && R_XT % 1024 == 0 && R_KT % 1024 == 0 && R_VT % 1024 == 0 && R_V1 % 1024 == 0 && R_WO % 1024 == 0, "align");
constexpr int R_SMEM_ALLOC = R_SMEM;
static_assert(R_SMEM_ALLOC <= 232448, "smem");

#define TR(i) do {} while (0)

__device__ __forceinline__ void red_pair(unsigned char* p, float lo, float hi) {
  const int b = __float2int_rn(lo), a = __float2int_rn(hi);
  asm volatile("{.reg .b64 t; mov.b64 t, {%1,%2}; red.relaxed.gpu.global.add.u64 [%0], t;}" ::"l"(p), "r"(b + ((1 << 29) + (1 << 23))), "r"(a * 8) : "memory");
}
__device__ __forceinline__ unsigned long long swap0(unsigned char* p) {
  unsigned long long r;
  asm volatile("atom.relaxed.gpu.global.exch.b64 %0, [%1], 0;" : "=l"(r) : "l"(p) : "memory");
  return r;
}
__device__ __forceinline__ uint32_t dec_pair(uint32_t lo, uint32_t hi, uint32_t bias) { return pack2((float)(int)(lo * 8u + bias), (float)(int)hi); }

__global__ void __cluster_dims__(3, 1, 1) __launch_bounds__(256, 1)
rec_kernel(const __grid_constant__ CUtensorMap tmX, const __grid_constant__ CUtensorMap tmK, const __grid_constant__ CUtensorMap tmV,
           const __grid_constant__ CUtensorMap tmWq, const __grid_constant__ CUtensorMap tmWq2, const __grid_constant__ CUtensorMap tmWk,
           const __grid_constant__ CUtensorMap tmWv, const __grid_constant__ CUtensorMap tmWo, const __grid_constant__ CUtensorMap tmOut,
           const bf16* __restrict__ mem0,
           const bf16* __restrict__ Wq, const bf16* __restrict__ Wk, const bf16* __restrict__ Wv, const bf16* __restrict__ Wo, const bf16* __restrict__ x, const bf16* __restrict__ gate_w,
           bf16* __restrict__ out, unsigned char* __restrict__ red) {
  extern __shared__ __align__(1024) unsigned char smem[];
  const uint32_t sb = smem_u32(smem);
  const int tid = threadIdx.x, lane = tid & 31, wid = __shfl_sync(~0u, tid >> 5, 0), g = wid >> 2, w = wid & 3;
  const int cta = blockIdx.x, head = cta / 3, rank = cta % 3;
  const int D0 = head * DH + rank * 64;
  const int tile0 = rank == 0 ? 0 : (rank == 1 ? 14 : 26);
  const uint32_t XBAR = sb + R_BAR, SBAR = XBAR + 8, OBAR = XBAR + 16, VBAR = XBAR + 24, FBAR = XBAR + 32, WBAR = XBAR + 40;
  constexpr uint32_t ONES = 0x3F803F80u;
  uint32_t ww[40][4], wqp[NPQ][4];
  GTR(0);
  if (wid == 0) {
    if (lane == 0) {
      mbar_init(XBAR, 1); mbar_init(SBAR, 4); mbar_init(OBAR, 5); mbar_init(VBAR, 1); mbar_init(FBAR, 2);
      mbar_init(WBAR, 1); mbar_init(WBAR + 8, 1); mbar_init(WBAR + 16, 1);
      for (int i = 0; i < 6; i++) mbar_init(sb + R_EB + i * 8, i < 4 ? 1 : 2);
      asm volatile("fence.mbarrier_init.release.cluster;" ::: "memory");
      mbar_expect(WBAR, 81920); mbar_expect(WBAR + 8, 81920 + 2 * NPQ * 2048); mbar_expect(XBAR, 40960);
      mbar_expect(SBAR, 3072); mbar_expect(OBAR, 2048); mbar_expect(VBAR, 8192);
      for (int i = 0; i < 4; i++) mbar_expect(sb + R_EB + i * 8, 30720);
      sts128(sb + R_MI + 48, 0, 0, 0, 0);
      sts32(sb + R_MI, *(volatile uint32_t*)&g_epoch + 1);
    }
    __syncwarp();
    if (lane < 5) tma_load2(sb + lane * 16384, &tmWk, D0, lane * 128, WBAR);
    if (lane == 5) tma_load3(sb + R_XT, &tmX, 0, 0, 0, XBAR);
    if (lane < 5) tma_load2(lane < 4 ? sb + 81920 + lane * 16384 : sb + R_QB, &tmWv, D0, lane * 128, WBAR + 8);
    if (lane < 2) tma_load2(sb + R_QB + 16384 + lane * 4096, &tmWq2, D0, lane * 320, WBAR + 8);
  }
  if (tid == 32) { prefetch_map(&tmWq); prefetch_map(&tmWo); prefetch_map(&tmK); prefetch_map(&tmV); prefetch_map(&tmOut); }
  if (tid >= 64 && tid < 144) prefetch_l2(mem0 + (tid - 64) * 64);
  __syncthreads();
  GTR(1);
  asm volatile("griddepcontrol.launch_dependents;" ::: "memory");
  const uint32_t c0 = clk32();
  {
    uint32_t xm = 0;
    {
      const int row = cta * 8 + wid;
      uint4 gw[3], v[3][3];
#pragma unroll
      for (int r = 0; r < 3; r++)
#pragma unroll
        for (int i = 0; i < 3; i++)
          v[r][i] = (i < 2 || lane < 16) && (r < 2 || row < 512) ? __ldg((const uint4*)(x + (size_t)(row + r * 768) * DM) + lane + 32 * i) : make_uint4(0, 0, 0, 0);
#pragma unroll
      for (int i = 0; i < 3; i++) gw[i] = (i < 2 || lane < 16) ? __ldg((const uint4*)gate_w + lane + 32 * i) : make_uint4(0, 0, 0, 0);
      if (wid == 7) {
        spin_until(c0, PFB);
        if (lane < 2) asm volatile("cp.async.bulk.prefetch.tensor.2d.L2.global [%0, {%1,%2}];" ::"l"(&tmWq), "r"(D0), "r"(32 + lane * 144) : "memory");
      }
      if (cta < 80 && tid < 128) ((uint4*)(out + (S_TOK - 128) * DM))[cta * 128 + tid] = make_uint4(0, 0, 0, 0);
      float z = 0.f;
#pragma unroll
      for (int r = 0; r < 3; r++) {
        float s_ = 0.f;
#pragma unroll
        for (int i = 0; i < 3; i++) {
          const uint4 q = v[r][i];
          xm = hmaxabs2(hmaxabs2(xm, hmaxabs2(q.x, q.y)), hmaxabs2(q.z, q.w));
          const uint32_t p0 = hmul2(q.x, gw[i].x), p1 = hmul2(q.y, gw[i].y), p2 = hmul2(q.z, gw[i].z), p3 = hmul2(q.w, gw[i].w);
          s_ += ((bf_lo(p0) + bf_hi(p0)) + (bf_lo(p1) + bf_hi(p1))) + ((bf_lo(p2) + bf_hi(p2)) + (bf_lo(p3) + bf_hi(p3)));
        }
#pragma unroll
        for (int o = 16; o; o >>= 1) s_ += __shfl_xor_sync(~0u, s_, o);
        if (lane == r) z = s_;
      }
      z = bf_lo(pack2(z, 0.f));
      const float gv = bf_lo(pack2(1.f / (1.f + __expf(-z)), 0.f));
      if (lane < 3) sts32(sb + R_EB + 64 + lane * 32 + wid * 4, __float_as_uint(gv));
      asm volatile("fence.proxy.async.global;" ::: "memory");
    }
    xm = __reduce_max_sync(~0u, max((xm << 16) & 0x7fffffffu, xm & 0x7fff0000u));
    const uint32_t p = sb + (lane >> 4) * 1024 + (lane & 7) * 128 + (((2 * w + ((lane >> 3) & 1)) ^ (lane & 7)) << 4);
    mbar_wait(WBAR + 8 * g, 0);
    GTR(2);
#pragma unroll
    for (int f = 0; f < 40; f++) ldsm4t(ww[f], (f >= 32 && g == 1) ? p + R_QB + (f - 32) * 2048 : p + g * 81920 + f * 2048);
    mbar_wait(WBAR + 8, 0);
    GTR(3);
#pragma unroll
    for (int f = 0; f < NPQ; f++) ldsm4t(wqp[f], p + R_QB + 16384 + g * 4096 + f * 2048);
    __syncthreads();
    GTR(5);
    asm volatile("barrier.cluster.arrive.relaxed.aligned;" ::: "memory");
    if (wid == 3 && lane < (cta < 64 ? 24 : 16)) {
      const float gv = __uint_as_float(lds32(sb + R_EB + 64 + lane * 4));
      float* gp = g_gate + cta * 8 + (lane >> 3) * 768 + (lane & 7);
      gp[0] = gv; gp[S_TOK] = bf_lo(pack2(1.f - gv, 0.f));
    }
    if (wid == 0) {
      if (lane == 0) mbar_expect(WBAR + 16, 18 * 4096 + 21 * 4096);
      __syncwarp();
      if (lane < 4) tma_load2(sb + R_WQ + lane * 18432, &tmWq, D0, (lane >> 1) * 320 + 32 + (lane & 1) * 144, WBAR + 16);
      else if (lane < 7) tma_load3(sb + R_WO + ((lane - 1 - rank) % 3) * 28672, &tmWo, 0, head * DH + (lane - 4) * 64, tile0 >> 1, WBAR + 16);
      __syncwarp();
    }
    GTR(6);
    float nv[4] = {0.f, 0.f, 0.f, 0.f};
#pragma unroll
    for (int f = 0; f < 40; f++) {
      const uint32_t a[4] = {ww[f][0] & 0x7fff7fffu, ww[f][1] & 0x7fff7fffu, ww[f][2] & 0x7fff7fffu, ww[f][3] & 0x7fff7fffu};
      mma16816(nv, a, ONES, ONES);
    }
    const uint32_t mv = __reduce_max_sync(~0u, __float_as_uint(fmaxf(nv[0], nv[2])));
    if (lane == 0) { if (g == 1) smax32(sb + R_MI + 48, mv); smax32(sb + R_MI + 52, xm); }
  }
  GTR(4);

  const uint32_t rF_ = opaque(sb + lane * 16);
  const uint32_t rP_ = opaque(sb + (lane >> 4) * 1024 + (lane & 7) * 128 + (((2 * w + ((lane >> 3) & 1)) ^ (lane & 7)) << 4));
  const int tA = g == 1 ? 2 * w : (rank != 1 ? (w < 2 ? 8 + 2 * w : 10 + w) : 8 + w);
  const bool two = g == 1 || (w < 2 && rank != 1);
  const uint32_t r1 = rank == 2 ? 0 : rank + 1, r2 = rank == 0 ? 2 : rank - 1;
  const uint32_t rW_ = opaque(sb + R_WO + (tA >> 1) * 4096 + ((lane >> 4) * 8 + (lane & 7)) * 64 +
                             (((2 * (tA & 1) + ((lane >> 3) & 1)) ^ ((lane >> 1) & 3)) << 4));
  const uint32_t toff = rb_q((tile0 + tA) >> 2) + rb_j(4 * (tile0 + tA)), zoff = rb_q((cta % 20) >> 1) + rb_j((cta % 20) * 8);
  uint32_t wqt[NQ][4];
  float u = 1.f;
  uint32_t t0 = 0;
  int s = -1;

#define WOFF(ks) (((ks) >> 2) * 28672 + ((ks) & 3) * 1024)
#define XDESC(j) (((uint64_t)0x40000040 << 32) | (dlo + ((((j) >> 2) * 4096 + ((j) & 3) * 32) >> 4)))

  auto vsend = [&]() {
    if (elect()) {
      bulk_s2s(mapa(sb + R_V1 + 4096, r1), sb + R_VT + 1024, 4096, mapa(VBAR, r1));
      bulk_s2s(mapa(sb + R_V1, r2), sb + R_VT + 1024, 4096, mapa(VBAR, r2));
    }
    __syncwarp();
  };
  auto window = [&](auto G_, auto KIND_) {
    constexpr int G = decltype(G_)::value;
    constexpr bool FIRST = decltype(KIND_)::value == 0;
    const uint32_t rF = pin(rF_), rP = pin(rP_);
    float d[16];
    const uint32_t dlo = pin(((sb + R_XT) >> 4) | 0x10000);
    const uint32_t wqS = rP + R_WQ + G * (20 - NPQ) * 2048;
    uint4 y[5];
    unsigned long long zr = 0;
    const uint32_t t = w * 32 + ((rF - sb) >> 4);
    if (G == 0) zr = swap0(red + (rb_b(s + 2) + zoff + rb_j(t >> 4) + (t & 15) * 8));
    if (G == 0) {
      if (!FIRST && w == 3) {
        if (elect()) {
          mbar_expect(SBAR, 3072); mbar_expect(OBAR, 2048); mbar_expect(VBAR, 8192);
          asm volatile("mbarrier.arrive.relaxed.cluster.shared::cluster.b64 _, [%0];" ::"r"(mapa(FBAR, r1)) : "memory");
          asm volatile("mbarrier.arrive.relaxed.cluster.shared::cluster.b64 _, [%0];" ::"r"(mapa(FBAR, r2)) : "memory");
        }
        __syncwarp();
      }
    }
    const unsigned char* yp = red + (rb_b(s) + rb_j(t >> 3) + (t & 7) * 16);
    auto poll = [&]() {
      TR(10);
      spin_until(t0, PD);
#pragma unroll
      for (int q = 0; q < 5; q++) y[q] = ldg_rlx128(yp + rb_q(G * 5 + q));
      TR(9);
      sched_fence(sb);
    };
    constexpr int WS = FIRST || G == 1 ? 40 : WSPLIT;
    if (!FIRST && G == 0) {
#pragma unroll
      for (int f = 0; f < NQ_WIN; f++) ldsm4t(wqt[f], wqS + f * 2048);
      asm volatile("" : "+l"(yp));
      mbar_wait(XBAR, (s + 1) & 1);
      if (WS) spin_until(t0, WD);
    } else {
      mbar_wait(XBAR, (s + 1) & 1);
    }
    TR(11);
    if (WS == 0) { poll(); spin_until(t0, WD); }
    wg_fence();
    wgmma_rs32<0>(d, ww[0], XDESC(0));
#pragma unroll
    for (int j = 1; j < WS; j++) wgmma_rs32<1>(d, ww[j], XDESC(j));
    if (FIRST) {
      const unsigned short* m = (const unsigned short*)mem0 + (t & 1) * 4 * DM + G * 320 + (t >> 1);
#pragma unroll
      for (int q = 0; q < 5; q++) y[q] = make_uint4(m[q * 64], m[q * 64 + DM], m[q * 64 + 2 * DM], m[q * 64 + 3 * DM]);
    } else if (G == 0 && WS) {
      poll();
    }
#pragma unroll
    for (int j = WS ? WS : 1; j < 40; j++) wgmma_rs32<1>(d, ww[j], XDESC(j));
    wg_commit();
    if (!FIRST && G == 1) {
      asm volatile("" : "+l"(yp));
      mbar_wait(FBAR, s & 1);
#pragma unroll
      for (int f = 0; f < NQ_W1; f++) ldsm4t(wqt[f], wqS + f * 2048);
      if (w == 1) {
        if (elect()) {
          bulk_wait0();
          asm volatile("red.relaxed.gpu.global.add.u32 [%0], 1;" ::"l"(&g_segcnt[s]) : "memory");
          asm volatile("red.relaxed.gpu.global.add.u32 [%0], 1;" ::"l"(&g_prog) : "memory");
          if (s == NSEG - 2) {
            asm volatile("fence.proxy.async.global;" ::: "memory");
#pragma unroll 1
            for (int b = 0; b < 6; b++)
              tma_load2(sb + b * 10240 + 5120, b < 3 ? &tmK : &tmV, head * DH + (b % 3) * 64, (NSEG - 3) * LK, sb + R_EB + (b / 3) * 8);
          }
        }
        __syncwarp();
      }
    }
    if (FIRST) asm volatile("barrier.cluster.wait.acquire.aligned;" ::: "memory");
    wg_wait0();
    fence_regs<16>(d);
    TR(13);
    bar_arrive(8 + G, 256);
    if (!FIRST && G == 1) poll();
    {
      uint32_t pk[8];
#pragma unroll
      for (int q = 0; q < 8; q++) pk[q] = pack2(d[2 * q], d[2 * q + 1]);
      stsm4t(rP + (G == 1 ? R_VT : R_KT) + 1024, pk[0], pk[1], pk[2], pk[3]);
      stsm4t(rP + (G == 1 ? R_VT : R_KT) + 3072, pk[4], pk[5], pk[6], pk[7]);
      if (G == 1) {
        fence_async_smem();
        if (w != VBW) bar_arrive(6, 128);
        else { bar_sync(6, 128); vsend(); }
      }
    }
    if (FIRST) {
      mbar_wait(WBAR + 16, 0);
      if (G == 0 && cta) GTR(11);
      const uint32_t woA = rW_;
      float na[4] = {0.f, 0.f, 0.f, 0.f}, nb[4] = {0.f, 0.f, 0.f, 0.f};
#pragma unroll 2
      for (int ks = 0; ks < 12; ks++) {
        uint32_t a[4], b[4];
        ldsm4t(a, woA + WOFF(ks));
        ldsm4t(b, (two ? woA ^ 32 : woA) + WOFF(ks));
#pragma unroll
        for (int q = 0; q < 4; q++) { a[q] &= 0x7fff7fffu; b[q] &= 0x7fff7fffu; }
        mma16816(na, a, ONES, ONES);
        mma16816(nb, b, ONES, ONES);
      }
      const uint32_t mo = __reduce_max_sync(~0u, __float_as_uint(fmaxf(fmaxf(na[0], na[2]), fmaxf(nb[0], nb[2]))));
      if (rF == sb) smax32(sb + R_MI + 56, mo);
      __syncthreads();
      if (G == 1 && w == 2) {
        const uint4 r = lds128(sb + R_MI + 48);
        const uint32_t epoch = lds32(sb + R_MI);
        if (rF == sb) stg_rlx64(&g_rec[cta], (r.y & 0xffff0000u) | (epoch & 0xffffu), ((r.x + 0xffffu) & 0xffff0000u) | ((r.z + 0xffffu) >> 16));
      }
    }
#pragma unroll
    for (int f = FIRST ? 0 : (G == 1 ? NQ_W1 : NQ_WIN); f < NQ; f++) ldsm4t(wqt[f], wqS + f * 2048);
    if (FIRST) sched_fence(sb);
    TR(14);
    const uint32_t ma = sb + R_MEM + G * 5120 + t * 8;
    if (FIRST) {
      bar_sync(9 - G, 256);
#pragma unroll
      for (int j = 0; j < 5; j++) sts64(ma + j * 1024, y[j].x | (y[j].y << 16), y[j].z | (y[j].w << 16));
    } else {
      int n = 0;
#pragma unroll 1
      while (!__all_sync(~0u, (y[0].y & y[0].w & y[1].y) & (y[1].w & y[2].y & y[2].w) & (y[3].y & y[3].w & y[4].y) & (y[4].w & 4))) {
#pragma unroll
        for (int j = 0; j < 5; j++) if (!(y[j].y & y[j].w & 4)) y[j] = ldg_rlx128(yp + rb_q(G * 5 + j));
        if (++n > SPIN_MAX) { g_err = 5; break; }
      }
      const uint32_t bias = 0x80000000u + (sb >> 31);
      bar_sync(9 - G, 256);
#pragma unroll
      for (int j = 0; j < 5; j++) sts64(ma + j * 1024, dec_pair(y[j].x, y[j].y, bias), dec_pair(y[j].z, y[j].w, bias));
    }
    if (G == 0 && zr == ~0ull) g_err = 9;
    TR(0);
  };

  auto oproj = [&](auto TWO_, auto NPRE_, auto& wot, const uint32_t rF, const uint32_t woA, const uint32_t woB,
                   float sm0, float sm1, bool have_sums) {
    constexpr bool TWO = decltype(TWO_)::value;
    constexpr int NPRE = decltype(NPRE_)::value;
    float c[4][4];
#pragma unroll
    for (int q = 0; q < 4; q++) c[q][0] = c[q][1] = c[q][2] = c[q][3] = 0.f;
    unsigned char* sp = red + (rb_b(s) + toff + ((rF - sb) & 256) + (((rF - sb) >> 1) & 120));
    bar_sync(3, 256);
    TR(8);
    uint4 ob[6];
    ob[0] = lds128(rF + R_QB); ob[1] = lds128(rF + R_QB + 512);
    const float2 su = lds64f(sb + R_MI + 48);
    if (!have_sums) { const float2 t = lds64f(sb + R_MI + 16 + (((rF - sb) >> 1) & 24)); sm0 = t.x; sm1 = t.y; }
#pragma unroll
    for (int p = 0; p < 6; p++) {
      if (p + 2 < 6) ob[p + 2] = lds128(rF + (p < 2 ? R_QA : R_O2) + (p & 1) * 512);
#pragma unroll
      for (int e = 0; e < 2; e++) {
        const int ks = 2 * p + e;
        const uint32_t b0 = e ? ob[p].z : ob[p].x, b1 = e ? ob[p].w : ob[p].y;
        if (TWO) {
          const int iA = 2 * ks, iB = iA + 1;
          mma16816(c[e], wot[iA % NPRE], b0, b1);
          if (iA + NPRE < 24) ldsm4t(wot[iA % NPRE], woA + WOFF((iA + NPRE) >> 1));
          mma16816(c[2 + e], wot[iB % NPRE], b0, b1);
          if (iB + NPRE < 24) ldsm4t(wot[iB % NPRE], woB + WOFF((iB + NPRE) >> 1));
        } else {
          mma16816(c[ks & 3], wot[ks], b0, b1);
        }
      }
    }
    const float f0 = su.x * rcp(sm0), f1 = su.x * rcp(sm1);
    t0 = clk32() + (TWO ? (have_sums ? -PDT : 0) : PDS);
    u = su.y;
    if (TWO) {
      red_pair(sp, (c[0][0] + c[1][0]) * f0, (c[0][1] + c[1][1]) * f1);
      red_pair(sp + rb_j(2), (c[0][2] + c[1][2]) * f0, (c[0][3] + c[1][3]) * f1);
      red_pair(sp + rb_j(4), (c[2][0] + c[3][0]) * f0, (c[2][1] + c[3][1]) * f1);
      red_pair(sp + rb_j(6), (c[2][2] + c[3][2]) * f0, (c[2][3] + c[3][3]) * f1);
    } else {
      red_pair(sp, ((c[0][0] + c[1][0]) + (c[2][0] + c[3][0])) * f0, ((c[0][1] + c[1][1]) + (c[2][1] + c[3][1])) * f1);
      red_pair(sp + rb_j(2), ((c[0][2] + c[1][2]) + (c[2][2] + c[3][2])) * f0, ((c[0][3] + c[1][3]) + (c[2][3] + c[3][3])) * f1);
    }
    TR(15);
  };

  auto step = [&](auto G_, auto LAST_) {
    constexpr int G = decltype(G_)::value;
    constexpr bool LAST = decltype(LAST_)::value;
    __syncthreads();
    const uint32_t rF = pin(rF_), rP = pin(rP_);
    TR(1);
    if (LAST) {
      const uint32_t l = (rF - sb) >> 4;
      uint4* qp = g_Ql + ((head * 2 + G) * 4 + w) * 384 + l;
      if ((int)lds32(sb + R_MI + 4) < 0) {
#pragma unroll 1
        for (int i = 0; i < 48; i++) {
          const bf16* xr = x + (size_t)(S_TOK - 128 + G * 64 + w * 16 + (l >> 2) + (i & 1) * 8) * DM;
          const uint32_t* wr = (const uint32_t*)(Wq + head * DH + (i >> 2) * 16 + (l & 3) * 2 + (i & 2) * 4);
          float a0 = 0.f, a1 = 0.f;
#pragma unroll 1
          for (int k = 0; k < DM; k++) {
            const float xv = __bfloat162float(xr[k]);
            const uint32_t wv = wr[k * (HD / 2)];
            a0 = fmaf(xv, bf_lo(wv), a0); a1 = fmaf(xv, bf_hi(wv), a1);
          }
          ((uint32_t*)(qp + (i >> 2) * 32))[i & 3] = pack2(a0, a1);
        }
      }
#pragma unroll
      for (int f = 0; f < 12; f++) { const uint4 t = ldg_rlx128(qp + f * 32); wqt[f][0] = t.x; wqt[f][1] = t.y; wqt[f][2] = t.z; wqt[f][3] = t.w; }
      const float* gp = g_gate + (S_TOK - 128) + G * 64 + w * 16 + ((rF - sb) >> 6);
      wqp[0][0] = ldg_rlx32(gp); wqp[0][1] = ldg_rlx32(gp + 8);
      if (G == 1 && w == 1) {
        mbar_wait(VBAR, (NSEG - 1) & 1);
        if (elect()) {
          asm volatile("mbarrier.arrive.relaxed.cluster.shared::cluster.b64 _, [%0];" ::"r"(mapa(sb + R_EB + 32, r1)) : "memory");
          asm volatile("mbarrier.arrive.relaxed.cluster.shared::cluster.b64 _, [%0];" ::"r"(mapa(sb + R_EB + 32, r2)) : "memory");
          asm volatile("fence.proxy.async.global;" ::: "memory");
#pragma unroll 1
          for (int b = 0; b < 5; b++)
            tma_load2(sb + (b < 3 ? E_KB + b * 10240 : (b == 3 ? E_VB0 : E_VB1)), b < 3 ? &tmK : &tmV, head * DH + (b % 3) * 64, (NSEG - 2) * LK,
                      sb + R_EB + 16 + (b / 3) * 8);
        }
        __syncwarp();
      }
    }
    const uint32_t wqS = rP + R_WQ + G * (20 - NPQ) * 2048, rM = rF + R_MEM;
    const uint32_t l8 = sb + ((rF - sb) >> 1) + w * 256;
    const uint32_t woA = pin(rW_), woB = woA ^ 32;
    float aq[2][4] = {};
    const uint32_t ln = (rF - sb) >> 4;
    const uint32_t rS = sb + (ln & 7) * 128 + (ln < 16 ? R_QB + (ln & 8) * 128 + (((2 * w + G) ^ (ln & 7)) << 4) : R_KT + (((2 * w + ((ln >> 3) & 1)) ^ (ln & 7)) << 4));
    auto qmma = [&](int f, uint32_t b0, uint32_t b1) {
      if (f < NPQ) mma16816(aq[f & 1], wqp[f], b0, b1);
      else {
        const int slot = (f - NPQ) % NQ;
        mma16816(aq[f & 1], wqt[slot], b0, b1);
        if (f + NQ < 20) ldsm4t(wqt[slot], wqS + (f - NPQ + NQ) * 2048);
      }
    };
    if constexpr (G == 1) {
      uint32_t bb[20][4];
      if (!LAST) {
        ldsm4t(bb[10], rM + 5120);
        ldsm4t(bb[11], rM + 5632);
#pragma unroll
        for (int i = 10; i < 20; i++) {
          if (i + 2 < 20) ldsm4t(bb[i + 2], rM + (i + 2) * 512);
          qmma(2 * i - 20, bb[i][0], bb[i][1]);
          qmma(2 * i - 19, bb[i][2], bb[i][3]);
        }
        stsm2t(rS, pack2(aq[0][0] + aq[1][0], aq[0][1] + aq[1][1]), pack2(aq[0][2] + aq[1][2], aq[0][3] + aq[1][3]));
        bar_arrive(1, 256);
      }
      TR(2);
      float av[4][4] = {};
      uint32_t m0 = 0, m1 = 0;
      auto vmma = [&](auto MAX_) {
#pragma unroll
        for (int n = 0; n < 20; n++) {
          const int i = (n + 10) % 20;
          if (LAST && n < 8) ldsm4t(bb[(n + 10) % 20], rM + ((n + 10) % 20) * 512);
          if (LAST && n == 0) { ldsm4t(bb[18], rM + 18 * 512); ldsm4t(bb[19], rM + 19 * 512); }
          if (n == VB && !LAST) { bar_sync(5, 256); sched_fence(sb); }
          if (n == VLD) {
            if (VB != VLD && !LAST) sched_fence(sb);
#pragma unroll
            for (int q = 0; q < 10; q++) ldsm4t(bb[q], rM + q * 512);
            if (!LAST) sched_fence(sb);
          }
          mma16816(av[(2 * n) & 3], ww[2 * i], bb[i][0], bb[i][1]);
          mma16816(av[(2 * n + 1) & 3], ww[2 * i + 1], bb[i][2], bb[i][3]);
          if (decltype(MAX_)::value) { m0 = hmaxabs2(m0, hmaxabs2(bb[i][0], bb[i][1])); m1 = hmaxabs2(m1, hmaxabs2(bb[i][2], bb[i][3])); }
        }
      };
      auto vout = [&]() {
        const uint32_t vm0 = pack2(((av[0][0] + av[1][0]) + (av[2][0] + av[3][0])) * u, ((av[0][1] + av[1][1]) + (av[2][1] + av[3][1])) * u);
        const uint32_t vm1 = pack2(((av[0][2] + av[1][2]) + (av[2][2] + av[3][2])) * u, ((av[0][3] + av[1][3]) + (av[2][3] + av[3][3])) * u);
        if (!LAST) {
          st_async2(mapa(l8 + R_VM + 1024, r1), vm0, vm1, mapa(OBAR, r1));
          st_async2(mapa(l8 + R_VM, r2), vm0, vm1, mapa(OBAR, r2));
          sts64(l8 + R_VS, vm0, vm1);
          __syncwarp();
          if (rF == sb) mbar_arrive(OBAR);
        }
        stsm2t(rP + R_VT, vm0, vm1);
      };
      if (LAST) {
        vmma(std::false_type{});
        vout();
        return;
      }
      uint32_t wot[NW1][4];
      auto wpre = [&](int i0, int i1) {
#pragma unroll
        for (int i = i0; i < i1; i++) ldsm4t(wot[i], ((i & 1) ? woB : woA) + WOFF(i >> 1));
      };
      if (w != 1) {
        vmma(std::false_type{});
        bar_arrive(7, 128);
        vout();
        bar_arrive(2, 128);
        TR(5);
        wpre(0, NW1A);
      } else {
        vmma(std::true_type{});
        bar_sync(7, 128);
        if (elect()) { mbar_expect(XBAR, 40960); tma_load3(sb + R_XT, &tmX, 0, (s + 1) * SEG, 0, XBAR); }
        __syncwarp();
        vout();
        if (XPF && s + XPF < NSEG && rF - sb < 64 && cta < 80) prefetch_l2(x + (size_t)(s + XPF) * SEG * DM + cta * 256 + (rF - sb) * 4);
        TR(5);
        m0 = hmaxabs2(m0, m1);
        const uint32_t mx = __reduce_max_sync(~0u, max((m0 << 16) & 0x7fffffffu, m0 & 0x7fff0000u));
        const float2 mi = lds64f(sb + R_MI + 8);
        wpre(0, NW1A);
        bar_sync(2, 128);
        if (elect()) {
          fence_async_smem();
          tma_store2(&tmK, sb + R_KT, D0, s * LK);
          tma_store2(&tmV, sb + R_VT, D0, s * LK);
          bulk_commit();
        }
        __syncwarp();
        float wb = mi.x, xm = mi.y;
        if (s == 0) {
          const uint32_t epoch = lds32(sb + R_MI);
          uint32_t av_ = 0, ao = 0, xi = 0;
#pragma unroll 1
          for (int j = 0; j < 3; j++) {
            uint2 r;
            int n = 0;
#pragma unroll 1
            while (true) {
              r = ldg_rlx64(&g_rec[j * 32 + ((rF - sb) >> 4)]);
              if (((r.x ^ epoch) & 0xffffu) == 0) break;
              if (++n > SPIN_MAX) { g_err = 6; break; }
            }
            av_ = max(av_, r.y & 0xffff0000u); ao = max(ao, r.y << 16); xi = max(xi, r.x & 0xffff0000u);
          }
          av_ = __reduce_max_sync(~0u, av_); ao = __reduce_max_sync(~0u, ao); xi = __reduce_max_sync(~0u, xi);
          wb = __uint_as_float(av_) * __uint_as_float(ao) * 33.f; xm = __uint_as_float(xi);
          if (rF == sb) {
            sts64f(sb + R_MI + 8, wb, xm);
            asm volatile("fence.acq_rel.gpu;\nred.relaxed.gpu.global.add.u32 [%0], 1;" ::"l"(&g_cnt[C_GATE * 8]) : "memory");
          }
          __syncwarp();
        }
        const float hm = fmaxf(__uint_as_float(mx) * u, xm);
        const uint32_t eb = min(max(__float_as_uint(hm * wb) >> 23, 40u), 200u);
        if (rF == sb) sts64(sb + R_MI + 48, (280u - eb) << 23, (eb - 29u) << 23);
        if (elect()) bulk_wait_read0();
        __syncwarp();
      }
      if (NW1A < NW1) {
        bar_sync(4, 256);
        wpre(NW1A, NW1);
      }
      TR(6);
      oproj(std::true_type{}, std::integral_constant<int, NW1>{}, wot, rF, woA, woB, 0.f, 0.f, false);
    } else {
      {
        uint32_t bb[20][4];
        float ak[4][4] = {};
        ldsm4t(bb[0], rM);
        ldsm4t(bb[10], rM + 5120);
#pragma unroll
        for (int i = 0; i < 10; i++) {
          if (i + 1 < 10) { ldsm4t(bb[i + 1], rM + (i + 1) * 512); ldsm4t(bb[i + 11], rM + (i + 11) * 512); }
          mma16816(ak[0], ww[2 * i], bb[i][0], bb[i][1]);
          if (!LAST) qmma(2 * i, bb[i][0], bb[i][1]);
          mma16816(ak[1], ww[2 * i + 1], bb[i][2], bb[i][3]);
          if (!LAST) qmma(2 * i + 1, bb[i][2], bb[i][3]);
          mma16816(ak[2], ww[2 * i + 20], bb[i + 10][0], bb[i + 10][1]);
          mma16816(ak[3], ww[2 * i + 21], bb[i + 10][2], bb[i + 10][3]);
        }
#pragma unroll
        for (int q = 0; q < 4; q++) { ak[0][q] += ak[2][q]; ak[1][q] += ak[3][q]; }
        stsm4t(rS, pack2(aq[0][0] + aq[1][0], aq[0][1] + aq[1][1]), pack2(aq[0][2] + aq[1][2], aq[0][3] + aq[1][3]),
               pack2((ak[0][0] + ak[1][0]) * u, (ak[0][1] + ak[1][1]) * u), pack2((ak[0][2] + ak[1][2]) * u, (ak[0][3] + ak[1][3]) * u));
      }
      if (LAST) return;
      bar_sync(1, 256);
      bar_arrive(5, 256);
      TR(2);
      if (w != 3) {
        uint32_t qa[4][4], kk[4][4];
        float x[4][4] = {};
#pragma unroll
        for (int i = 0; i < 4; i++) { ldsm4(qa[i], (rP ^ (i << 5)) + R_QB); ldsm4(kk[i], ((rP ^ (i << 5)) + w * 2048) + R_KT); }
        const uint32_t dst = rF + R_SX + rank * 1536 + w * 512;
        const uint32_t e1 = mapa(dst, r1), e2 = mapa(dst, r2), s1 = mapa(SBAR, r1), s2 = mapa(SBAR, r2);
#pragma unroll
        for (int i = 0; i < 4; i++) { mma16816(x[i & 1], qa[i], kk[i][0], kk[i][1]); mma16816(x[2 + (i & 1)], qa[i], kk[i][2], kk[i][3]); }
        const uint32_t u0 = __float_as_uint((x[0][0] + x[0][2]) + (x[1][0] + x[1][2])), u1 = __float_as_uint((x[0][1] + x[0][3]) + (x[1][1] + x[1][3]));
        const uint32_t u2 = __float_as_uint((x[2][0] + x[2][2]) + (x[3][0] + x[3][2])), u3 = __float_as_uint((x[2][1] + x[2][3]) + (x[3][1] + x[3][3]));
        st_async4(e1, u0, u1, u2, u3, s1);
        st_async4(e2, u0, u1, u2, u3, s2);
        sts128(dst, u0, u1, u2, u3);
        __syncwarp();
        if (rF == sb) mbar_arrive(SBAR);
      } else if (s == NSEG - 2) {
        sts32(sb + R_MI + 4, ldg_rlx32(&g_cnt[(C_O + 240 + (head >> 1)) * 8]) - lds32(sb + R_MI) * 2);
        asm volatile("fence.acquire.gpu; fence.proxy.async.global;" ::: "memory");
        if (elect()) {
#pragma unroll 1
          for (int b = 0; b < 6; b++)
            tma_load2(sb + b * 10240, b < 3 ? &tmK : &tmV, head * DH + (b % 3) * 64, (NSEG - 4) * LK, sb + R_EB + (b / 3) * 8);
        }
        __syncwarp();
      }
      TR(4);
      mbar_wait(VBAR, s & 1);
      uint32_t wot[12][4], va[3][8];
      ldsm4t(va[0], rP + R_VT + 1024); ldsm4t(va[0] + 4, rP + R_VT + 3072);
#pragma unroll
      for (int q = 0; q < 4; q++) ldsm4t(va[1 + (q >> 1)] + (q & 1) * 4, rP + R_V1 + q * 2048);
      auto wpre = [&](int i0, int i1) {
        if (two) {
#pragma unroll
          for (int i = i0; i < i1; i++) ldsm4t(wot[i], ((i & 1) ? woB : woA) + WOFF(i >> 1));
        } else {
#pragma unroll
          for (int i = i0; i < i1; i++) ldsm4t(wot[i], woA + WOFF(i));
        }
      };
      wpre(0, NO_EARLY);
      const uint32_t dst = rF + (w >> 1) * 512 + (w & 1) * 8;
      const float scl = u * (0.07216878364870322f * 1.4426950408889634f);
      mbar_wait(SBAR, s & 1);
      TR(6);
      float sc[10];
      {
        const float4 a0 = lds128f(rF + R_SX), b0 = lds128f(rF + R_SX + 1536), c0 = lds128f(rF + R_SX + 3072);
        const float4 a1 = lds128f(rF + R_SX + 512), b1 = lds128f(rF + R_SX + 2048), c1 = lds128f(rF + R_SX + 3584);
        const float2 a2 = lds64f(rF + R_SX + 1024), b2 = lds64f(rF + R_SX + 2560), c2 = lds64f(rF + R_SX + 4096);
        sc[8] = a0.x + b0.x + c0.x; sc[9] = a0.y + b0.y + c0.y; sc[0] = a0.z + b0.z + c0.z; sc[1] = a0.w + b0.w + c0.w;
        sc[2] = a1.x + b1.x + c1.x; sc[3] = a1.y + b1.y + c1.y; sc[4] = a1.z + b1.z + c1.z; sc[5] = a1.w + b1.w + c1.w;
        sc[6] = a2.x + b2.x + c2.x; sc[7] = a2.y + b2.y + c2.y;
      }
      float mx = fmaxf(fmaxf(fmaxf(sc[0], sc[1]), fmaxf(sc[2], sc[3])), fmaxf(fmaxf(sc[4], sc[5]), fmaxf(sc[6], sc[7])));
      mx = fmaxf(mx, fmaxf(sc[8], sc[9]));
      mx = fmaxf(mx, __shfl_xor_sync(~0u, mx, 1));
      const bool vok = mbar_test(OBAR, s & 1);
      mx = fmaxf(mx, __shfl_xor_sync(~0u, mx, 2));
      if (NW1A < NW1) bar_arrive(4, 256);
      const float mo = mx * scl;
      uint32_t pb[5];
#pragma unroll
      for (int j = 0; j < 5; j++) pb[j] = pack2(ex2(fmaf(sc[2 * j], scl, -mo)), ex2(fmaf(sc[2 * j + 1], scl, -mo)));
      if (!vok) mbar_wait(OBAR, s & 1);
      const uint2 m0 = lds64(l8 + R_VS), m1 = lds64(l8 + R_VM), m2 = lds64(l8 + R_VM + 1024);
      const uint32_t ones[4] = {ONES, ONES, ONES, ONES};
      float o[3][4], o2[3][4], sm[4] = {0.f, 0.f, 0.f, 0.f}, sn[4] = {0.f, 0.f, 0.f, 0.f}, so[4] = {0.f, 0.f, 0.f, 0.f};
#pragma unroll
      for (int b = 0; b < 3; b++) {
        o[b][0] = o[b][1] = o[b][2] = o[b][3] = o2[b][0] = o2[b][1] = o2[b][2] = o2[b][3] = 0.f;
        mma16816(o[b], va[b], pb[0], pb[1]);
      }
#pragma unroll
      for (int b = 0; b < 3; b++) mma16816(o2[b], va[b] + 4, pb[2], pb[3]);
      mma1688(o[0], m0.x, m0.y, pb[4]);
      mma1688(o[1], m1.x, m1.y, pb[4]);
      mma1688(o[2], m2.x, m2.y, pb[4]);
      mma16816(sm, ones, pb[0], pb[1]);
      mma16816(sn, ones, pb[2], pb[3]);
      mma1688(so, ONES, ONES, pb[4]);
      wpre(NO_EARLY, NO_MID);
#pragma unroll
      for (int b = 0; b < 3; b++)
        sts64(dst + (b == 0 ? R_QB : (b == 1 ? R_QA : R_O2)), movmat(pack2(o[b][0] + o2[b][0], o[b][1] + o2[b][1])),
              movmat(pack2(o[b][2] + o2[b][2], o[b][3] + o2[b][3])));
      sm[0] += sn[0] + so[0]; sm[1] += sn[1] + so[1];
      if (rF - sb < 64) sts64f(sb + R_MI + 16 + ((rF - sb) >> 1), sm[0], sm[1]);
      wpre(NO_MID, 12);
      TR(7);
      if (two) oproj(std::true_type{}, std::integral_constant<int, 12>{}, wot, rF, woA, woB, sm[0], sm[1], true);
      else oproj(std::false_type{}, std::integral_constant<int, 12>{}, wot, rF, woA, woB, sm[0], sm[1], true);
    }
  };

  if (g == 0) {
    window(std::integral_constant<int, 0>{}, std::integral_constant<int, 0>{});
    GTR(7);
#pragma unroll 1
    for (s = 0; s < NSEG - 1; s++) {
      step(std::integral_constant<int, 0>{}, std::false_type{});
      window(std::integral_constant<int, 0>{}, std::integral_constant<int, 1>{});
    }
    step(std::integral_constant<int, 0>{}, std::true_type{});
  } else {
    window(std::integral_constant<int, 1>{}, std::integral_constant<int, 0>{});
#pragma unroll 1
    for (s = 0; s < NSEG - 1; s++) {
      step(std::integral_constant<int, 1>{}, std::false_type{});
      window(std::integral_constant<int, 1>{}, std::integral_constant<int, 1>{});
    }
    step(std::integral_constant<int, 1>{}, std::true_type{});
  }
  fence_async_smem();
  __syncthreads();
  GTR(8);
#define CG(i) do {} while (0)
  if (wid == 5) {
    if (elect()) {
      const uint32_t kd = sb + E_KB + rank * 10240 + 5120, vd = sb + (rank == 0 ? E_VB0 : (rank == 1 ? E_VB1 : E_VB2)) + 5120;
      if (rank != 2) asm volatile("mbarrier.arrive.relaxed.cluster.shared::cluster.b64 _, [%0];" ::"r"(mapa(sb + R_EB + 40, 2)) : "memory");
      mbar_wait(sb + R_EB + 32, 0);
#pragma unroll 1
      for (uint32_t r = 0; r < 3; r++) bulk_s2s(mapa(kd, r), sb + R_KT, 5120, mapa(sb + R_EB + 16, r));
      tma_load2(sb + E_VB2, &tmV, head * DH + 128, (NSEG - 2) * LK, sb + R_EB + 24);
      if (rank == 2) mbar_wait(sb + R_EB + 40, 0);
#pragma unroll 1
      for (uint32_t r = 0; r < 3; r++) bulk_s2s(mapa(vd, r), sb + R_VT, 5120, mapa(sb + R_EB + 24, r));
      asm volatile("red.relaxed.gpu.global.add.u32 [%0], 1;" ::"l"(&g_prog) : "memory");
    }
    __syncwarp();
  }
  {
    const uint32_t kb = sb + (g ? E_KB : E_KA);
    float sc[40] = {};
    uint32_t pf[5][4];
    mbar_wait(sb + R_EB + g * 16, 0);
    CG(11);
    wg_fence();
#pragma unroll
    for (int ks = 0; ks < 12; ks++) wgmma_rs80(sc, wqt[ks], mk_desc(kb, 16, 1024, 1) + (((ks >> 2) * 10240 + (ks & 3) * 32) >> 4), ks);
    wg_commit();
    const AttMask am(tid, sb);
    wg_wait0();
    fence_regs<40>(sc);
    CG(12);
    att_softmax(am, sc, pf, __uint_as_float(wqp[0][0]), __uint_as_float(wqp[0][1]));
    float o[96] = {};
    mbar_wait(sb + R_EB + g * 16 + 8, 0);
    CG(13);
    wg_fence();
#pragma unroll
    for (int b = 0; b < 3; b++) {
      const Desc db = mk_desc(sb + (g ? (b == 0 ? E_VB0 : (b == 1 ? E_VB1 : E_VB2)) : E_VA + b * 10240), 1024, 1024, 1);
#pragma unroll
      for (int ks = 0; ks < 5; ks++) wgmma_rs64t(o + 32 * b, pf[ks], db + ks * 128, ks);
    }
    wg_commit();
    wg_wait0();
    fence_regs<96>(o);
    CG(14);
    uint32_t of[12][4];
#pragma unroll
    for (int i = 0; i < 48; i++) asm volatile("cvt.rn.bf16x2.f32 %0, %1, %2;" : "=r"(of[i >> 2][i & 3]) : "f"(o[2 * i + 1]), "f"(o[2 * i]));
    float y[112] = {};
    wg_fence();
#pragma unroll
    for (int j = 0; j < 3; j++) {
      const Desc db = mk_desc((sb & 0x3ffff) + R_WO + ((j + 3 - rank) % 3) * 28672, 4096, 512, 2);
#pragma unroll
      for (int ks = 0; ks < 4; ks++) wgmma_rs224t(y, of[4 * j + ks], db + ks * 64, j + ks);
    }
    wg_commit();
    wg_wait0();
    fence_regs<112>(y);
    CG(15);
    const uint32_t da = kb + (w * 16 + (lane & 15)) * 64, sx = (lane >> 1) & 3;
#pragma unroll
    for (int i = 0; i < 14; i++)
      stsm4(da + (i >> 1) * 4096 + (((2 * (i & 1) + (lane >> 4)) ^ sx) << 4), pack2(y[8 * i], y[8 * i + 1]), pack2(y[8 * i + 2], y[8 * i + 3]),
            pack2(y[8 * i + 4], y[8 * i + 5]), pack2(y[8 * i + 6], y[8 * i + 7]));
    fence_async_smem();
    bar_sync(1 + g, 128);
    if (w == 0 && elect()) {
#pragma unroll 1
      for (int i = 0; i < (rank == 1 ? 6 : 7); i++) tma_red2(&tmOut, kb + i * 4096, tile0 * 16 + i * 32, S_TOK - 128 + g * 64);
      bulk_commit();
      bulk_wait0();
    }
  }
  GTR(9);
}

enum { IT_QKV = 1, IT_XATT = 2, IT_OUT = 3, IT_BATT = 4, IT_Q = 5, IT_INIT = 6, IT_END = 7 };
constexpr uint32_t NONE = ~0u;
#define HP 0x1224468888888888ull
#define XD 0x4888888888888999ull
#define KREQ 5
#define ADELAY 7000
#define W_PRO 11
#define W_SCH 8
#define W_AG1 10
#define CVTS 6
#define RSL 20
#define PACE 500
#define XPP 22
#define PP 3
__host__ __device__ constexpr uint32_t mk_item(int ty, int t, int a, int b = 0, int c = 0) { return ty | (t << 3) | (a << 8) | (b << 16) | (c << 24); }
struct ItemTab { uint32_t v[1280]; int n; };
constexpr ItemTab make_items() {
  ItemTab T{};
  int n = 0;
  for (int a = 0; a < 16; a++) T.v[n++] = mk_item(IT_Q, 15, a);
  for (int t = 0; t < 16; t++) for (int a = 0; a < 5; a++) T.v[n++] = mk_item(IT_QKV, t, a);
  for (int t = 0; t < 32; t++) T.v[n++] = mk_item(IT_BATT, t, 0);
  for (int t = 0; t < 16; t++) for (int a = 0; a < 2; a++) T.v[n++] = mk_item(IT_INIT, t, a);
#define NOOUT 15
  for (int t = 0; t < NOOUT; t++) {
    const int hp = (HP >> 4 * t) & 15;
    for (int h = 0; h < 32; h += hp) for (int a = 0; a < 2; a++) T.v[n++] = mk_item(IT_OUT, t, a, h, h + hp < 32 ? h + hp : 32);
  }
  T.n = n;
  return T;
}
constexpr ItemTab k_items_host = make_items();
constexpr int NITEMS = k_items_host.n;
__constant__ ItemTab c_items = make_items();

constexpr int NST = 7, STG = 32768;
constexpr int A_FULL = NST * STG, A_EMPTY = A_FULL + 64, A_ITEM = A_EMPTY + 64, A_QBAR = A_ITEM + 32, A_QENT = A_QBAR + 128, A_MISC = A_QENT + 256,
              A_SMEM = A_MISC + 64, A_REQ = A_FULL + 56, A_RSP = A_EMPTY + 56, A_MAIL = A_MISC + 48, A_RDY = A_MISC + 32;
static_assert(A_SMEM <= 232448, "smem");
enum { OP_END = 0, OP_O = 1, OP_QKV = 2, OP_OB = 3, OP_SET = 4, OP_ADD = 5, OP_Q = 6 };

struct AuxMaps { CUtensorMap xA, wq, wqkv, wo, wob, k, v, oA, oS, obA, obS, qkvS, qkvQ, qkvK, out; };

__device__ __forceinline__ void mbar_wait_long(uint32_t b, uint32_t par) {
  int n = 0;
#pragma unroll 1
  while (!mbar_try(b, par)) { if (++n > (SPIN_MAX << 4)) { g_err = 8; break; } }
}
__device__ __forceinline__ void mbar_wait_u(uint32_t b, uint32_t par) {
  asm volatile("{.reg .pred p; .reg .u32 n;\nmov.u32 n, 0;\nLW: mbarrier.try_wait.parity.shared::cta.b64 p, [%0], %1;\n@p bra.uni LD;\n"
               "add.u32 n, n, 1;\nsetp.lt.u32 p, n, %2;\n@p bra.uni LW;\nLD:\n}" ::"r"(b), "r"(par), "n"(SPIN_MAX << 4) : "memory");
}
__global__ void __launch_bounds__(384, 1)
aux_kernel(const __grid_constant__ AuxMaps tm) {
  extern __shared__ __align__(1024) unsigned char smem[];
  const uint32_t sb = smem_u32(smem);
  const int tid = threadIdx.x, lane = tid & 31, wid = __shfl_sync(~0u, tid >> 5, 0);
  uint32_t epoch = 0;
  const uint32_t c0 = clk32();
  if (tid == W_SCH * 32) GTA(0);
  if (tid >= 256) epoch = *(volatile uint32_t*)&g_epoch + 1;
  if (tid == 0) {
    mbar_init(sb + A_REQ, 1); mbar_init(sb + A_RSP, 1); mbar_init(sb + A_RDY, 1);
    for (int i = 0; i < NST; i++) { mbar_init(sb + A_FULL + i * 8, 1); mbar_init(sb + A_EMPTY + i * 8, 8); }
    for (int i = 0; i < 16; i++) mbar_init(sb + A_QBAR + i * 8, 4);
    asm volatile("fence.mbarrier_init.release.cluster;" ::: "memory");
    const uint32_t b = blockIdx.x;
    sts128(sb + A_MAIL, b < 16 ? mk_item(IT_Q, 15, b) : mk_item(IT_QKV, (b - 16) / 5, (b - 16) % 5), 1, b, PACE);
    mbar_arrive(sb + A_RSP);
  }
  if (tid < 15) prefetch_map(&tm.xA + tid);
  if (tid == W_SCH * 32) GTA(4);
  __syncthreads();
  if (tid == W_SCH * 32) GTA(5);
  uint32_t st = 0, ph = 0;
  auto advance = [&]() { if (++st == NST) { st = 0; ph ^= 1; } };

  if (wid >= 8) {
    asm volatile("setmaxnreg.dec.sync.aligned.u32 40;");
    if (tid == W_SCH * 32) GTA(6);
    auto cnt = [&](int c, uint32_t per) -> bool { return (int)(ldg_rlx32(&g_cnt[c * 8]) - epoch * per) >= 0; };
    auto ready = [&](uint32_t item, int known) -> int {
      const int ty = known == 7 ? item & 7 : known, t = (item >> 3) & 31, b = (item >> 17) & 127, n = (((item >> 24) + 1) >> 1) - b;
      int r;
      if (ty == IT_OUT) {
        const int c = C_O + t * 16 + b;
        const bool r0 = cnt(c, 2), r1 = cnt(c + (n > 1), 2), r2 = cnt(c + (n > 2) * 2, 2), r3 = cnt(c + (n > 3) * 3, 2);
        r = r0 & cnt(C_ACC + t, 4) ? (r1 ? (r2 ? (r3 ? 4 : 3) : 2) : 1) : 0;
      } else if (known == IT_XATT) {
        const uint4 v = ldg_rlx128(&g_segcnt[4 * t]);
        const uint32_t e = epoch * 96;
        r = ((int)(v.x - e) >= 0) & ((int)(v.y - e) >= 0) & ((int)(v.z - e) >= 0) & ((int)(v.w - e) >= 0);
      } else if (ty == IT_BATT) {
        r = cnt(C_GATE, NGATE) & cnt(C_QKV + (t >> 1), 10) & cnt(C_QKV + (max(t - 1, 0) >> 1), 10);
      } else {
        r = ty == IT_QKV || ty == IT_Q || cnt(C_OB + t, 8);
      }
      asm volatile("fence.acquire.gpu; fence.proxy.async.global;" ::: "memory");
      return r;
    };
    if (wid == W_SCH && lane == 0) {
      uint32_t pend = NONE;
      bool xleft = true;
      uint32_t nidx = 0, pidx = 0;
#pragma unroll 1
      for (uint32_t e = 1;; e++) {
        mbar_wait_long(sb + A_REQ, (e - 1) & 1);
        uint32_t item = NONE;
        int rdy = 0, spins = 0;
#pragma unroll 1
        while (true) {
          const bool fresh = pend == NONE;
          uint4 c;
          uint32_t pr = 0;
          bool gates = false;
          if (xleft) {
            c = ldg_rlx128(&g_queue[0]);
            pr = ldg_rlx32(&g_prog) - (epoch - 1) * (96 * NSEG);
            gates = cnt(C_GATE, NGATE);
          }
          auto need = [&](uint32_t it) { return (it & 7) == IT_OUT && xleft ? (((it >> 24) + 1) >> 1) - ((it >> 17) & 127) : 1; };
          if (!fresh) rdy = ready(pend, 7);
          if (xleft && (fresh || pend == IT_END || rdy < need(pend))) {
            auto full = [](uint32_t v) { v = (v | (v >> 2)) & 0x30303030u; return __popc((v | (v >> 1)) & 0x10101010u); };
            const int t = full(c.x) + full(c.y) + full(c.z) + full(c.w);
            xleft = t < 15;
            if (xleft && gates && (int)pr >= 96 * (4 * t - 8 + (int)((XD >> 4 * t) & 15))) {
              const uint32_t j = (atomicAdd(&g_queue[t >> 2], 1u << (t & 3) * 8) >> (t & 3) * 8) & 255;
              if (j < 16) { item = mk_item(IT_XATT, t, j); rdy = 0; nidx = NITEMS + 132 + t * 16 + j; }
            }
          }
          if (item == NONE && fresh) {
            pidx = atomicAdd(&g_queue[32], 1u) + gridDim.x;
            pend = pidx < (uint32_t)NITEMS ? c_items.v[pidx] : (uint32_t)IT_END;
            continue;
          }
          if (item == NONE && (pend == IT_END ? !xleft : rdy >= need(pend))) { item = pend; pend = NONE; nidx = pidx; }
          if (item != NONE) break;
          if (++spins > SPIN_MAX) { g_err = 10; item = IT_END; break; }
          __nanosleep(50);
        }
        sts128(sb + A_MAIL, item, rdy, nidx, xleft ? PACE : 0);
        mbar_arrive(sb + A_RSP);
        if (item == IT_END) break;
        if ((item & 7) == IT_XATT) {
#pragma unroll 1
          for (spins = 0; !ready(item, IT_XATT); __nanosleep(RSL))
            if (++spins > SPIN_MAX) { g_err = 11; break; }
          mbar_arrive(sb + A_RDY);
        }
      }
      if (atomicAdd(&g_queue[64], 1u) == gridDim.x - 1) { *(uint4*)g_queue = make_uint4(0, 0, 0, 0); g_queue[32] = 0; g_queue[64] = 0; g_epoch = epoch; }
      asm volatile("griddepcontrol.wait;" ::: "memory");
    } else if (wid == W_PRO) {
      uint32_t xph = 0, tl = c0;
      int pace = 0;
      if (ADELAY) spin_until(c0, ADELAY);
      auto arm = [&](uint32_t bytes) -> uint32_t {
        mbar_wait_u(sb + A_EMPTY + st * 8, ph ^ 1);
        if (PACE && bytes) { spin_until(tl, pace); tl = clk32(); }
        return sb + st * STG;
      };
#pragma unroll 1
      for (uint32_t e = 0;; e++) {
        mbar_wait_long(sb + A_RSP, e & 1);
        const uint4 mail = lds128(sb + A_MAIL);
        asm volatile("fence.proxy.async.global;" ::: "memory");
        const uint32_t item = __shfl_sync(~0u, mail.x, 0);
        pace = mail.w;
        const int ty = item & 7, t = (item >> 3) & 31, a = (item >> 8) & 255;
        arm(0);
        if (elect()) {
          sts32(sb + A_ITEM + st * 4, item);
        }
        if (ty == IT_OUT || ty == IT_INIT) {
          const bool out_ = ty == IT_OUT;
          const CUtensorMap *pa = out_ ? &tm.oA : &tm.obA, *pb = out_ ? &tm.wo : &tm.wob;
          int k = out_ ? ((item >> 16) & 255) * 6 : 0;
          const int k1 = out_ ? (item >> 24) * 6 : 20, kreq = max(k1 - KREQ, k);
          int kdep = out_ ? (((item >> 17) & 127) + __shfl_sync(~0u, mail.y, 0)) * 12 : 20;
#pragma unroll 1
          for (; k < k1; k++) {
            if (k >= kdep) {
              int n = 0;
#pragma unroll 1
              while (k >= (kdep = (((item >> 17) & 127) + __shfl_sync(~0u, ready(item, IT_OUT), 0)) * 12)) {
                if (++n > SPIN_MAX) { g_err = 7; break; }
                __nanosleep(20);
              }
            }
            PTR((item & 255) == PT && lane == 0, 0, k & 63);
            const uint32_t d = arm(1), fb = sb + A_FULL + st * 8;
            PTR((item & 255) == PT && lane == 0, 1, k & 63);
            if (elect()) {
              mbar_expect(fb, 28672);
              tma_load2(d, pa, k * 32, t * 128, fb);
              tma_load3(d + 8192, pb, 0, k * 32, a * 5, fb);
              if (k == kreq) mbar_arrive(sb + A_REQ);
            }
            PTR((item & 255) == PT && lane == 0, 2, k & 63);
            advance();
          }
        } else if (ty == IT_QKV || ty == IT_XATT || ty == IT_Q) {
          const CUtensorMap* pb = ty == IT_QKV ? &tm.wqkv : &tm.wq;
          const int kreq = ty == IT_XATT ? 28 - KREQ : 20 - KREQ;
#pragma unroll 1
          for (int k = 0; k < 20; k++) {
            PTR((item & 255) == PT && lane == 0, 0, k & 63);
            const uint32_t d = arm(1), fb = sb + A_FULL + st * 8;
            PTR((item & 255) == PT && lane == 0, 1, k & 63);
            if (elect()) {
              mbar_expect(fb, 32768);
              tma_load2(d, &tm.xA, k * 32, t * 128, fb);
              tma_load3(d + 8192, pb, 0, k * 32, a * 6, fb);
              if (k == kreq) mbar_arrive(sb + A_REQ);
            }
            PTR((item & 255) == PT && lane == 0, 2, k & 63);
            advance();
          }
          if (ty == IT_XATT) {
            mbar_wait_long(sb + A_RDY, xph);
            xph ^= 1;
            asm volatile("fence.proxy.async.global;" ::: "memory");
#pragma unroll 1
            for (int k = 20; k < 28; k++) {
              PTR((item & 255) == PT && lane == 0, 0, k & 63);
              const uint32_t d = arm(1), fb = sb + A_FULL + st * 8;
              PTR((item & 255) == PT && lane == 0, 1, k & 63);
              if (elect()) {
                mbar_expect(fb, 30720);
                tma_load3(d, k < 24 ? &tm.k : &tm.v, 0, (4 * t + (k & 2)) * LK, (2 * a + (k & 1)) * 3, fb);
                if (k == kreq) mbar_arrive(sb + A_REQ);
              }
              PTR((item & 255) == PT && lane == 0, 2, k & 63);
              advance();
            }
          }
        } else if (ty == IT_BATT) {
#pragma unroll 1
          for (int k = 0, j = 0, c = 0; k < 12; k++) {
            PTR((item & 255) == PT && lane == 0, 0, k & 63);
            const uint32_t d = arm(1), fb = sb + A_FULL + st * 8;
            PTR((item & 255) == PT && lane == 0, 1, k & 63);
            if (elect()) {
              mbar_expect(fb, c ? 25600 : 20480);
              tma_load3(d, c ? &tm.qkvK : &tm.qkvQ, 0, t * 32 - (c ? 8 : 0), (j & 1) * 30 + (j >> 1) * 5 + c, fb);
              if (k == 6) mbar_arrive(sb + A_REQ);
            }
            PTR((item & 255) == PT && lane == 0, 2, k & 63);
            if (c == 20) { c = 0; j++; } else c += 10;
            advance();
          }
        } else {
          if (elect()) { mbar_arrive(sb + A_FULL + st * 8); mbar_arrive(sb + A_REQ); }
          advance();
        }
        if (item == IT_END) break;
        if ((0x6a >> ty) & 1) {
#pragma unroll 1
          for (int k = 0; k < 4; k++) {
            arm(0);
            if (elect()) mbar_arrive(sb + A_FULL + st * 8);
            advance();
          }
        }
      }
    } else if (lane == 0) {
      const uint32_t qb = sb + A_QBAR + (wid == W_AG1) * 64, qe = sb + A_QENT + (wid == W_AG1) * 128;
      for (uint32_t e = 0;; e++) {
        mbar_wait_long(qb + (e & 7) * 8, (e >> 3) & 1);
        const uint4 en = lds128(qe + (e & 7) * 16);
        const int op = en.x & 15, sg = (en.x >> 4) & 15, rel = (en.x >> 8) & 15, nb = (en.x >> 12) & 15;
        if (op == OP_END) break;
        const uint32_t src = sb + sg * STG;
        if (op == OP_OB) tma_store3(&tm.obS, src, 0, en.y, en.z);
        else if (op == OP_Q) asm volatile("cp.async.bulk.global.shared::cta.bulk_group [%0], [%1], 24576;" ::"l"(g_Ql + en.y * 1536), "r"(src) : "memory");
        else {
          const CUtensorMap* pm = op == OP_O ? &tm.oS : (op == OP_QKV ? &tm.qkvS : &tm.out);
#pragma unroll 1
          for (int i = 0; i < nb; i++) {
            if (op == OP_ADD) tma_red3(pm, src + i * 8192, 0, en.y, en.z + i); else tma_store3(pm, src + i * 8192, 0, en.y, en.z + i);
          }
        }
        bulk_commit();
        bulk_wait_read0();
        asm volatile("mbarrier.arrive.shared::cta.b64 _, [%0], %1;" ::"r"(sb + A_EMPTY + sg * 8), "r"(rel) : "memory");
        if (en.w) {
          bulk_wait0();
          asm volatile("red.relaxed.gpu.global.add.u32 [%0], %1;" ::"l"(&g_cnt[(en.w - 1) * 8]), "r"(1) : "memory");
        }
      }
      bulk_wait0();
      if (wid == W_AG1) GTA(7);
    }
  } else {
    asm volatile("setmaxnreg.inc.sync.aligned.u32 232;");
    const int g = wid >> 2, w = wid & 3;
    uint32_t qn = 0;
    auto wait_full = [&]() { mbar_wait_u(sb + A_FULL + st * 8, ph); };
    auto release = [&](uint32_t s_) { if (lane == 0) mbar_arrive(sb + A_EMPTY + s_ * 8); };
    auto take_pair = [&]() -> uint32_t {
      wait_full();
      const uint32_t s0 = st; advance();
      wait_full();
      const uint32_t s1 = st; advance();
      release(g ? s0 : s1);
      return g ? s1 : s0;
    };
    auto push = [&](uint32_t w0, uint32_t w1, uint32_t w2, uint32_t w3) {
      fence_async_smem();
      if (w == 0 && lane == 0) sts128(sb + A_QENT + g * 128 + (qn & 7) * 16, w0, w1, w2, w3);
      __syncwarp();
      if (lane == 0) mbar_arrive(sb + A_QBAR + g * 64 + (qn & 7) * 8);
      qn++;
    };
    const uint32_t stm = (16 * w + (lane & 7) + (lane & 8)) * 128, stx = lane & 7, sth = lane >> 4;
    auto stage_bf16 = [&](uint32_t dst, const float* d, int nks = 12) {
#pragma unroll
      for (int ks = 0; ks < nks; ks++)
        stsm4(dst + (ks >> 2) * 8192 + stm + (((2 * (ks & 3) + sth) ^ stx) << 4), pack2(d[8 * ks], d[8 * ks + 1]), pack2(d[8 * ks + 2], d[8 * ks + 3]),
              pack2(d[8 * ks + 4], d[8 * ks + 5]), pack2(d[8 * ks + 6], d[8 * ks + 7]));
    };
#pragma unroll 1
    while (true) {
      wait_full();
      const uint32_t item = lds32(sb + A_ITEM + st * 4);
      const int ty = item & 7, t = (item >> 3) & 31, a = (item >> 8) & 255;
      if (ty == IT_QKV || ty == IT_XATT || ty == IT_Q) {
        float acc[192] = {};
        uint32_t prev = 0;
#define XG(i) do {} while (0)
#pragma unroll 1
        for (int k = 0; k < 20; k++) {
          if (k) wait_full();
          PTR((item & 255) == PT && tid == 32, 3, k);
          const uint32_t s_ = sb + st * STG;
          const Desc da = mk_desc(s_, 16, 512, 2), db = mk_desc(s_ + 8192 + g * 12288, 4096, 1024, 1);
          wg_fence();
          wgmma_ss192t(acc, da, db, k);
          wgmma_ss192t(acc + 96, da + 256, db, k);
          wgmma_ss192t(acc, da + 2, db + 128, 1);
          wgmma_ss192t(acc + 96, da + 258, db + 128, 1);
          wg_commit();
          if (k) { wg_wait1(); release(prev); }
          prev = st; advance();
        }
        uint32_t kst[2];
        if (ty == IT_XATT) { kst[0] = take_pair(); kst[1] = take_pair(); }
        wg_wait0();
        fence_regs<192>(acc);
        release(prev);
        XG(0);
        if (ty != IT_XATT) {
          const bool frag = ty == IT_Q;
#pragma unroll
          for (int q = 0; q < 2; q++) {
            const uint32_t m = take_pair();
#pragma unroll
            for (int ks = 0; ks < 12; ks++) {
              const float* d = acc + q * 96 + ks * 8;
              const uint32_t p0 = pack2(d[0], d[1]), p1 = pack2(d[2], d[3]), p2 = pack2(d[4], d[5]), p3 = pack2(d[6], d[7]);
              if (frag) sts128(sb + m * STG + (w * 12 + ks) * 512 + lane * 16, p0, p1, p2, p3);
              else stsm4(sb + m * STG + (ks >> 2) * 8192 + stm + (((2 * (ks & 3) + sth) ^ stx) << 4), p0, p1, p2, p3);
            }
            push((frag ? OP_Q : OP_QKV | (3 << 12)) | (m << 4) | (4 << 8), frag ? (2 * a + g) * 2 + q : t * 128 + q * 64, a * 6 + g * 3,
                 q ? (frag ? C_O + 240 + a : C_QKV + t) + 1 : 0);
          }
        } else {
          uint32_t qf[24][4];
          float sc[2][40], gt[4];
#pragma unroll
          for (int q = 0; q < 2; q++) {
#pragma unroll
            for (int ks = 23; ks >= 0; ks--)
#pragma unroll
              for (int j = 0; j < 4; j++)
                if ((ks >= 12 && ks < 12 + CVTS) == (q == 1))
                  asm volatile("cvt.rn.bf16x2.f32 %0, %1, %2;" : "=r"(qf[ks][j]) : "f"(acc[8 * ks + 2 * j + 1]), "f"(acc[8 * ks + 2 * j]));
            if (q == 0) XG(1);
            if (q == 0 && XPP && g == 1) bar_sync(6, 256);
            if (q == 1) {
              const float* gp = g_gate + t * 128 + 16 * w + (lane >> 2);
              gt[0] = ldg_cg(gp); gt[1] = ldg_cg(gp + 8); gt[2] = ldg_cg(gp + 64); gt[3] = ldg_cg(gp + 72);
            }
#pragma unroll
            for (int i = 0; i < 40; i++) sc[q][i] = 0.f;
            const Desc db = mk_desc(sb + kst[q] * STG, 16, 1024, 1);
            wg_fence();
#pragma unroll
            for (int ks = 0; ks < 12; ks++) {
              if (XPP && g == 0 && q * 12 + ks == XPP) bar_arrive(6, 256);
              wgmma_rs80(sc[q], qf[q * 12 + ks], db + (((ks >> 2) * 10240 + (ks & 3) * 32) >> 4), ks);
            }
            wg_commit();
          }
          uint32_t pf[2][5][4];
          const AttMask am(tid, sb);
          wg_wait1();
          fence_regs<40>(sc[0]);
          XG(2);
          release(kst[0]);
          sched_fence(sb);
          att_softmax(am, sc[0], pf[0], gt[0], gt[1]);
          XG(3);
          float o[96] = {};
          auto pv = [&](int q, uint32_t m) {
            const Desc db = mk_desc(sb + m * STG, 10240, 1024, 1);
            wg_fence();
#pragma unroll
            for (int ks = 0; ks < 5; ks++) wgmma_rs192t(o, pf[q][ks], db + ks * 128, ks);
            wg_commit();
          };
          PTR((item & 255) == PT && tid == 32, 3, 24);
          const uint32_t m0 = take_pair();
          PTR((item & 255) == PT && tid == 32, 3, 25);
          pv(0, m0);
          wg_wait1();
          fence_regs<40>(sc[1]);
          release(kst[1]);
          att_softmax(am, sc[1], pf[1], gt[2], gt[3]);
          PTR((item & 255) == PT && tid == 32, 3, 26);
          const uint32_t m1 = take_pair();
          PTR((item & 255) == PT && tid == 32, 3, 27);
          wg_wait0();
          fence_regs<96>(o);
          XG(4);
#pragma unroll
          for (int i = 0; i < 48; i++) asm volatile("cvt.rn.bf16x2.f32 %0, %1, %2;" : "=r"(qf[i >> 2][i & 3]) : "f"(o[2 * i + 1]), "f"(o[2 * i]));
          pv(1, m1);
          bar_sync(1 + g, 128);
#pragma unroll
          for (int ks = 0; ks < 12; ks++)
            stsm4(sb + m0 * STG + (ks >> 2) * 8192 + stm + (((2 * (ks & 3) + sth) ^ stx) << 4), qf[ks][0], qf[ks][1], qf[ks][2], qf[ks][3]);
          push(OP_O | (m0 << 4) | (4 << 8) | (3 << 12), t * 128, a * 6 + g * 3, 0);
          XG(5);
          wg_wait0();
          fence_regs<96>(o);
          XG(6);
          bar_sync(1 + g, 128);
          stage_bf16(sb + m1 * STG, o);
          push(OP_O | (m1 << 4) | (4 << 8) | (3 << 12), t * 128 + 64, a * 6 + g * 3, C_O + t * 16 + a + 1);
          XG(7);
        }
      } else if (ty == IT_OUT || ty == IT_INIT) {
        float acc[160] = {};
        const int hb = (item >> 16) & 255, nh = (item >> 24) - hb, nk = ty == IT_OUT ? nh * 6 : 20, jh = a & 1;
        const uint32_t ln = pin(lane), ao = (g * 64 + 16 * w + (ln & 15)) * 64 + (((ln >> 4) ^ ((ln >> 1) & 3)) << 4);
        if (PP && g == 1) bar_arrive(4, 256);
#pragma unroll 1
        for (int k = 0; k < nk; k += 2) {
          uint32_t af[4][4], sg[2];
#pragma unroll
          for (int e = 0; e < 2; e++) {
            if (k + e) wait_full();
            sg[e] = st;
            ldsm4(af[2 * e], sb + st * STG + ao);
            ldsm4(af[2 * e + 1], sb + st * STG + (ao ^ 32));
            advance();
          }
          if (PP) bar_sync(4 + g, 256);
          wg_fence();
#pragma unroll
          for (int e = 0; e < 4; e++) {
            const Desc db = mk_desc(sb + sg[e >> 1] * STG + 8192 + (e & 1) * 2048, 4096, 1024, 1);
            if (PP == 2 && e == 3 && (g == 0 || k + 2 < nk)) bar_arrive(5 - g, 256);
            wgmma_rs192t(acc, af[e], db, 1);
            if (PP == 3 && e == 3 && (g == 0 || k + 2 < nk)) bar_arrive(5 - g, 256);
            wgmma_rs128t(acc + 96, af[e], db + 768, 1);
          }
          wg_commit();
          if (PP == 1 && (g == 0 || k + 2 < nk)) bar_arrive(5 - g, 256);
          wg_wait0();
          release(sg[0]); release(sg[1]);
        }
        fence_regs<160>(acc);
        const uint32_t row = t * 128 + g * 64;
#pragma unroll
        for (int q = 0; q < 2; q++) {
          const uint32_t m = take_pair();
          stage_bf16(sb + m * STG, acc + q * 96, q ? 8 : 12);
          push((ty == IT_OUT || t == 15 ? OP_ADD : OP_SET) | (m << 4) | (4 << 8) | ((3 - q) << 12), row, jh * 5 + q * 3, q && ty == IT_INIT ? C_ACC + t + 1 : 0);
        }
      } else if (ty == IT_BATT) {
        const int ln = pin(lane);
        const int q4 = ln & 3, r8 = ln >> 2;
        const bool lo = q4 < 2, m0 = 2 * q4 > r8, m1 = 2 * q4 + 1 > r8;
        const uint32_t mk = (m0 ? 0xffffu : 0u) | (m1 ? 0xffff0000u : 0u);
        uint32_t aq[5], ak[5];
#pragma unroll
        for (int i = 0; i < 5; i++) {
          const int c = 5 * wid + i;
          aq[i] = (c >> 3) * 4096 + ln * 128 + (((c ^ ln) & 7) << 4);
          ak[i] = aq[i] + (c >> 3) * 1024;
        }
        const int c4 = 5 * wid + min(ln >> 3, 2), c5 = 5 * wid + (ln < 16 ? 3 + (ln >> 3) : 2);
        const uint32_t ak4 = (c4 >> 3) * 5120 + (32 + (ln & 7)) * 128 + (((c4 ^ ln) & 7) << 4), ak5 = (c5 >> 3) * 5120 + (32 + (ln & 7)) * 128 + (((c5 ^ ln) & 7) << 4);
#pragma unroll 1
        for (int j = 0; j < 4; j++) {
          float gt[4];
#pragma unroll
          for (int i = 0; i < 4; i++) gt[i] = ldg_cg(g_gate + S_TOK + t * 64 + (j & 1) + 2 * r8 + i * 16);
          if (j) wait_full();
          PTR((item & 255) == PT && tid == 32, 3, j * 3);
          const uint32_t sq = st; advance();
          wait_full();
          const uint32_t sk = st; advance();
          wait_full();
          const uint32_t sv = st; advance();
          uint32_t q2[4], y2[4];
          ldsm4(q2, sb + sq * STG + aq[2]);
#pragma unroll 1
          for (int h = 0; h < 2; h++) {
            uint32_t qf[2][4], kf[4][4], vf[4][4], pa[2], pb[2];
            float sc[2][3][4] = {}, o[2][3][4] = {}, l[2][4], xa[2], xb[2];
            const uint32_t a0 = h ? aq[3] : aq[0], a1 = h ? aq[4] : aq[1], b0 = h ? ak[3] : ak[0], b1 = h ? ak[4] : ak[1], b4 = h ? ak5 : ak4;
            const bool own = lo == (h == 0);
            ldsm4(qf[0], sb + sq * STG + a0); ldsm4(qf[1], sb + sq * STG + a1);
            ldsm4(kf[0], sb + sk * STG + b0); ldsm4(kf[1], sb + sk * STG + b1); ldsm4(kf[2], sb + sk * STG + ak[2]); ldsm4(kf[3], sb + sk * STG + b4);
            ldsm4t(vf[0], sb + sv * STG + b0); ldsm4t(vf[1], sb + sv * STG + b1); ldsm4t(vf[2], sb + sv * STG + ak[2]); ldsm4t(vf[3], sb + sv * STG + b4);
            auto frag = [](uint32_t (*f)[4], int c, int n) { return n < 4 ? f[c][n] : f[3][c]; };
#pragma unroll
            for (int b = 0; b < 2; b++) {
              const uint32_t x[4] = {qf[0][2 * b], qf[0][2 * b + 1], qf[1][2 * b], qf[1][2 * b + 1]};
#pragma unroll
              for (int n = 0; n < 3; n++) mma16816(sc[b][n], x, frag(kf, 0, 2 * b + n), frag(kf, 1, 2 * b + n));
            }
#pragma unroll
            for (int b = 0; b < 2; b++)
#pragma unroll
              for (int n = 0; n < 3; n++) mma1688(sc[b][n], own ? q2[2 * b] : 0u, own ? q2[2 * b + 1] : 0u, frag(kf, 2, 2 * b + n));
            if (t == 0) sc[0][0][0] = sc[0][0][1] = -INFINITY;
            constexpr float SCL = 0.22360679774997896f * 1.4426950408889634f;
#pragma unroll
            for (int b = 0; b < 2; b++) {
              l[b][0] = m0 ? sc[b][0][0] : sc[b][1][0]; l[b][1] = m1 ? sc[b][0][1] : sc[b][1][1];
              l[b][2] = m0 ? sc[b][1][2] : sc[b][2][2]; l[b][3] = m1 ? sc[b][1][3] : sc[b][2][3];
              xa[b] = fmaxf(l[b][0], l[b][1]); xb[b] = fmaxf(l[b][2], l[b][3]);
            }
#pragma unroll
            for (int d = 1; d < 4; d *= 2)
#pragma unroll
              for (int b = 0; b < 2; b++) { xa[b] = fmaxf(xa[b], __shfl_xor_sync(~0u, xa[b], d)); xb[b] = fmaxf(xb[b], __shfl_xor_sync(~0u, xb[b], d)); }
#pragma unroll
            for (int b = 0; b < 2; b++) {
              xa[b] *= SCL; xb[b] *= SCL;
#pragma unroll
              for (int i = 0; i < 4; i++) l[b][i] = ex2(fmaf(l[b][i], SCL, -(i < 2 ? xa[b] : xb[b])));
              xa[b] = l[b][0] + l[b][1]; xb[b] = l[b][2] + l[b][3];
            }
#pragma unroll
            for (int d = 1; d < 4; d *= 2)
#pragma unroll
              for (int b = 0; b < 2; b++) { xa[b] += __shfl_xor_sync(~0u, xa[b], d); xb[b] += __shfl_xor_sync(~0u, xb[b], d); }
#pragma unroll
            for (int b = 0; b < 2; b++) {
              xa[b] = gt[2 * b] * rcp(xa[b]); xb[b] = gt[2 * b + 1] * rcp(xb[b]);
              pa[b] = pack2(l[b][0] * xa[b], l[b][1] * xa[b]); pb[b] = pack2(l[b][2] * xb[b], l[b][3] * xb[b]);
              const uint32_t pf[4] = {pa[b] & mk, 0u, pa[b] & ~mk, pb[b] & mk};
#pragma unroll
              for (int n = 0; n < 3; n++) mma16816(o[b][n], pf, vf[n][2 * b], vf[n][2 * b + 1]);
            }
#pragma unroll
            for (int b = 0; b < 2; b++)
#pragma unroll
              for (int n = 0; n < 3; n++) mma1688(o[b][n], 0u, pb[b] & ~mk, frag(vf, n, 2 * b + 2));
#pragma unroll
            for (int n = 0; n < 2; n++)
              stsm4(sb + sq * STG + (n ? a1 : a0), pack2(o[0][n][0], o[0][n][1]), pack2(o[0][n][2], o[0][n][3]), pack2(o[1][n][0], o[1][n][1]), pack2(o[1][n][2], o[1][n][3]));
#pragma unroll
            for (int e = 0; e < 4; e++) { const uint32_t v = pack2(o[e >> 1][2][2 * (e & 1)], o[e >> 1][2][2 * (e & 1) + 1]); y2[e] = own || h == 0 ? v : y2[e]; }
          }
          release(sk); release(sv);
          stsm4(sb + sq * STG + aq[2], y2[0], y2[1], y2[2], y2[3]);
          PTR((item & 255) == PT && tid == 32, 3, 12 + j * 2);
          fence_async_smem();
          bar_sync(3, 256);
          PTR((item & 255) == PT && tid == 32, 3, 13 + j * 2);
          if (g == (j & 1)) push(OP_OB | (sq << 4) | (8 << 8), t * 32, (j & 1) * 10 + (j >> 1) * 5, C_OB + (t >> 1) + 1);
        }
      } else {
        release(st);
        push(OP_END, 0, 0, 0);
        break;
      }
    }
  }
}

typedef CUresult (*EncFn)(CUtensorMap*, CUtensorMapDataType, cuuint32_t, void*, const cuuint64_t*, const cuuint64_t*, const cuuint32_t*,
                          const cuuint32_t*, CUtensorMapInterleave, CUtensorMapSwizzle, CUtensorMapL2promotion, CUtensorMapFloatOOBfill);

void make_map(EncFn enc, CUtensorMap* tm, const void* base, int rank, const cuuint64_t* dims, const cuuint64_t* strides, const cuuint32_t* box,
              CUtensorMapSwizzle sw = CU_TENSOR_MAP_SWIZZLE_128B, CUtensorMapDataType dt = CU_TENSOR_MAP_DATA_TYPE_BFLOAT16) {
  const cuuint32_t es[5] = {1, 1, 1, 1, 1};
  enc(tm, dt, rank, const_cast<void*>(base), dims, strides, box, es, CU_TENSOR_MAP_INTERLEAVE_NONE, sw, CU_TENSOR_MAP_L2_PROMOTION_L2_128B,
      CU_TENSOR_MAP_FLOAT_OOB_FILL_NONE);
}
void map_blk(EncFn enc, CUtensorMap* tm, const void* base, int rows, int cols, int brows, int bblk) {
  const cuuint64_t d[3] = {64, (cuuint64_t)rows, (cuuint64_t)cols / 64}, st[2] = {(cuuint64_t)cols * 2, 128};
  const cuuint32_t b[3] = {64, (cuuint32_t)brows, (cuuint32_t)bblk};
  make_map(enc, tm, base, 3, d, st, b);
}
void map_2d(EncFn enc, CUtensorMap* tm, const void* base, int rows, int cols, int brows, int bcols, CUtensorMapSwizzle sw) {
  const cuuint64_t d[2] = {(cuuint64_t)cols, (cuuint64_t)rows}, st[1] = {(cuuint64_t)cols * 2};
  const cuuint32_t b[2] = {(cuuint32_t)bcols, (cuuint32_t)brows};
  make_map(enc, tm, base, 2, d, st, b, sw);
}

}

extern "C" void kernel_launch(void* const* d_in, const int* in_sizes, int n_in, void* d_out, int out_size) {
  const bf16* x = (const bf16*)d_in[0];
  const bf16* mem0 = (const bf16*)d_in[1];
  const bf16* Wq = (const bf16*)d_in[2];
  const bf16* Wk = (const bf16*)d_in[3];
  const bf16* Wv = (const bf16*)d_in[4];
  const bf16* Wo = (const bf16*)d_in[5];
  const bf16* wqkv = (const bf16*)d_in[8];
  const bf16* wob = (const bf16*)d_in[9];
  const bf16* gate_w = (const bf16*)d_in[10];
  static EncFn enc = nullptr;
  static int aux_grid = 36;
  static void *pR = nullptr, *pK = nullptr, *pV = nullptr, *pO = nullptr, *pQ = nullptr, *pB = nullptr;
  if (!enc) {
    void* fn = nullptr;
    cudaDriverEntryPointQueryResult qr;
    cudaGetDriverEntryPoint("cuTensorMapEncodeTiled", &fn, cudaEnableDefault, &qr);
    enc = (EncFn)fn;
    cudaGetSymbolAddress(&pR, g_red);
    cudaGetSymbolAddress(&pK, g_K);
    cudaGetSymbolAddress(&pV, g_V);
    cudaGetSymbolAddress(&pO, g_O);
    cudaGetSymbolAddress(&pQ, g_qkv);
    cudaGetSymbolAddress(&pB, g_Ob);
    cudaFuncSetAttribute(rec_kernel, cudaFuncAttributeMaxDynamicSharedMemorySize, R_SMEM_ALLOC);
    cudaFuncSetAttribute(aux_kernel, cudaFuncAttributeMaxDynamicSharedMemorySize, A_SMEM);
    int dev = 0, sms = 132;
    cudaGetDevice(&dev);
    cudaDeviceGetAttribute(&sms, cudaDevAttrMultiProcessorCount, dev);
    aux_grid = sms - 96 < 8 ? 8 : (sms - 96 > 96 ? 96 : sms - 96);
  }
  CUtensorMap tmX, tmK, tmV, tmWq, tmWq2, tmWk, tmWv, tmWo, tmOut;
  map_2d(enc, &tmOut, d_out, S_TOK, DM, 64, 32, CU_TENSOR_MAP_SWIZZLE_64B);
  map_2d(enc, &tmWq, Wq, DM, HD, 144, 64, CU_TENSOR_MAP_SWIZZLE_128B);
  map_2d(enc, &tmWq2, Wq, DM, HD, 32, 64, CU_TENSOR_MAP_SWIZZLE_128B);
  map_2d(enc, &tmWk, Wk, DM, HD, 128, 64, CU_TENSOR_MAP_SWIZZLE_128B);
  map_2d(enc, &tmWv, Wv, DM, HD, 128, 64, CU_TENSOR_MAP_SWIZZLE_128B);
  {
    const cuuint64_t d[3] = {32, HD, 20}, st[2] = {DM * 2, 64};
    const cuuint32_t b[3] = {32, 64, 7};
    make_map(enc, &tmWo, Wo, 3, d, st, b, CU_TENSOR_MAP_SWIZZLE_64B);
  }
  map_blk(enc, &tmX, x, S_TOK, DM, 32, 10);
  map_2d(enc, &tmK, pK, NSEG * LK, HD, LK, 64, CU_TENSOR_MAP_SWIZZLE_128B);
  map_2d(enc, &tmV, pV, NSEG * LK, HD, LK, 64, CU_TENSOR_MAP_SWIZZLE_128B);
  AuxMaps am;
  map_2d(enc, &am.xA, x, S_TOK, DM, 128, 32, CU_TENSOR_MAP_SWIZZLE_64B);
  map_blk(enc, &am.wq, Wq, DM, HD, 32, 6);
  map_blk(enc, &am.wqkv, wqkv, DM, 3 * DM, 32, 6);
  map_blk(enc, &am.wo, Wo, HD, DM, 32, 5);
  map_blk(enc, &am.wob, wob, DM, DM, 32, 5);
  map_blk(enc, &am.k, pK, NSEG * LK, HD, 80, 3);
  map_blk(enc, &am.v, pV, NSEG * LK, HD, 80, 3);
  map_2d(enc, &am.oA, pO, S_TOK, HD, 128, 32, CU_TENSOR_MAP_SWIZZLE_64B);
  map_blk(enc, &am.oS, pO, S_TOK, HD, 64, 1);
  map_2d(enc, &am.obA, pB, S_TOK, DM, 128, 32, CU_TENSOR_MAP_SWIZZLE_64B);
  map_blk(enc, &am.obS, pB, S_TOK / 2, 2 * DM, 32, 5);
  map_blk(enc, &am.qkvS, pQ, S_TOK, 3 * DM, 64, 1);
  map_blk(enc, &am.qkvQ, pQ, S_TOK / 2, 6 * DM, 32, 5);
  map_blk(enc, &am.qkvK, pQ, S_TOK / 2, 6 * DM, 40, 5);
  map_blk(enc, &am.out, d_out, S_TOK, DM, 64, 1);
  rec_kernel<<<96, 256, R_SMEM_ALLOC, cudaStreamPerThread>>>(tmX, tmK, tmV, tmWq, tmWq2, tmWk, tmWv, tmWo, tmOut, mem0, Wq, Wk, Wv, Wo, x, gate_w, (bf16*)d_out,
                                                               (unsigned char*)(((uintptr_t)pR + 0x1fffff) & ~(uintptr_t)0x1fffff));
  cudaLaunchConfig_t cfg = {};
  cfg.gridDim = dim3(aux_grid); cfg.blockDim = dim3(384); cfg.dynamicSmemBytes = A_SMEM; cfg.stream = cudaStreamPerThread;
  cudaLaunchAttribute at[1];
  at[0].id = cudaLaunchAttributeProgrammaticStreamSerialization;
  at[0].val.programmaticStreamSerializationAllowed = 1;
  cfg.attrs = at;
  cfg.numAttrs = 1;
  cudaLaunchKernelEx(&cfg, aux_kernel, am);
}
```
